```python
import torch

def _softmax(x, axis=-1):
    return torch.softmax(x, dim=axis)
def _gelu(x):
    return torch.nn.functional.gelu(x, approximate="tanh")
def _silu(x):
    return torch.nn.functional.silu(x)
def _sigmoid(x):
    return torch.sigmoid(x)
def _layernorm(x, axis=-1, eps=1e-5):
    m = x.mean(dim=axis, keepdim=True)
    v = x.var(dim=axis, keepdim=True, unbiased=False)
    return (x - m) / torch.sqrt(v + eps)
def _scatter_add(tgt, idx, src, axis=0):
    return tgt.clone().index_add_(axis, idx, src)
def _segment_sum(src, seg, n):
    out = torch.zeros((n,) + src.shape[1:], dtype=src.dtype)
    return out.index_add_(0, seg, src)
def _pad(x, pw):
    flat = tuple(v for pair in reversed(pw) for v in pair)
    return torch.nn.functional.pad(x, flat)

kernel_name = 'concat_heads__gqa_block_cached__gqa_block_cached__near_ridge'

def setup_inputs():

    _w = (lambda a: (lambda t: t.to(torch.bfloat16) if t.is_floating_point() else t)(torch.as_tensor(a)))
    def _A_setup():
        B, Sq, D = 8, 64, 576
        Hq, Hkv, Sk, Dh = 32, 16, 512, 128
        assert Hq % Hkv == 0, (Hq, Hkv)
        return {
            "x": _w((lambda *s: torch.randn(*s, dtype=torch.bfloat16) * 0.8)(B, Sq, D)),
            "k_cache": _w((lambda *s: torch.randn(*s, dtype=torch.bfloat16) * 0.8)(B, Hkv, Sk, Dh)),
            "v_cache": _w((lambda *s: torch.randn(*s, dtype=torch.bfloat16) * 0.05)(B, Hkv, Sk, Dh)),
            "wq": _w((lambda *s: torch.randn(*s, dtype=torch.bfloat16) * 0.8)(D, Hq * Dh) * (D ** -0.5)),
            "wo": _w((lambda *s: torch.randn(*s, dtype=torch.bfloat16) * 0.05)(Hq * Dh, D) * ((Hq * Dh) ** -0.5)),
        }
    _A_in = _A_setup()

    def _B_setup():
        B, Sq, D = 8, 64, 576
        Hq, Hkv, Sk, Dh = 32, 16, 512, 128
        assert Hq % Hkv == 0, (Hq, Hkv)
        return {
            "x": _w((lambda *s: torch.randn(*s, dtype=torch.bfloat16) * 0.8)(B, Sq, D)),
            "k_cache": _w((lambda *s: torch.randn(*s, dtype=torch.bfloat16) * 0.8)(B, Hkv, Sk, Dh)),
            "v_cache": _w((lambda *s: torch.randn(*s, dtype=torch.bfloat16) * 0.05)(B, Hkv, Sk, Dh)),
            "wq": _w((lambda *s: torch.randn(*s, dtype=torch.bfloat16) * 0.8)(D, Hq * Dh) * (D ** -0.5)),
            "wo": _w((lambda *s: torch.randn(*s, dtype=torch.bfloat16) * 0.05)(Hq * Dh, D) * ((Hq * Dh) ** -0.5)),
        }
    _B_in = _B_setup()

    return {
        "A_x": _A_in["x"],
        "A_k_cache": _A_in["k_cache"],
        "A_v_cache": _A_in["v_cache"],
        "A_wq": _A_in["wq"],
        "A_wo": _A_in["wo"],
        "B_x": _B_in["x"],
        "B_k_cache": _B_in["k_cache"],
        "B_v_cache": _B_in["v_cache"],
        "B_wq": _B_in["wq"],
        "B_wo": _B_in["wo"],
    }

def reference(A_x, A_k_cache, A_v_cache, A_wq, A_wo, B_x, B_k_cache, B_v_cache, B_wq, B_wo):
    def _A_ref(x, k_cache, v_cache, wq, wo):
        B, Sq, D = x.shape
        Hq, Dh = 32, 128
        Hkv = k_cache.shape[1]
        rep = Hq // Hkv
        q = (lambda x, *d: x.permute(*d))((x @ wq).reshape(B, Sq, Hq, Dh), 0, 2, 1, 3)
        k = (lambda x, n, axis: torch.repeat_interleave(x, n, dim=axis))(k_cache, rep, axis=1)
        v = (lambda x, n, axis: torch.repeat_interleave(x, n, dim=axis))(v_cache, rep, axis=1)
        scores = torch.einsum("bhqd,bhkd->bhqk", q, k) * (Dh ** -0.5)
        p = _softmax(scores, axis=-1)
        o = torch.einsum("bhqk,bhkd->bhqd", p, v)
        return (lambda x, *d: x.permute(*d))(o, 0, 2, 1, 3).reshape(B, Sq, Hq * Dh) @ wo

    def _B_ref(x, k_cache, v_cache, wq, wo):
        B, Sq, D = x.shape
        Hq, Dh = 32, 128
        Hkv = k_cache.shape[1]
        rep = Hq // Hkv
        q = (lambda x, *d: x.permute(*d))((x @ wq).reshape(B, Sq, Hq, Dh), 0, 2, 1, 3)
        k = (lambda x, n, axis: torch.repeat_interleave(x, n, dim=axis))(k_cache, rep, axis=1)
        v = (lambda x, n, axis: torch.repeat_interleave(x, n, dim=axis))(v_cache, rep, axis=1)
        scores = torch.einsum("bhqd,bhkd->bhqk", q, k) * (Dh ** -0.5)
        p = _softmax(scores, axis=-1)
        o = torch.einsum("bhqk,bhkd->bhqd", p, v)
        return (lambda x, *d: x.permute(*d))(o, 0, 2, 1, 3).reshape(B, Sq, Hq * Dh) @ wo

    a = _A_ref(A_x, A_k_cache, A_v_cache, A_wq, A_wo)
    b = _B_ref(B_x, B_k_cache, B_v_cache, B_wq, B_wo)
    return torch.concatenate([a, b], axis=-1)
```

```cpp
#include <cuda_runtime.h>
#include <cuda_bf16.h>
#include <cuda.h>
#include <stdint.h>

namespace {

constexpr int kB = 8, kSq = 64, kD = 576, kHq = 32, kHkv = 16, kSk = 512, kDh = 128;
constexpr int NSTAGE = 5;
constexpr int STAGE_BYTES = 32768;
constexpr int R_BYTES = 65536;
constexpr int SMEM_BYTES = R_BYTES + NSTAGE * STAGE_BYTES + 1024   + 256  ;
constexpr int N_WQ = 18, N_KV = 16, N_WO = 18;
constexpr int PF_DIST = 6;

struct __align__(64) Params {
    CUtensorMap x[2], wq[2], k[2], v[2], wo[2];
    const __nv_bfloat16* wqp[2];
    const __nv_bfloat16* kp[2];
    const __nv_bfloat16* vp[2];
    const __nv_bfloat16* wop[2];
    __nv_bfloat16* out;
};

__device__ float4 g_part[16 * 80 * 8 * 128];
__device__ unsigned int g_cnt[16 * 9 * 8];

__device__ __forceinline__ uint32_t smem_u32(const void* p) { return (uint32_t)__cvta_generic_to_shared(p); }
__device__ __forceinline__ void mbar_init(uint32_t bar, int cnt) {
    asm volatile("mbarrier.init.shared::cta.b64 [%0], %1;" ::"r"(bar), "r"(cnt));
}
__device__ __forceinline__ void mbar_expect_tx(uint32_t bar, uint32_t bytes) {
    asm volatile("mbarrier.arrive.expect_tx.shared::cta.b64 _, [%0], %1;" ::"r"(bar), "r"(bytes) : "memory");
}
__device__ __forceinline__ void mbar_arrive(uint32_t bar) {
    asm volatile("mbarrier.arrive.shared::cta.b64 _, [%0];" ::"r"(bar) : "memory");
}
__device__ __forceinline__ bool mbar_try(uint32_t bar, uint32_t parity) {
    uint32_t ok;
    asm volatile("{\n.reg .pred p;\nmbarrier.try_wait.parity.shared::cta.b64 p, [%1], %2;\nselp.u32 %0, 1, 0, p;\n}\n"
                 : "=r"(ok) : "r"(bar), "r"(parity) : "memory");
    return ok != 0;
}
__device__ __forceinline__ void mbar_wait(uint32_t bar, uint32_t parity) {
    if (mbar_try(bar, parity)) return;
    uint32_t n = 0;
    while (!mbar_try(bar, parity)) {
        if (++n > (1u << 20)) break;
    }
}
__device__ __forceinline__ void tma_2d(uint32_t dst, const CUtensorMap* tm, int c0, int c1, uint32_t bar) {
    asm volatile("cp.async.bulk.tensor.2d.shared::cluster.global.mbarrier::complete_tx::bytes [%0], [%1, {%3, %4}], [%2];"
                 ::"r"(dst), "l"(tm), "r"(bar), "r"(c0), "r"(c1) : "memory");
}
__device__ __forceinline__ void l2_prefetch(const void* p, uint32_t bytes) {
    asm volatile("cp.async.bulk.prefetch.L2.global [%0], %1;" ::"l"(p), "r"(bytes) : "memory");
}
__device__ __forceinline__ void wg_fence() { asm volatile("wgmma.fence.sync.aligned;" ::: "memory"); }
__device__ __forceinline__ void wg_commit() { asm volatile("wgmma.commit_group.sync.aligned;" ::: "memory"); }
template <int N> __device__ __forceinline__ void wg_wait() { asm volatile("wgmma.wait_group.sync.aligned %0;" ::"n"(N) : "memory"); }
template <int N> __device__ __forceinline__ void fence_regs(float (&d)[N]) {
#pragma unroll
    for (int i = 0; i < N; i++) asm volatile("" : "+f"(d[i])::"memory");
}
__device__ __forceinline__ uint64_t mk_desc(uint32_t addr, uint32_t lbo, uint32_t sbo) {
    return (uint64_t)((addr & 0x3FFFF) >> 4) | ((uint64_t)(lbo >> 4) << 16) | ((uint64_t)(sbo >> 4) << 32) | (1ull << 62);
}
__device__ __forceinline__ uint32_t pack_bf16(float a, float b) {
    uint32_t r;
    asm("cvt.rn.bf16x2.f32 %0, %1, %2;" : "=r"(r) : "f"(b), "f"(a));
    return r;
}
__device__ __forceinline__ float ex2(float x) {
    float y;
    asm("ex2.approx.ftz.f32 %0, %1;" : "=f"(y) : "f"(x));
    return y;
}
template <int ID, int N> __device__ __forceinline__ void bar_sync() { asm volatile("bar.sync %0, %1;" ::"n"(ID), "n"(N) : "memory"); }
__device__ __forceinline__ void sts128(uint32_t addr, uint32_t a, uint32_t b, uint32_t c, uint32_t d) {
    asm volatile("st.shared.v4.b32 [%0], {%1,%2,%3,%4};" ::"r"(addr), "r"(a), "r"(b), "r"(c), "r"(d) : "memory");
}
__device__ __forceinline__ void lds128(uint32_t addr, uint32_t (&r)[4]) {
    asm volatile("ld.shared.v4.b32 {%0,%1,%2,%3}, [%4];" : "=r"(r[0]), "=r"(r[1]), "=r"(r[2]), "=r"(r[3]) : "r"(addr) : "memory");
}

__device__ __forceinline__ void wgmma_ss_n256_tb(float (&d)[128], uint64_t da, uint64_t db, int sd) {
    asm volatile("{\n.reg .pred p;\nsetp.ne.b32 p, %130, 0;\n"
        "wgmma.mma_async.sync.aligned.m64n256k16.f32.bf16.bf16 "
        "{%0, %1, %2, %3, %4, %5, %6, %7, %8, %9, %10, %11, %12, %13, %14, %15, %16, %17, %18, %19, %20, %21, %22, %23, %24, %25, %26, %27, %28, %29, %30, %31, %32, %33, %34, %35, %36, %37, %38, %39, %40, %41, %42, %43, %44, %45, %46, %47, %48, %49, %50, %51, %52, %53, %54, %55, %56, %57, %58, %59, %60, %61, %62, %63, %64, %65, %66, %67, %68, %69, %70, %71, %72, %73, %74, %75, %76, %77, %78, %79, %80, %81, %82, %83, %84, %85, %86, %87, %88, %89, %90, %91, %92, %93, %94, %95, %96, %97, %98, %99, %100, %101, %102, %103, %104, %105, %106, %107, %108, %109, %110, %111, %112, %113, %114, %115, %116, %117, %118, %119, %120, %121, %122, %123, %124, %125, %126, %127}, "
        "%128, %129, p, 1, 1, 0, 1;\n}\n"
        : "+f"(d[0]), "+f"(d[1]), "+f"(d[2]), "+f"(d[3]), "+f"(d[4]), "+f"(d[5]), "+f"(d[6]), "+f"(d[7]), "+f"(d[8]), "+f"(d[9]), "+f"(d[10]), "+f"(d[11]), "+f"(d[12]), "+f"(d[13]), "+f"(d[14]), "+f"(d[15]), "+f"(d[16]), "+f"(d[17]), "+f"(d[18]), "+f"(d[19]), "+f"(d[20]), "+f"(d[21]), "+f"(d[22]), "+f"(d[23]), "+f"(d[24]), "+f"(d[25]), "+f"(d[26]), "+f"(d[27]), "+f"(d[28]), "+f"(d[29]), "+f"(d[30]), "+f"(d[31]), "+f"(d[32]), "+f"(d[33]), "+f"(d[34]), "+f"(d[35]), "+f"(d[36]), "+f"(d[37]), "+f"(d[38]), "+f"(d[39]), "+f"(d[40]), "+f"(d[41]), "+f"(d[42]), "+f"(d[43]), "+f"(d[44]), "+f"(d[45]), "+f"(d[46]), "+f"(d[47]), "+f"(d[48]), "+f"(d[49]), "+f"(d[50]), "+f"(d[51]), "+f"(d[52]), "+f"(d[53]), "+f"(d[54]), "+f"(d[55]), "+f"(d[56]), "+f"(d[57]), "+f"(d[58]), "+f"(d[59]), "+f"(d[60]), "+f"(d[61]), "+f"(d[62]), "+f"(d[63]), "+f"(d[64]), "+f"(d[65]), "+f"(d[66]), "+f"(d[67]), "+f"(d[68]), "+f"(d[69]), "+f"(d[70]), "+f"(d[71]), "+f"(d[72]), "+f"(d[73]), "+f"(d[74]), "+f"(d[75]), "+f"(d[76]), "+f"(d[77]), "+f"(d[78]), "+f"(d[79]), "+f"(d[80]), "+f"(d[81]), "+f"(d[82]), "+f"(d[83]), "+f"(d[84]), "+f"(d[85]), "+f"(d[86]), "+f"(d[87]), "+f"(d[88]), "+f"(d[89]), "+f"(d[90]), "+f"(d[91]), "+f"(d[92]), "+f"(d[93]), "+f"(d[94]), "+f"(d[95]), "+f"(d[96]), "+f"(d[97]), "+f"(d[98]), "+f"(d[99]), "+f"(d[100]), "+f"(d[101]), "+f"(d[102]), "+f"(d[103]), "+f"(d[104]), "+f"(d[105]), "+f"(d[106]), "+f"(d[107]), "+f"(d[108]), "+f"(d[109]), "+f"(d[110]), "+f"(d[111]), "+f"(d[112]), "+f"(d[113]), "+f"(d[114]), "+f"(d[115]), "+f"(d[116]), "+f"(d[117]), "+f"(d[118]), "+f"(d[119]), "+f"(d[120]), "+f"(d[121]), "+f"(d[122]), "+f"(d[123]), "+f"(d[124]), "+f"(d[125]), "+f"(d[126]), "+f"(d[127])
        : "l"(da), "l"(db), "r"(sd));
}
__device__ __forceinline__ void wgmma_rs_n128(float (&d)[64], uint32_t a0, uint32_t a1, uint32_t a2, uint32_t a3, uint64_t db, int sd) {
    asm volatile("{\n.reg .pred p;\nsetp.ne.b32 p, %69, 0;\n"
        "wgmma.mma_async.sync.aligned.m64n128k16.f32.bf16.bf16 "
        "{%0, %1, %2, %3, %4, %5, %6, %7, %8, %9, %10, %11, %12, %13, %14, %15, %16, %17, %18, %19, %20, %21, %22, %23, %24, %25, %26, %27, %28, %29, %30, %31, %32, %33, %34, %35, %36, %37, %38, %39, %40, %41, %42, %43, %44, %45, %46, %47, %48, %49, %50, %51, %52, %53, %54, %55, %56, %57, %58, %59, %60, %61, %62, %63}, "
        "{%64, %65, %66, %67}, %68, p, 1, 1, 0;\n}\n"
        : "+f"(d[0]), "+f"(d[1]), "+f"(d[2]), "+f"(d[3]), "+f"(d[4]), "+f"(d[5]), "+f"(d[6]), "+f"(d[7]), "+f"(d[8]), "+f"(d[9]), "+f"(d[10]), "+f"(d[11]), "+f"(d[12]), "+f"(d[13]), "+f"(d[14]), "+f"(d[15]), "+f"(d[16]), "+f"(d[17]), "+f"(d[18]), "+f"(d[19]), "+f"(d[20]), "+f"(d[21]), "+f"(d[22]), "+f"(d[23]), "+f"(d[24]), "+f"(d[25]), "+f"(d[26]), "+f"(d[27]), "+f"(d[28]), "+f"(d[29]), "+f"(d[30]), "+f"(d[31]), "+f"(d[32]), "+f"(d[33]), "+f"(d[34]), "+f"(d[35]), "+f"(d[36]), "+f"(d[37]), "+f"(d[38]), "+f"(d[39]), "+f"(d[40]), "+f"(d[41]), "+f"(d[42]), "+f"(d[43]), "+f"(d[44]), "+f"(d[45]), "+f"(d[46]), "+f"(d[47]), "+f"(d[48]), "+f"(d[49]), "+f"(d[50]), "+f"(d[51]), "+f"(d[52]), "+f"(d[53]), "+f"(d[54]), "+f"(d[55]), "+f"(d[56]), "+f"(d[57]), "+f"(d[58]), "+f"(d[59]), "+f"(d[60]), "+f"(d[61]), "+f"(d[62]), "+f"(d[63])
        : "r"(a0), "r"(a1), "r"(a2), "r"(a3), "l"(db), "r"(sd));
}
__device__ __forceinline__ void wgmma_rs_n128_tb(float (&d)[64], uint32_t a0, uint32_t a1, uint32_t a2, uint32_t a3, uint64_t db, int sd) {
    asm volatile("{\n.reg .pred p;\nsetp.ne.b32 p, %69, 0;\n"
        "wgmma.mma_async.sync.aligned.m64n128k16.f32.bf16.bf16 "
        "{%0, %1, %2, %3, %4, %5, %6, %7, %8, %9, %10, %11, %12, %13, %14, %15, %16, %17, %18, %19, %20, %21, %22, %23, %24, %25, %26, %27, %28, %29, %30, %31, %32, %33, %34, %35, %36, %37, %38, %39, %40, %41, %42, %43, %44, %45, %46, %47, %48, %49, %50, %51, %52, %53, %54, %55, %56, %57, %58, %59, %60, %61, %62, %63}, "
        "{%64, %65, %66, %67}, %68, p, 1, 1, 1;\n}\n"
        : "+f"(d[0]), "+f"(d[1]), "+f"(d[2]), "+f"(d[3]), "+f"(d[4]), "+f"(d[5]), "+f"(d[6]), "+f"(d[7]), "+f"(d[8]), "+f"(d[9]), "+f"(d[10]), "+f"(d[11]), "+f"(d[12]), "+f"(d[13]), "+f"(d[14]), "+f"(d[15]), "+f"(d[16]), "+f"(d[17]), "+f"(d[18]), "+f"(d[19]), "+f"(d[20]), "+f"(d[21]), "+f"(d[22]), "+f"(d[23]), "+f"(d[24]), "+f"(d[25]), "+f"(d[26]), "+f"(d[27]), "+f"(d[28]), "+f"(d[29]), "+f"(d[30]), "+f"(d[31]), "+f"(d[32]), "+f"(d[33]), "+f"(d[34]), "+f"(d[35]), "+f"(d[36]), "+f"(d[37]), "+f"(d[38]), "+f"(d[39]), "+f"(d[40]), "+f"(d[41]), "+f"(d[42]), "+f"(d[43]), "+f"(d[44]), "+f"(d[45]), "+f"(d[46]), "+f"(d[47]), "+f"(d[48]), "+f"(d[49]), "+f"(d[50]), "+f"(d[51]), "+f"(d[52]), "+f"(d[53]), "+f"(d[54]), "+f"(d[55]), "+f"(d[56]), "+f"(d[57]), "+f"(d[58]), "+f"(d[59]), "+f"(d[60]), "+f"(d[61]), "+f"(d[62]), "+f"(d[63])
        : "r"(a0), "r"(a1), "r"(a2), "r"(a3), "l"(db), "r"(sd));
}
__device__ __forceinline__ void wgmma_rs_n64_tb(float (&d)[32], uint32_t a0, uint32_t a1, uint32_t a2, uint32_t a3, uint64_t db, int sd) {
    asm volatile("{\n.reg .pred p;\nsetp.ne.b32 p, %37, 0;\n"
        "wgmma.mma_async.sync.aligned.m64n64k16.f32.bf16.bf16 "
        "{%0, %1, %2, %3, %4, %5, %6, %7, %8, %9, %10, %11, %12, %13, %14, %15, %16, %17, %18, %19, %20, %21, %22, %23, %24, %25, %26, %27, %28, %29, %30, %31}, "
        "{%32, %33, %34, %35}, %36, p, 1, 1, 1;\n}\n"
        : "+f"(d[0]), "+f"(d[1]), "+f"(d[2]), "+f"(d[3]), "+f"(d[4]), "+f"(d[5]), "+f"(d[6]), "+f"(d[7]), "+f"(d[8]), "+f"(d[9]), "+f"(d[10]), "+f"(d[11]), "+f"(d[12]), "+f"(d[13]), "+f"(d[14]), "+f"(d[15]), "+f"(d[16]), "+f"(d[17]), "+f"(d[18]), "+f"(d[19]), "+f"(d[20]), "+f"(d[21]), "+f"(d[22]), "+f"(d[23]), "+f"(d[24]), "+f"(d[25]), "+f"(d[26]), "+f"(d[27]), "+f"(d[28]), "+f"(d[29]), "+f"(d[30]), "+f"(d[31])
        : "r"(a0), "r"(a1), "r"(a2), "r"(a3), "l"(db), "r"(sd));
}


__global__ void __launch_bounds__(384, 1) fused_gqa_kernel(const __grid_constant__ Params P) {
    extern __shared__ uint8_t smem_raw[];
    const uint32_t base = (smem_u32(smem_raw) + 1023u) & ~1023u;
    const uint32_t smR = base;
    const uint32_t smS = base + R_BYTES;
    const uint32_t bars = smS + NSTAGE * STAGE_BYTES;
    const int tid = threadIdx.x;
    const int wid = __shfl_sync(0xffffffffu, tid >> 5, 0);
    const int lane = tid & 31;

    const int cta = blockIdx.x;
    const int blk = cta >> 6;
    const int hp = (cta >> 3) & 7;
    const int b = cta & 7;
    const int grp = blk * 8 + b;

    if (tid == 0) {
        for (int i = 0; i < NSTAGE; i++) {
            mbar_init(bars + 8 * i, 1);
            mbar_init(bars + 8 * (NSTAGE + i), 8);
        }
        asm volatile("fence.mbarrier_init.release.cluster;" ::: "memory");
        asm volatile("fence.proxy.async.shared::cta;" ::: "memory");
    }
    __syncthreads();

    if (wid >= 8) {
        asm volatile("setmaxnreg.dec.sync.aligned.u32 40;");
        const char* kbase = (const char*)(P.kp[blk] + (size_t)(b * kHkv + hp * 2) * kSk * kDh);
        const char* vbase = (const char*)(P.vp[blk] + (size_t)(b * kHkv + hp * 2) * kSk * kDh);
        if (wid == 9) {
            const char* wqs = (const char*)(P.wqp[blk] + hp * 512);
            for (int r = lane; r < 72; r += 32) l2_prefetch(wqs + (size_t)(b * 72 + r) * 8192, 1024);
            if (lane < PF_DIST) {
                int i = lane;
                const char* p = ((i & 1) ? vbase : kbase) + (size_t)(i >> 1) * 32768;
                l2_prefetch(p, 32768);
            }
        } else if (wid == 8 && lane == 0) {
            int slot = 0, ph = 1;
            for (int s = 0; s < N_WQ; s++) {
                const uint32_t fb = bars + 8 * slot;
                mbar_wait(bars + 8 * (NSTAGE + slot), ph);
                const uint32_t dst = smS + slot * STAGE_BYTES;
                mbar_expect_tx(fb, (s & 1) ? STAGE_BYTES : STAGE_BYTES + 8192);
                if (!(s & 1)) tma_2d(smR + ((s >> 1) & 7) * 8192, &P.x[blk], (s >> 1) * 64, b * 64, fb);
#pragma unroll
                for (int p = 0; p < 8; p++) {
                    const int w = p >> 2, j = (p >> 1) & 1, glo = p & 1;
                    tma_2d(dst + p * 4096, &P.wq[blk], hp * 512 + (j * 4 + w * 2 + glo) * 64, s * 32, fb);
                }
                if (++slot == NSTAGE) { slot = 0; ph ^= 1; }
            }
            const char* wos = (const char*)(P.wop[blk] + (size_t)hp * 512 * kD) + (size_t)b * 73728;
            for (int i = 0; i < N_KV; i++) {
                const uint32_t fb = bars + 8 * slot;
                mbar_wait(bars + 8 * (NSTAGE + slot), ph);
                const uint32_t dst = smS + slot * STAGE_BYTES;
                mbar_expect_tx(fb, STAGE_BYTES);
                const int row = (b * kHkv + hp * 2) * kSk + (i >> 1) * 128;
                const CUtensorMap* tm = (i & 1) ? &P.v[blk] : &P.k[blk];
                tma_2d(dst, tm, 0, row, fb);
                tma_2d(dst + 16384, tm, 64, row, fb);
                const int n = i + PF_DIST;
                if (n < N_KV) {
                    const char* p = ((n & 1) ? vbase : kbase) + (size_t)(n >> 1) * 32768;
                    l2_prefetch(p, 32768);
                } else if (n < N_KV + 3) {
                    l2_prefetch(wos + (n - N_KV) * 24576, 24576);
                }
                if (++slot == NSTAGE) { slot = 0; ph ^= 1; }
            }
            for (int i = 0; i < N_WO; i++) {
                const uint32_t fb = bars + 8 * slot;
                mbar_wait(bars + 8 * (NSTAGE + slot), ph);
                const uint32_t dst = smS + slot * STAGE_BYTES;
                mbar_expect_tx(fb, STAGE_BYTES);
                if (i < 16) {
                    tma_2d(dst, &P.wo[blk], (i >> 2) * 128, hp * 512 + (i & 3) * 128, fb);
                    tma_2d(dst + 16384, &P.wo[blk], (i >> 2) * 128 + 64, hp * 512 + ((i + 2) & 3) * 128, fb);
                } else {
                    const int row = hp * 512 + (i - 16) * 128;
                    tma_2d(dst, &P.wo[blk], 512, row, fb);
                    tma_2d(dst + 16384, &P.wo[blk], 512, row + 256, fb);
                }
                if (++slot == NSTAGE) { slot = 0; ph ^= 1; }
            }
        }
        __syncwarp();
        const int t = tid - 256;
        __nv_bfloat16* orow = P.out + (size_t)(b * 64 + (t >> 5) * 16 + (lane >> 2)) * (2 * kD) + blk * kD + hp * 8 + (lane & 3) * 2;
        for (int c = 0; c < 9; c++) {
            const unsigned need = (c < 8) ? 8u : 16u;
            if (t == 0) {
                unsigned* cp = &g_cnt[(grp * 9 + c) * 8 + hp];
                unsigned v, n = 0;
                while (true) {
                    asm volatile("ld.acquire.gpu.global.u32 %0, [%1];" : "=r"(v) : "l"(cp) : "memory");
                    if (v >= need) break;
                    if (++n > (1u << 21)) break;
                    __nanosleep(40);
                }
                *cp = 0;
            }
            bar_sync<3, 128>();
            const float4* src = g_part + ((size_t)(grp * 80 + c * 8) * 8 + hp) * 128 + t;
            float4 v[8];
#pragma unroll
            for (int i = 0; i < 8; i++) v[i] = __ldcg(src + (size_t)i * 1024);
            float4 a = v[0];
#pragma unroll
            for (int i = 1; i < 8; i++) { a.x += v[i].x; a.y += v[i].y; a.z += v[i].z; a.w += v[i].w; }
            if (c == 8) {
#pragma unroll
                for (int i = 0; i < 8; i++) v[i] = __ldcg(src + (size_t)(8 + i) * 1024);
#pragma unroll
                for (int i = 0; i < 8; i++) { a.x += v[i].x; a.y += v[i].y; a.z += v[i].z; a.w += v[i].w; }
            }
            *(uint32_t*)(orow + c * 64) = pack_bf16(a.x, a.y);
            *(uint32_t*)(orow + c * 64 + 8 * 2 * kD) = pack_bf16(a.z, a.w);
        }
    } else {
        asm volatile("setmaxnreg.inc.sync.aligned.u32 232;");
        const int w = wid >> 2;
        const int t = tid & 127;
        int slot = 0, ph = 0;
        uint32_t qf[8][4];
        const uint32_t stash = smR + (1 + w) * 16384 + t * 16;
        {
            float acc[128];
            int pslot = 0;
            for (int s = 0; s < N_WQ; s++) {
                mbar_wait(bars + 8 * slot, ph);
                const uint64_t da = mk_desc(smR + ((s >> 1) & 7) * 8192 + (s & 1) * 64, 16, 1024);
                const uint64_t db = mk_desc(smS + slot * STAGE_BYTES + w * 16384, 4096, 1024);
                wg_fence();
                wgmma_ss_n256_tb(acc, da, db, s != 0);
                wgmma_ss_n256_tb(acc, da + 2, db + 128, 1);
                wg_commit();
                if (s > 0) {
                    wg_wait<1>();
                    if (lane == 0) mbar_arrive(bars + 8 * (NSTAGE + pslot));
                }
                pslot = slot;
                if (++slot == NSTAGE) { slot = 0; ph ^= 1; }
            }
            wg_wait<0>();
            if (lane == 0) mbar_arrive(bars + 8 * (NSTAGE + pslot));
            fence_regs(acc);
#pragma unroll
            for (int kk = 0; kk < 8; kk++) {
#pragma unroll
                for (int i = 0; i < 4; i++) qf[kk][i] = pack_bf16(acc[8 * kk + 2 * i], acc[8 * kk + 2 * i + 1]);
                sts128(stash + kk * 2048,
                       pack_bf16(acc[64 + 8 * kk + 0], acc[64 + 8 * kk + 1]), pack_bf16(acc[64 + 8 * kk + 2], acc[64 + 8 * kk + 3]),
                       pack_bf16(acc[64 + 8 * kk + 4], acc[64 + 8 * kk + 5]), pack_bf16(acc[64 + 8 * kk + 6], acc[64 + 8 * kk + 7]));
            }
        }
        const float sc = 0.08838834764831845f * 1.4426950408889634f;
#pragma unroll 1
        for (int u = 0; u < 2; u++) {
            if (u == 1) {
#pragma unroll
                for (int kk = 0; kk < 8; kk++) lds128(stash + kk * 2048, qf[kk]);
            }
            float o[64];
            float m0 = -INFINITY, m1 = -INFINITY, l0 = 0.f, l1 = 0.f;
#pragma unroll 1
            for (int tt = 0; tt < 4; tt++) {
                float s[64];
                mbar_wait(bars + 8 * slot, ph);
                {
                    const uint64_t db = mk_desc(smS + slot * STAGE_BYTES, 16, 1024);
                    wg_fence();
#pragma unroll
                    for (int kk = 0; kk < 8; kk++)
                        wgmma_rs_n128(s, qf[kk][0], qf[kk][1], qf[kk][2], qf[kk][3], db + (kk >> 2) * 1024 + (kk & 3) * 2, kk != 0);
                    wg_commit();
                    wg_wait<0>();
                    fence_regs(s);
                }
                if (lane == 0) mbar_arrive(bars + 8 * (NSTAGE + slot));
                if (++slot == NSTAGE) { slot = 0; ph ^= 1; }
                float mx0 = s[0], mx1 = s[2];
#pragma unroll
                for (int j = 0; j < 16; j++) {
                    mx0 = fmaxf(mx0, fmaxf(s[4 * j], s[4 * j + 1]));
                    mx1 = fmaxf(mx1, fmaxf(s[4 * j + 2], s[4 * j + 3]));
                }
                mx0 = fmaxf(mx0, __shfl_xor_sync(0xffffffffu, mx0, 1));
                mx1 = fmaxf(mx1, __shfl_xor_sync(0xffffffffu, mx1, 1));
                mx0 = fmaxf(mx0, __shfl_xor_sync(0xffffffffu, mx0, 2));
                mx1 = fmaxf(mx1, __shfl_xor_sync(0xffffffffu, mx1, 2));
                const float mn0 = fmaxf(m0, mx0), mn1 = fmaxf(m1, mx1);
                const float al0 = ex2((m0 - mn0) * sc), al1 = ex2((m1 - mn1) * sc);
                m0 = mn0; m1 = mn1;
                const float ms0 = mn0 * sc, ms1 = mn1 * sc;
                uint32_t pf[8][4];
                float rs0 = 0.f, rs1 = 0.f;
#pragma unroll
                for (int j = 0; j < 16; j++) {
                    const float p0 = ex2(fmaf(s[4 * j], sc, -ms0)), p1 = ex2(fmaf(s[4 * j + 1], sc, -ms0));
                    const float p2 = ex2(fmaf(s[4 * j + 2], sc, -ms1)), p3 = ex2(fmaf(s[4 * j + 3], sc, -ms1));
                    rs0 += p0 + p1; rs1 += p2 + p3;
                    pf[j >> 1][(j & 1) * 2] = pack_bf16(p0, p1);
                    pf[j >> 1][(j & 1) * 2 + 1] = pack_bf16(p2, p3);
                }
                l0 = l0 * al0 + rs0; l1 = l1 * al1 + rs1;
                if (tt > 0) {
#pragma unroll
                    for (int j = 0; j < 16; j++) { o[4 * j] *= al0; o[4 * j + 1] *= al0; o[4 * j + 2] *= al1; o[4 * j + 3] *= al1; }
                }
                mbar_wait(bars + 8 * slot, ph);
                {
                    const uint64_t db = mk_desc(smS + slot * STAGE_BYTES, 16384, 1024);
                    wg_fence();
#pragma unroll
                    for (int kk = 0; kk < 8; kk++)
                        wgmma_rs_n128_tb(o, pf[kk][0], pf[kk][1], pf[kk][2], pf[kk][3], db + kk * 128, (tt | kk) != 0);
                    wg_commit();
                    wg_wait<0>();
                    fence_regs(o);
                }
                if (lane == 0) mbar_arrive(bars + 8 * (NSTAGE + slot));
                if (++slot == NSTAGE) { slot = 0; ph ^= 1; }
            }
            l0 += __shfl_xor_sync(0xffffffffu, l0, 1);
            l1 += __shfl_xor_sync(0xffffffffu, l1, 1);
            l0 += __shfl_xor_sync(0xffffffffu, l0, 2);
            l1 += __shfl_xor_sync(0xffffffffu, l1, 2);
            const float i0 = 1.f / l0, i1 = 1.f / l1;
            const uint32_t zone = smR + ((u == 0) ? (w ? 3 : 0) : (w ? 2 : 1)) * 16384 + t * 16;
#pragma unroll
            for (int kk = 0; kk < 8; kk++)
                sts128(zone + kk * 2048,
                       pack_bf16(o[8 * kk + 0] * i0, o[8 * kk + 1] * i0), pack_bf16(o[8 * kk + 2] * i1, o[8 * kk + 3] * i1),
                       pack_bf16(o[8 * kk + 4] * i0, o[8 * kk + 5] * i0), pack_bf16(o[8 * kk + 6] * i1, o[8 * kk + 7] * i1));
        }
        bar_sync<4, 256>();
        uint32_t af[32][4];
#pragma unroll
        for (int hh = 0; hh < 4; hh++) {
            const int h2 = (hh + 2 * w) & 3;
            const int z = (0x2130 >> (h2 * 4)) & 3;
#pragma unroll
            for (int kk = 0; kk < 8; kk++) lds128(smR + z * 16384 + kk * 2048 + t * 16, af[hh * 8 + kk]);
        }
#pragma unroll 1
        for (int cp = 0; cp < 5; cp++) {
            float acc[32];
            if (cp < 4) {
#pragma unroll
                for (int kq = 0; kq < 4; kq++) {
                    mbar_wait(bars + 8 * slot, ph);
                    const uint64_t db = mk_desc(smS + slot * STAGE_BYTES + w * 16384, 16384, 1024);
                    wg_fence();
#pragma unroll
                    for (int kk = 0; kk < 8; kk++)
                        wgmma_rs_n64_tb(acc, af[kq * 8 + kk][0], af[kq * 8 + kk][1], af[kq * 8 + kk][2], af[kq * 8 + kk][3], db + kk * 128, (kq | kk) != 0);
                    wg_commit();
                    wg_wait<0>();
                    if (lane == 0) mbar_arrive(bars + 8 * (NSTAGE + slot));
                    if (++slot == NSTAGE) { slot = 0; ph ^= 1; }
                }
            } else {
#pragma unroll
                for (int kq = 0; kq < 2; kq++) {
                    mbar_wait(bars + 8 * slot, ph);
                    const uint64_t db = mk_desc(smS + slot * STAGE_BYTES + w * 16384, 16384, 1024);
                    wg_fence();
#pragma unroll
                    for (int kk = 0; kk < 8; kk++)
                        wgmma_rs_n64_tb(acc, af[kq * 8 + kk][0], af[kq * 8 + kk][1], af[kq * 8 + kk][2], af[kq * 8 + kk][3], db + kk * 128, (kq | kk) != 0);
                    wg_commit();
                    wg_wait<0>();
                    if (lane == 0) mbar_arrive(bars + 8 * (NSTAGE + slot));
                    if (++slot == NSTAGE) { slot = 0; ph ^= 1; }
                }
            }
            fence_regs(acc);
            const int c = (cp < 4) ? (2 * cp + w) : 8;
            const int pslot = (cp < 4) ? (c * 8 + hp) : (64 + hp * 2 + w);
            float4* dst = g_part + (size_t)(grp * 80 + pslot) * 1024 + t;
#pragma unroll
            for (int j = 0; j < 8; j++) __stcg(dst + j * 128, make_float4(acc[4 * j], acc[4 * j + 1], acc[4 * j + 2], acc[4 * j + 3]));
            if (w == 0) bar_sync<1, 128>(); else bar_sync<2, 128>();
            if (t < 8) {
                asm volatile("red.release.gpu.global.add.u32 [%0], 1;" ::"l"(&g_cnt[(grp * 9 + c) * 8 + t]) : "memory");
            }
        }
    }
}

typedef CUresult (*EncodeFn)(CUtensorMap*, CUtensorMapDataType, cuuint32_t, void*, const cuuint64_t*, const cuuint64_t*,
                             const cuuint32_t*, const cuuint32_t*, CUtensorMapInterleave, CUtensorMapSwizzle,
                             CUtensorMapL2promotion, CUtensorMapFloatOOBfill);

void make_map(EncodeFn fn, CUtensorMap* m, const void* ptr, uint64_t cols, uint64_t rows, uint32_t box_rows) {
    cuuint64_t dims[2] = {cols, rows};
    cuuint64_t strides[1] = {cols * 2};
    cuuint32_t box[2] = {64, box_rows};
    cuuint32_t es[2] = {1, 1};
    fn(m, CU_TENSOR_MAP_DATA_TYPE_BFLOAT16, 2, const_cast<void*>(ptr), dims, strides, box, es, CU_TENSOR_MAP_INTERLEAVE_NONE,
       CU_TENSOR_MAP_SWIZZLE_128B, CU_TENSOR_MAP_L2_PROMOTION_L2_256B, CU_TENSOR_MAP_FLOAT_OOB_FILL_NONE);
}

}

extern "C" void kernel_launch(void* const* d_in, const int* in_sizes, int n_in, void* d_out, int out_size) {
    static EncodeFn enc = nullptr;
    if (!enc) {
        void* fn = nullptr;
        cudaDriverEntryPointQueryResult st;
        cudaGetDriverEntryPoint("cuTensorMapEncodeTiled", &fn, cudaEnableDefault, &st);
        enc = (EncodeFn)fn;
        cudaFuncSetAttribute(fused_gqa_kernel, cudaFuncAttributeMaxDynamicSharedMemorySize, SMEM_BYTES);
    }
    Params P;
    for (int blk = 0; blk < 2; blk++) {
        const void* x = d_in[blk * 5 + 0];
        const void* k = d_in[blk * 5 + 1];
        const void* v = d_in[blk * 5 + 2];
        const void* wq = d_in[blk * 5 + 3];
        const void* wo = d_in[blk * 5 + 4];
        make_map(enc, &P.x[blk], x, kD, kB * kSq, 64);
        make_map(enc, &P.wq[blk], wq, kHq * kDh, kD, 32);
        make_map(enc, &P.k[blk], k, kDh, (uint64_t)kB * kHkv * kSk, 128);
        make_map(enc, &P.v[blk], v, kDh, (uint64_t)kB * kHkv * kSk, 128);
        make_map(enc, &P.wo[blk], wo, kD, kHq * kDh, 128);
        P.wqp[blk] = (const __nv_bfloat16*)wq;
        P.kp[blk] = (const __nv_bfloat16*)k;
        P.vp[blk] = (const __nv_bfloat16*)v;
        P.wop[blk] = (const __nv_bfloat16*)wo;
    }
    P.out = (__nv_bfloat16*)d_out;
    fused_gqa_kernel<<<128, 384, SMEM_BYTES>>>(P);
}
```

```cpp
#include <cuda_runtime.h>
#include <cuda_bf16.h>
#include <cuda.h>
#include <stdint.h>

namespace {

constexpr int kB = 8, kSq = 64, kD = 576, kHq = 32, kHkv = 16, kSk = 512, kDh = 128;
constexpr int NSTAGE = 5;
constexpr int STAGE_BYTES = 32768;
constexpr int R_BYTES = 65536;
constexpr int SMEM_BYTES = R_BYTES + NSTAGE * STAGE_BYTES + 1024   + 256  ;
constexpr int N_WQ = 18, N_KV = 16, N_WO = 18;
#define PF_DIST_V 4
#define PF_WQ 1
constexpr int PF_DIST = PF_DIST_V;

struct __align__(64) Params {
    CUtensorMap x[2], wq[2], k[2], v[2], wo[2];
    const __nv_bfloat16* wqp[2];
    const __nv_bfloat16* kp[2];
    const __nv_bfloat16* vp[2];
    const __nv_bfloat16* wop[2];
    __nv_bfloat16* out;
};

__device__ float4 g_part[16 * 80 * 8 * 128];
__device__ unsigned int g_cnt[16 * 9 * 32];
#define TS(k) do {} while (0)

__device__ __forceinline__ uint32_t smem_u32(const void* p) { return (uint32_t)__cvta_generic_to_shared(p); }
__device__ __forceinline__ void mbar_init(uint32_t bar, int cnt) {
    asm volatile("mbarrier.init.shared::cta.b64 [%0], %1;" ::"r"(bar), "r"(cnt));
}
__device__ __forceinline__ void mbar_expect_tx(uint32_t bar, uint32_t bytes) {
    asm volatile("mbarrier.arrive.expect_tx.shared::cta.b64 _, [%0], %1;" ::"r"(bar), "r"(bytes) : "memory");
}
__device__ __forceinline__ void mbar_arrive(uint32_t bar) {
    asm volatile("mbarrier.arrive.shared::cta.b64 _, [%0];" ::"r"(bar) : "memory");
}
__device__ __forceinline__ bool mbar_try(uint32_t bar, uint32_t parity) {
    uint32_t ok;
    asm volatile("{\n.reg .pred p;\nmbarrier.try_wait.parity.shared::cta.b64 p, [%1], %2;\nselp.u32 %0, 1, 0, p;\n}\n"
                 : "=r"(ok) : "r"(bar), "r"(parity) : "memory");
    return ok != 0;
}
__device__ __forceinline__ void mbar_wait(uint32_t bar, uint32_t parity) {
    if (mbar_try(bar, parity)) return;
    uint32_t n = 0;
    while (!mbar_try(bar, parity)) {
        if (++n > (1u << 20)) break;
    }
}
__device__ __forceinline__ void tma_2d(uint32_t dst, const CUtensorMap* tm, int c0, int c1, uint32_t bar) {
    asm volatile("cp.async.bulk.tensor.2d.shared::cluster.global.mbarrier::complete_tx::bytes [%0], [%1, {%3, %4}], [%2];"
                 ::"r"(dst), "l"(tm), "r"(bar), "r"(c0), "r"(c1) : "memory");
}
__device__ __forceinline__ void l2_prefetch(const void* p, uint32_t bytes) {
    asm volatile("cp.async.bulk.prefetch.L2.global [%0], %1;" ::"l"(p), "r"(bytes) : "memory");
}
__device__ __forceinline__ uint32_t l2_touch(const void* p) {
    uint32_t v;
    asm volatile("ld.global.L2::256B.b32 %0, [%1];" : "=r"(v) : "l"(p) : "memory");
    return v;
}
__device__ __forceinline__ void wg_fence() { asm volatile("wgmma.fence.sync.aligned;" ::: "memory"); }
__device__ __forceinline__ void wg_commit() { asm volatile("wgmma.commit_group.sync.aligned;" ::: "memory"); }
template <int N> __device__ __forceinline__ void wg_wait() { asm volatile("wgmma.wait_group.sync.aligned %0;" ::"n"(N) : "memory"); }
template <int N> __device__ __forceinline__ void fence_regs(float (&d)[N]) {
#pragma unroll
    for (int i = 0; i < N; i++) asm volatile("" : "+f"(d[i])::"memory");
}
__device__ __forceinline__ uint64_t mk_desc(uint32_t addr, uint32_t lbo, uint32_t sbo) {
    return (uint64_t)((addr & 0x3FFFF) >> 4) | ((uint64_t)(lbo >> 4) << 16) | ((uint64_t)(sbo >> 4) << 32) | (1ull << 62);
}
__device__ __forceinline__ uint32_t pack_bf16(float a, float b) {
    uint32_t r;
    asm("cvt.rn.bf16x2.f32 %0, %1, %2;" : "=r"(r) : "f"(b), "f"(a));
    return r;
}
__device__ __forceinline__ float ex2(float x) {
    float y;
    asm("ex2.approx.ftz.f32 %0, %1;" : "=f"(y) : "f"(x));
    return y;
}
template <int ID, int N> __device__ __forceinline__ void bar_sync() { asm volatile("bar.sync %0, %1;" ::"n"(ID), "n"(N) : "memory"); }
__device__ __forceinline__ void sts128(uint32_t addr, uint32_t a, uint32_t b, uint32_t c, uint32_t d) {
    asm volatile("st.shared.v4.b32 [%0], {%1,%2,%3,%4};" ::"r"(addr), "r"(a), "r"(b), "r"(c), "r"(d) : "memory");
}
__device__ __forceinline__ void lds128(uint32_t addr, uint32_t (&r)[4]) {
    asm volatile("ld.shared.v4.b32 {%0,%1,%2,%3}, [%4];" : "=r"(r[0]), "=r"(r[1]), "=r"(r[2]), "=r"(r[3]) : "r"(addr) : "memory");
}

__device__ __forceinline__ void wgmma_ss_n256_tb(float (&d)[128], uint64_t da, uint64_t db, int sd) {
    asm volatile("{\n.reg .pred p;\nsetp.ne.b32 p, %130, 0;\n"
        "wgmma.mma_async.sync.aligned.m64n256k16.f32.bf16.bf16 "
        "{%0, %1, %2, %3, %4, %5, %6, %7, %8, %9, %10, %11, %12, %13, %14, %15, %16, %17, %18, %19, %20, %21, %22, %23, %24, %25, %26, %27, %28, %29, %30, %31, %32, %33, %34, %35, %36, %37, %38, %39, %40, %41, %42, %43, %44, %45, %46, %47, %48, %49, %50, %51, %52, %53, %54, %55, %56, %57, %58, %59, %60, %61, %62, %63, %64, %65, %66, %67, %68, %69, %70, %71, %72, %73, %74, %75, %76, %77, %78, %79, %80, %81, %82, %83, %84, %85, %86, %87, %88, %89, %90, %91, %92, %93, %94, %95, %96, %97, %98, %99, %100, %101, %102, %103, %104, %105, %106, %107, %108, %109, %110, %111, %112, %113, %114, %115, %116, %117, %118, %119, %120, %121, %122, %123, %124, %125, %126, %127}, "
        "%128, %129, p, 1, 1, 0, 1;\n}\n"
        : "+f"(d[0]), "+f"(d[1]), "+f"(d[2]), "+f"(d[3]), "+f"(d[4]), "+f"(d[5]), "+f"(d[6]), "+f"(d[7]), "+f"(d[8]), "+f"(d[9]), "+f"(d[10]), "+f"(d[11]), "+f"(d[12]), "+f"(d[13]), "+f"(d[14]), "+f"(d[15]), "+f"(d[16]), "+f"(d[17]), "+f"(d[18]), "+f"(d[19]), "+f"(d[20]), "+f"(d[21]), "+f"(d[22]), "+f"(d[23]), "+f"(d[24]), "+f"(d[25]), "+f"(d[26]), "+f"(d[27]), "+f"(d[28]), "+f"(d[29]), "+f"(d[30]), "+f"(d[31]), "+f"(d[32]), "+f"(d[33]), "+f"(d[34]), "+f"(d[35]), "+f"(d[36]), "+f"(d[37]), "+f"(d[38]), "+f"(d[39]), "+f"(d[40]), "+f"(d[41]), "+f"(d[42]), "+f"(d[43]), "+f"(d[44]), "+f"(d[45]), "+f"(d[46]), "+f"(d[47]), "+f"(d[48]), "+f"(d[49]), "+f"(d[50]), "+f"(d[51]), "+f"(d[52]), "+f"(d[53]), "+f"(d[54]), "+f"(d[55]), "+f"(d[56]), "+f"(d[57]), "+f"(d[58]), "+f"(d[59]), "+f"(d[60]), "+f"(d[61]), "+f"(d[62]), "+f"(d[63]), "+f"(d[64]), "+f"(d[65]), "+f"(d[66]), "+f"(d[67]), "+f"(d[68]), "+f"(d[69]), "+f"(d[70]), "+f"(d[71]), "+f"(d[72]), "+f"(d[73]), "+f"(d[74]), "+f"(d[75]), "+f"(d[76]), "+f"(d[77]), "+f"(d[78]), "+f"(d[79]), "+f"(d[80]), "+f"(d[81]), "+f"(d[82]), "+f"(d[83]), "+f"(d[84]), "+f"(d[85]), "+f"(d[86]), "+f"(d[87]), "+f"(d[88]), "+f"(d[89]), "+f"(d[90]), "+f"(d[91]), "+f"(d[92]), "+f"(d[93]), "+f"(d[94]), "+f"(d[95]), "+f"(d[96]), "+f"(d[97]), "+f"(d[98]), "+f"(d[99]), "+f"(d[100]), "+f"(d[101]), "+f"(d[102]), "+f"(d[103]), "+f"(d[104]), "+f"(d[105]), "+f"(d[106]), "+f"(d[107]), "+f"(d[108]), "+f"(d[109]), "+f"(d[110]), "+f"(d[111]), "+f"(d[112]), "+f"(d[113]), "+f"(d[114]), "+f"(d[115]), "+f"(d[116]), "+f"(d[117]), "+f"(d[118]), "+f"(d[119]), "+f"(d[120]), "+f"(d[121]), "+f"(d[122]), "+f"(d[123]), "+f"(d[124]), "+f"(d[125]), "+f"(d[126]), "+f"(d[127])
        : "l"(da), "l"(db), "r"(sd));
}
__device__ __forceinline__ void wgmma_rs_n128(float (&d)[64], uint32_t a0, uint32_t a1, uint32_t a2, uint32_t a3, uint64_t db, int sd) {
    asm volatile("{\n.reg .pred p;\nsetp.ne.b32 p, %69, 0;\n"
        "wgmma.mma_async.sync.aligned.m64n128k16.f32.bf16.bf16 "
        "{%0, %1, %2, %3, %4, %5, %6, %7, %8, %9, %10, %11, %12, %13, %14, %15, %16, %17, %18, %19, %20, %21, %22, %23, %24, %25, %26, %27, %28, %29, %30, %31, %32, %33, %34, %35, %36, %37, %38, %39, %40, %41, %42, %43, %44, %45, %46, %47, %48, %49, %50, %51, %52, %53, %54, %55, %56, %57, %58, %59, %60, %61, %62, %63}, "
        "{%64, %65, %66, %67}, %68, p, 1, 1, 0;\n}\n"
        : "+f"(d[0]), "+f"(d[1]), "+f"(d[2]), "+f"(d[3]), "+f"(d[4]), "+f"(d[5]), "+f"(d[6]), "+f"(d[7]), "+f"(d[8]), "+f"(d[9]), "+f"(d[10]), "+f"(d[11]), "+f"(d[12]), "+f"(d[13]), "+f"(d[14]), "+f"(d[15]), "+f"(d[16]), "+f"(d[17]), "+f"(d[18]), "+f"(d[19]), "+f"(d[20]), "+f"(d[21]), "+f"(d[22]), "+f"(d[23]), "+f"(d[24]), "+f"(d[25]), "+f"(d[26]), "+f"(d[27]), "+f"(d[28]), "+f"(d[29]), "+f"(d[30]), "+f"(d[31]), "+f"(d[32]), "+f"(d[33]), "+f"(d[34]), "+f"(d[35]), "+f"(d[36]), "+f"(d[37]), "+f"(d[38]), "+f"(d[39]), "+f"(d[40]), "+f"(d[41]), "+f"(d[42]), "+f"(d[43]), "+f"(d[44]), "+f"(d[45]), "+f"(d[46]), "+f"(d[47]), "+f"(d[48]), "+f"(d[49]), "+f"(d[50]), "+f"(d[51]), "+f"(d[52]), "+f"(d[53]), "+f"(d[54]), "+f"(d[55]), "+f"(d[56]), "+f"(d[57]), "+f"(d[58]), "+f"(d[59]), "+f"(d[60]), "+f"(d[61]), "+f"(d[62]), "+f"(d[63])
        : "r"(a0), "r"(a1), "r"(a2), "r"(a3), "l"(db), "r"(sd));
}
__device__ __forceinline__ void wgmma_rs_n128_tb(float (&d)[64], uint32_t a0, uint32_t a1, uint32_t a2, uint32_t a3, uint64_t db, int sd) {
    asm volatile("{\n.reg .pred p;\nsetp.ne.b32 p, %69, 0;\n"
        "wgmma.mma_async.sync.aligned.m64n128k16.f32.bf16.bf16 "
        "{%0, %1, %2, %3, %4, %5, %6, %7, %8, %9, %10, %11, %12, %13, %14, %15, %16, %17, %18, %19, %20, %21, %22, %23, %24, %25, %26, %27, %28, %29, %30, %31, %32, %33, %34, %35, %36, %37, %38, %39, %40, %41, %42, %43, %44, %45, %46, %47, %48, %49, %50, %51, %52, %53, %54, %55, %56, %57, %58, %59, %60, %61, %62, %63}, "
        "{%64, %65, %66, %67}, %68, p, 1, 1, 1;\n}\n"
        : "+f"(d[0]), "+f"(d[1]), "+f"(d[2]), "+f"(d[3]), "+f"(d[4]), "+f"(d[5]), "+f"(d[6]), "+f"(d[7]), "+f"(d[8]), "+f"(d[9]), "+f"(d[10]), "+f"(d[11]), "+f"(d[12]), "+f"(d[13]), "+f"(d[14]), "+f"(d[15]), "+f"(d[16]), "+f"(d[17]), "+f"(d[18]), "+f"(d[19]), "+f"(d[20]), "+f"(d[21]), "+f"(d[22]), "+f"(d[23]), "+f"(d[24]), "+f"(d[25]), "+f"(d[26]), "+f"(d[27]), "+f"(d[28]), "+f"(d[29]), "+f"(d[30]), "+f"(d[31]), "+f"(d[32]), "+f"(d[33]), "+f"(d[34]), "+f"(d[35]), "+f"(d[36]), "+f"(d[37]), "+f"(d[38]), "+f"(d[39]), "+f"(d[40]), "+f"(d[41]), "+f"(d[42]), "+f"(d[43]), "+f"(d[44]), "+f"(d[45]), "+f"(d[46]), "+f"(d[47]), "+f"(d[48]), "+f"(d[49]), "+f"(d[50]), "+f"(d[51]), "+f"(d[52]), "+f"(d[53]), "+f"(d[54]), "+f"(d[55]), "+f"(d[56]), "+f"(d[57]), "+f"(d[58]), "+f"(d[59]), "+f"(d[60]), "+f"(d[61]), "+f"(d[62]), "+f"(d[63])
        : "r"(a0), "r"(a1), "r"(a2), "r"(a3), "l"(db), "r"(sd));
}
__device__ __forceinline__ void wgmma_rs_n64_tb(float (&d)[32], uint32_t a0, uint32_t a1, uint32_t a2, uint32_t a3, uint64_t db, int sd) {
    asm volatile("{\n.reg .pred p;\nsetp.ne.b32 p, %37, 0;\n"
        "wgmma.mma_async.sync.aligned.m64n64k16.f32.bf16.bf16 "
        "{%0, %1, %2, %3, %4, %5, %6, %7, %8, %9, %10, %11, %12, %13, %14, %15, %16, %17, %18, %19, %20, %21, %22, %23, %24, %25, %26, %27, %28, %29, %30, %31}, "
        "{%32, %33, %34, %35}, %36, p, 1, 1, 1;\n}\n"
        : "+f"(d[0]), "+f"(d[1]), "+f"(d[2]), "+f"(d[3]), "+f"(d[4]), "+f"(d[5]), "+f"(d[6]), "+f"(d[7]), "+f"(d[8]), "+f"(d[9]), "+f"(d[10]), "+f"(d[11]), "+f"(d[12]), "+f"(d[13]), "+f"(d[14]), "+f"(d[15]), "+f"(d[16]), "+f"(d[17]), "+f"(d[18]), "+f"(d[19]), "+f"(d[20]), "+f"(d[21]), "+f"(d[22]), "+f"(d[23]), "+f"(d[24]), "+f"(d[25]), "+f"(d[26]), "+f"(d[27]), "+f"(d[28]), "+f"(d[29]), "+f"(d[30]), "+f"(d[31])
        : "r"(a0), "r"(a1), "r"(a2), "r"(a3), "l"(db), "r"(sd));
}

__global__ void __launch_bounds__(384, 1) fused_gqa_kernel(const __grid_constant__ Params P) {
    extern __shared__ uint8_t smem_raw[];
    const uint32_t base = (smem_u32(smem_raw) + 1023u) & ~1023u;
    const uint32_t smR = base;
    const uint32_t smS = base + R_BYTES;
    const uint32_t bars = smS + NSTAGE * STAGE_BYTES;
    const int tid = threadIdx.x;
    const int wid = __shfl_sync(0xffffffffu, tid >> 5, 0);
    const int lane = tid & 31;

    const int cta = blockIdx.x;
    const int blk = cta >> 6;
    const int hp = (cta >> 3) & 7;
    const int b = cta & 7;
    const int grp = blk * 8 + b;

    if (tid == 0) {
        TS(0);
        for (int i = 0; i < NSTAGE; i++) {
            mbar_init(bars + 8 * i, 1);
            mbar_init(bars + 8 * (NSTAGE + i), 8);
        }
        for (int i = 0; i < 10; i++) mbar_init(bars + 8 * (2 * NSTAGE + i), 4);
        asm volatile("fence.mbarrier_init.release.cluster;" ::: "memory");
        asm volatile("fence.proxy.async.shared::cta;" ::: "memory");
    }
    __syncthreads();

    if (wid >= 8) {
        asm volatile("setmaxnreg.dec.sync.aligned.u32 40;");
        const char* kbase = (const char*)(P.kp[blk] + (size_t)(b * kHkv + hp * 2) * kSk * kDh);
        const char* vbase = (const char*)(P.vp[blk] + (size_t)(b * kHkv + hp * 2) * kSk * kDh);
        if (wid != 8) {
            const int hw = wid - 9;
            uint32_t sink = 0;
            if (PF_WQ) {
                const char* wqs = (const char*)(P.wqp[blk] + hp * 512) + (size_t)(b * 72 + hw * 24) * 8192;
#pragma unroll
                for (int i = 0; i < 3; i++) {
                    const int e = i * 32 + lane;
                    sink |= l2_touch(wqs + (size_t)(e >> 2) * 8192 + (e & 3) * 256);
                }
                asm volatile("" ::"r"(sink) : "memory");
            }
            for (int i = hw; i < PF_DIST; i += 3) {
                const char* p = ((i & 1) ? vbase : kbase) + (size_t)(i >> 1) * 32768 + lane * 256;
#pragma unroll
                for (int j = 0; j < 4; j++) sink |= l2_touch(p + j * 8192);
                asm volatile("" ::"r"(sink) : "memory");
            }
            if (hw < 2) {
                for (int k = 0; k < 5; k++) {
                    mbar_wait(bars + 8 * (2 * NSTAGE + hw * 5 + k), 0);
                    const int c = (k < 4) ? (2 * k + hw) : 8;
                    asm volatile("fence.acq_rel.gpu;" ::: "memory");
                    asm volatile("red.relaxed.gpu.global.add.u32 [%0], 1;" ::"l"(&g_cnt[(grp * 9 + c) * 32 + lane]) : "memory");
                }
            }
        } else if (wid == 8 && lane == 0) {
            int slot = 0, ph = 1;
            for (int s = 0; s < N_WQ; s++) {
                const uint32_t fb = bars + 8 * slot;
                mbar_wait(bars + 8 * (NSTAGE + slot), ph);
                const uint32_t dst = smS + slot * STAGE_BYTES;
                mbar_expect_tx(fb, (s & 1) ? STAGE_BYTES : STAGE_BYTES + 8192);
                if (!(s & 1)) tma_2d(smR + ((s >> 1) & 7) * 8192, &P.x[blk], (s >> 1) * 64, b * 64, fb);
#pragma unroll
                for (int p = 0; p < 8; p++) {
                    const int w = p >> 2, j = (p >> 1) & 1, glo = p & 1;
                    tma_2d(dst + p * 4096, &P.wq[blk], hp * 512 + (j * 4 + w * 2 + glo) * 64, s * 32, fb);
                }
                if (++slot == NSTAGE) { slot = 0; ph ^= 1; }
            }
            for (int i = 0; i < N_KV; i++) {
                const uint32_t fb = bars + 8 * slot;
                mbar_wait(bars + 8 * (NSTAGE + slot), ph);
                const uint32_t dst = smS + slot * STAGE_BYTES;
                mbar_expect_tx(fb, STAGE_BYTES);
                const int row = (b * kHkv + hp * 2) * kSk + (i >> 1) * 128;
                const CUtensorMap* tm = (i & 1) ? &P.v[blk] : &P.k[blk];
                tma_2d(dst, tm, 0, row, fb);
                tma_2d(dst + 16384, tm, 64, row, fb);
                if (++slot == NSTAGE) { slot = 0; ph ^= 1; }
            }
            for (int i = 0; i < N_WO; i++) {
                const uint32_t fb = bars + 8 * slot;
                mbar_wait(bars + 8 * (NSTAGE + slot), ph);
                const uint32_t dst = smS + slot * STAGE_BYTES;
                mbar_expect_tx(fb, STAGE_BYTES);
                if (i < 16) {
                    tma_2d(dst, &P.wo[blk], (i >> 2) * 128, hp * 512 + (i & 3) * 128, fb);
                    tma_2d(dst + 16384, &P.wo[blk], (i >> 2) * 128 + 64, hp * 512 + ((i + 2) & 3) * 128, fb);
                } else {
                    const int row = hp * 512 + (i - 16) * 128;
                    tma_2d(dst, &P.wo[blk], 512, row, fb);
                    tma_2d(dst + 16384, &P.wo[blk], 512, row + 256, fb);
                }
                if (++slot == NSTAGE) { slot = 0; ph ^= 1; }
            }
        }
    } else {
        asm volatile("setmaxnreg.inc.sync.aligned.u32 232;");
        const int w = wid >> 2;
        const int t = tid & 127;
        int slot = 0, ph = 0;
        uint32_t qf[8][4];
        const uint32_t stash = smR + (1 + w) * 16384 + t * 16;
        {
            float acc[128];
            int pslot = 0;
            for (int s = 0; s < N_WQ; s++) {
                mbar_wait(bars + 8 * slot, ph);
                if (tid == 0 && s == 0) TS(20);
                if (tid == 0 && s == 5) TS(21);
                if (tid == 0 && s == 10) TS(22);
                const uint64_t da = mk_desc(smR + ((s >> 1) & 7) * 8192 + (s & 1) * 64, 16, 1024);
                const uint64_t db = mk_desc(smS + slot * STAGE_BYTES + w * 16384, 4096, 1024);
                wg_fence();
                wgmma_ss_n256_tb(acc, da, db, s != 0);
                wgmma_ss_n256_tb(acc, da + 2, db + 128, 1);
                wg_commit();
                if (s > 0) {
                    wg_wait<1>();
                    if (lane == 0) mbar_arrive(bars + 8 * (NSTAGE + pslot));
                }
                pslot = slot;
                if (++slot == NSTAGE) { slot = 0; ph ^= 1; }
            }
            wg_wait<0>();
            if (lane == 0) mbar_arrive(bars + 8 * (NSTAGE + pslot));
            fence_regs(acc);
            if (tid == 0) TS(1);
#pragma unroll
            for (int kk = 0; kk < 8; kk++) {
#pragma unroll
                for (int i = 0; i < 4; i++) qf[kk][i] = pack_bf16(acc[8 * kk + 2 * i], acc[8 * kk + 2 * i + 1]);
                sts128(stash + kk * 2048,
                       pack_bf16(acc[64 + 8 * kk + 0], acc[64 + 8 * kk + 1]), pack_bf16(acc[64 + 8 * kk + 2], acc[64 + 8 * kk + 3]),
                       pack_bf16(acc[64 + 8 * kk + 4], acc[64 + 8 * kk + 5]), pack_bf16(acc[64 + 8 * kk + 6], acc[64 + 8 * kk + 7]));
            }
        }
        const float sc = 0.08838834764831845f * 1.4426950408889634f;
#pragma unroll 1
        for (int u = 0; u < 2; u++) {
            if (u == 1) {
#pragma unroll
                for (int kk = 0; kk < 8; kk++) lds128(stash + kk * 2048, qf[kk]);
            }
            float o[64];
            float m0 = -INFINITY, m1 = -INFINITY, l0 = 0.f, l1 = 0.f;
#pragma unroll 1
            for (int tt = 0; tt < 4; tt++) {
                float s[64];
                mbar_wait(bars + 8 * slot, ph);
                if (tid == 0) TS(32 + u * 20 + tt * 5);
                {
                    const uint64_t db = mk_desc(smS + slot * STAGE_BYTES, 16, 1024);
                    wg_fence();
#pragma unroll
                    for (int kk = 0; kk < 8; kk++)
                        wgmma_rs_n128(s, qf[kk][0], qf[kk][1], qf[kk][2], qf[kk][3], db + (kk >> 2) * 1024 + (kk & 3) * 2, kk != 0);
                    wg_commit();
                    wg_wait<0>();
                    fence_regs(s);
                }
                if (tid == 0) TS(32 + u * 20 + tt * 5 + 1);
                if (lane == 0) mbar_arrive(bars + 8 * (NSTAGE + slot));
                if (++slot == NSTAGE) { slot = 0; ph ^= 1; }
                float mx0 = s[0], mx1 = s[2];
#pragma unroll
                for (int j = 0; j < 16; j++) {
                    mx0 = fmaxf(mx0, fmaxf(s[4 * j], s[4 * j + 1]));
                    mx1 = fmaxf(mx1, fmaxf(s[4 * j + 2], s[4 * j + 3]));
                }
                mx0 = fmaxf(mx0, __shfl_xor_sync(0xffffffffu, mx0, 1));
                mx1 = fmaxf(mx1, __shfl_xor_sync(0xffffffffu, mx1, 1));
                mx0 = fmaxf(mx0, __shfl_xor_sync(0xffffffffu, mx0, 2));
                mx1 = fmaxf(mx1, __shfl_xor_sync(0xffffffffu, mx1, 2));
                const float mn0 = fmaxf(m0, mx0), mn1 = fmaxf(m1, mx1);
                const float al0 = ex2((m0 - mn0) * sc), al1 = ex2((m1 - mn1) * sc);
                m0 = mn0; m1 = mn1;
                const float ms0 = mn0 * sc, ms1 = mn1 * sc;
                uint32_t pf[8][4];
                float rs0 = 0.f, rs1 = 0.f;
#pragma unroll
                for (int j = 0; j < 16; j++) {
                    const float p0 = ex2(fmaf(s[4 * j], sc, -ms0)), p1 = ex2(fmaf(s[4 * j + 1], sc, -ms0));
                    const float p2 = ex2(fmaf(s[4 * j + 2], sc, -ms1)), p3 = ex2(fmaf(s[4 * j + 3], sc, -ms1));
                    rs0 += p0 + p1; rs1 += p2 + p3;
                    pf[j >> 1][(j & 1) * 2] = pack_bf16(p0, p1);
                    pf[j >> 1][(j & 1) * 2 + 1] = pack_bf16(p2, p3);
                }
                l0 = l0 * al0 + rs0; l1 = l1 * al1 + rs1;
                if (tt > 0) {
#pragma unroll
                    for (int j = 0; j < 16; j++) { o[4 * j] *= al0; o[4 * j + 1] *= al0; o[4 * j + 2] *= al1; o[4 * j + 3] *= al1; }
                }
                if (tid == 0) TS(32 + u * 20 + tt * 5 + 2);
                mbar_wait(bars + 8 * slot, ph);
                if (tid == 0) TS(32 + u * 20 + tt * 5 + 3);
                {
                    const uint64_t db = mk_desc(smS + slot * STAGE_BYTES, 16384, 1024);
                    wg_fence();
#pragma unroll
                    for (int kk = 0; kk < 8; kk++)
                        wgmma_rs_n128_tb(o, pf[kk][0], pf[kk][1], pf[kk][2], pf[kk][3], db + kk * 128, (tt | kk) != 0);
                    wg_commit();
                    wg_wait<0>();
                    fence_regs(o);
                }
                if (tid == 0) TS(32 + u * 20 + tt * 5 + 4);
                if (lane == 0) mbar_arrive(bars + 8 * (NSTAGE + slot));
                if (++slot == NSTAGE) { slot = 0; ph ^= 1; }
            }
            if (tid == 0) TS(2 + u);
            l0 += __shfl_xor_sync(0xffffffffu, l0, 1);
            l1 += __shfl_xor_sync(0xffffffffu, l1, 1);
            l0 += __shfl_xor_sync(0xffffffffu, l0, 2);
            l1 += __shfl_xor_sync(0xffffffffu, l1, 2);
            const float i0 = 1.f / l0, i1 = 1.f / l1;
            const uint32_t zone = smR + ((u == 0) ? (w ? 3 : 0) : (w ? 2 : 1)) * 16384 + t * 16;
#pragma unroll
            for (int kk = 0; kk < 8; kk++)
                sts128(zone + kk * 2048,
                       pack_bf16(o[8 * kk + 0] * i0, o[8 * kk + 1] * i0), pack_bf16(o[8 * kk + 2] * i1, o[8 * kk + 3] * i1),
                       pack_bf16(o[8 * kk + 4] * i0, o[8 * kk + 5] * i0), pack_bf16(o[8 * kk + 6] * i1, o[8 * kk + 7] * i1));
        }
        bar_sync<4, 256>();
        uint32_t af[32][4];
#pragma unroll
        for (int hh = 0; hh < 4; hh++) {
            const int h2 = (hh + 2 * w) & 3;
            const int z = (0x2130 >> (h2 * 4)) & 3;
#pragma unroll
            for (int kk = 0; kk < 8; kk++) lds128(smR + z * 16384 + kk * 2048 + t * 16, af[hh * 8 + kk]);
        }
        {
            float acc[2][32];
            int pslot = 0;
            float4* dst0 = g_part + (size_t)(grp * 80 + w * 8 + hp) * 1024 + t;
            float4* dst8 = g_part + (size_t)(grp * 80 + 64 + hp * 2 + w) * 1024 + t;
#pragma unroll
            for (int st = 0; st <= N_WO; st++) {
                if (st < N_WO) {
                    const int kq = st & 3, ab = (st >> 2) & 1;
                    mbar_wait(bars + 8 * slot, ph);
                    const uint64_t db = mk_desc(smS + slot * STAGE_BYTES + w * 16384, 16384, 1024);
                    wg_fence();
#pragma unroll
                    for (int kk = 0; kk < 8; kk++)
                        wgmma_rs_n64_tb(acc[ab], af[kq * 8 + kk][0], af[kq * 8 + kk][1], af[kq * 8 + kk][2], af[kq * 8 + kk][3], db + kk * 128, (kq | kk) != 0);
                    wg_commit();
                }
                if (st > 0) {
                    if (st < N_WO) wg_wait<1>(); else wg_wait<0>();
                    if (lane == 0) mbar_arrive(bars + 8 * (NSTAGE + pslot));
                    if ((st & 3) == 0 || st == N_WO) {
                        const int k = (st - 1) >> 2, ab = k & 1;
                        fence_regs(acc[ab]);
                        float4* dst = (k < 4) ? (dst0 + (size_t)k * 16 * 1024) : dst8;
#pragma unroll
                        for (int j = 0; j < 8; j++) __stcg(dst + j * 128, make_float4(acc[ab][4 * j], acc[ab][4 * j + 1], acc[ab][4 * j + 2], acc[ab][4 * j + 3]));
                        __syncwarp();
                        if (lane == 0) mbar_arrive(bars + 8 * (2 * NSTAGE + w * 5 + k));
                        if (tid == 0) TS(4 + k);
                    }
                }
                pslot = slot;
                if (++slot == NSTAGE) { slot = 0; ph ^= 1; }
            }
        }
        {
            const int nch = (w == 0) ? 5 : 4;
            if (lane < nch) {
                const int c = (lane < 4) ? (2 * lane + w) : 8;
                const unsigned need = (lane < 4) ? 8u : 16u;
                unsigned* cp = &g_cnt[(grp * 9 + c) * 32 + hp * 4 + (wid & 3)];
                unsigned v, n = 0;
                while (true) {
                    asm volatile("ld.acquire.gpu.global.u32 %0, [%1];" : "=r"(v) : "l"(cp) : "memory");
                    if (v >= need) break;
                    if (++n > (1u << 21)) break;
                }
                *cp = 0;
            }
            __syncwarp();
            if (tid == 0) TS(10);
            __nv_bfloat16* orow = P.out + (size_t)(b * 64 + (t >> 5) * 16 + (lane >> 2)) * (2 * kD) + blk * kD + hp * 8 + (lane & 3) * 2;
            const float4* src = g_part + ((size_t)(grp * 80 + w * 8) * 8 + hp) * 128 + t;
            float4 v[4][8];
#pragma unroll
            for (int k = 0; k < 4; k++)
#pragma unroll
                for (int i = 0; i < 8; i++) v[k][i] = __ldcg(src + (size_t)(k * 16 + i) * 1024);
            if (w == 0) {
                const float4* src8 = g_part + ((size_t)(grp * 80 + 64) * 8 + hp) * 128 + t;
                float4 u[16];
#pragma unroll
                for (int i = 0; i < 16; i++) u[i] = __ldcg(src8 + (size_t)i * 1024);
                float4 a = u[0];
#pragma unroll
                for (int i = 1; i < 16; i++) { a.x += u[i].x; a.y += u[i].y; a.z += u[i].z; a.w += u[i].w; }
                *(uint32_t*)(orow + 512) = pack_bf16(a.x, a.y);
                *(uint32_t*)(orow + 512 + 8 * 2 * kD) = pack_bf16(a.z, a.w);
            }
#pragma unroll
            for (int k = 0; k < 4; k++) {
                float4 a = v[k][0];
#pragma unroll
                for (int i = 1; i < 8; i++) { a.x += v[k][i].x; a.y += v[k][i].y; a.z += v[k][i].z; a.w += v[k][i].w; }
                *(uint32_t*)(orow + (2 * k + w) * 64) = pack_bf16(a.x, a.y);
                *(uint32_t*)(orow + (2 * k + w) * 64 + 8 * 2 * kD) = pack_bf16(a.z, a.w);
            }
            if (tid == 0) TS(18);
        }
    }
}

typedef CUresult (*EncodeFn)(CUtensorMap*, CUtensorMapDataType, cuuint32_t, void*, const cuuint64_t*, const cuuint64_t*,
                             const cuuint32_t*, const cuuint32_t*, CUtensorMapInterleave, CUtensorMapSwizzle,
                             CUtensorMapL2promotion, CUtensorMapFloatOOBfill);

void make_map(EncodeFn fn, CUtensorMap* m, const void* ptr, uint64_t cols, uint64_t rows, uint32_t box_rows) {
    cuuint64_t dims[2] = {cols, rows};
    cuuint64_t strides[1] = {cols * 2};
    cuuint32_t box[2] = {64, box_rows};
    cuuint32_t es[2] = {1, 1};
    fn(m, CU_TENSOR_MAP_DATA_TYPE_BFLOAT16, 2, const_cast<void*>(ptr), dims, strides, box, es, CU_TENSOR_MAP_INTERLEAVE_NONE,
       CU_TENSOR_MAP_SWIZZLE_128B, CU_TENSOR_MAP_L2_PROMOTION_L2_256B, CU_TENSOR_MAP_FLOAT_OOB_FILL_NONE);
}

}

extern "C" void kernel_launch(void* const* d_in, const int* in_sizes, int n_in, void* d_out, int out_size) {
    static EncodeFn enc = nullptr;
    if (!enc) {
        void* fn = nullptr;
        cudaDriverEntryPointQueryResult st;
        cudaGetDriverEntryPoint("cuTensorMapEncodeTiled", &fn, cudaEnableDefault, &st);
        enc = (EncodeFn)fn;
        cudaFuncSetAttribute(fused_gqa_kernel, cudaFuncAttributeMaxDynamicSharedMemorySize, SMEM_BYTES);
    }
    Params P;
    for (int blk = 0; blk < 2; blk++) {
        const void* x = d_in[blk * 5 + 0];
        const void* k = d_in[blk * 5 + 1];
        const void* v = d_in[blk * 5 + 2];
        const void* wq = d_in[blk * 5 + 3];
        const void* wo = d_in[blk * 5 + 4];
        make_map(enc, &P.x[blk], x, kD, kB * kSq, 64);
        make_map(enc, &P.wq[blk], wq, kHq * kDh, kD, 32);
        make_map(enc, &P.k[blk], k, kDh, (uint64_t)kB * kHkv * kSk, 128);
        make_map(enc, &P.v[blk], v, kDh, (uint64_t)kB * kHkv * kSk, 128);
        make_map(enc, &P.wo[blk], wo, kD, kHq * kDh, 128);
        P.wqp[blk] = (const __nv_bfloat16*)wq;
        P.kp[blk] = (const __nv_bfloat16*)k;
        P.vp[blk] = (const __nv_bfloat16*)v;
        P.wop[blk] = (const __nv_bfloat16*)wo;
    }
    P.out = (__nv_bfloat16*)d_out;
    fused_gqa_kernel<<<128, 384, SMEM_BYTES>>>(P);
}
```

```cpp
#include <cuda_runtime.h>
#include <cuda_bf16.h>
#include <cuda.h>
#include <stdint.h>

namespace {

constexpr int kB = 8, kSq = 64, kD = 576, kHq = 32, kHkv = 16, kSk = 512, kDh = 128;
constexpr int NSTAGE = 5;
constexpr int STAGE_BYTES = 32768;
constexpr int R_BYTES = 65536;
constexpr int SMEM_BYTES = R_BYTES + NSTAGE * STAGE_BYTES + 1024   + 256  ;
constexpr int N_WQ = 18, N_KV = 16, N_WO = 18;
#define PF_DIST_V 5
#define PF_WQ 1
constexpr int PF_DIST = PF_DIST_V;

struct __align__(64) Params {
    CUtensorMap x[2], wq[2], k[2], v[2], wo[2];
    const __nv_bfloat16* wqp[2];
    const __nv_bfloat16* kp[2];
    const __nv_bfloat16* vp[2];
    const __nv_bfloat16* wop[2];
    __nv_bfloat16* out;
};

__device__ float4 g_part[16 * 80 * 8 * 128];
__device__ unsigned int g_cnt[16 * 9 * 32];
#define TS(k) do {} while (0)

__device__ __forceinline__ uint32_t smem_u32(const void* p) { return (uint32_t)__cvta_generic_to_shared(p); }
__device__ __forceinline__ void mbar_init(uint32_t bar, int cnt) {
    asm volatile("mbarrier.init.shared::cta.b64 [%0], %1;" ::"r"(bar), "r"(cnt));
}
__device__ __forceinline__ void mbar_expect_tx(uint32_t bar, uint32_t bytes) {
    asm volatile("mbarrier.arrive.expect_tx.shared::cta.b64 _, [%0], %1;" ::"r"(bar), "r"(bytes) : "memory");
}
__device__ __forceinline__ void mbar_arrive(uint32_t bar) {
    asm volatile("mbarrier.arrive.shared::cta.b64 _, [%0];" ::"r"(bar) : "memory");
}
__device__ __forceinline__ bool mbar_try(uint32_t bar, uint32_t parity) {
    uint32_t ok;
    asm volatile("{\n.reg .pred p;\nmbarrier.try_wait.parity.shared::cta.b64 p, [%1], %2;\nselp.u32 %0, 1, 0, p;\n}\n"
                 : "=r"(ok) : "r"(bar), "r"(parity) : "memory");
    return ok != 0;
}
__device__ __forceinline__ void mbar_wait(uint32_t bar, uint32_t parity) {
    if (mbar_try(bar, parity)) return;
    uint32_t n = 0;
    while (!mbar_try(bar, parity)) {
        if (++n > (1u << 20)) break;
    }
}
__device__ __forceinline__ void tma_2d(uint32_t dst, const CUtensorMap* tm, int c0, int c1, uint32_t bar) {
    asm volatile("cp.async.bulk.tensor.2d.shared::cluster.global.mbarrier::complete_tx::bytes [%0], [%1, {%3, %4}], [%2];"
                 ::"r"(dst), "l"(tm), "r"(bar), "r"(c0), "r"(c1) : "memory");
}
__device__ __forceinline__ void l2_prefetch(const void* p, uint32_t bytes) {
    asm volatile("cp.async.bulk.prefetch.L2.global [%0], %1;" ::"l"(p), "r"(bytes) : "memory");
}
__device__ __forceinline__ uint32_t l2_touch(const void* p) {
    uint32_t v;
    asm volatile("ld.global.L2::256B.b32 %0, [%1];" : "=r"(v) : "l"(p) : "memory");
    return v;
}
__device__ __forceinline__ void wg_fence() { asm volatile("wgmma.fence.sync.aligned;" ::: "memory"); }
__device__ __forceinline__ void wg_commit() { asm volatile("wgmma.commit_group.sync.aligned;" ::: "memory"); }
template <int N> __device__ __forceinline__ void wg_wait() { asm volatile("wgmma.wait_group.sync.aligned %0;" ::"n"(N) : "memory"); }
template <int N> __device__ __forceinline__ void fence_regs(float (&d)[N]) {
#pragma unroll
    for (int i = 0; i < N; i++) asm volatile("" : "+f"(d[i])::"memory");
}
__device__ __forceinline__ uint64_t mk_desc(uint32_t addr, uint32_t lbo, uint32_t sbo) {
    return (uint64_t)((addr & 0x3FFFF) >> 4) | ((uint64_t)(lbo >> 4) << 16) | ((uint64_t)(sbo >> 4) << 32) | (1ull << 62);
}
__device__ __forceinline__ uint32_t pack_bf16(float a, float b) {
    uint32_t r;
    asm("cvt.rn.bf16x2.f32 %0, %1, %2;" : "=r"(r) : "f"(b), "f"(a));
    return r;
}
__device__ __forceinline__ float ex2(float x) {
    float y;
    asm("ex2.approx.ftz.f32 %0, %1;" : "=f"(y) : "f"(x));
    return y;
}
template <int ID, int N> __device__ __forceinline__ void bar_sync() { asm volatile("bar.sync %0, %1;" ::"n"(ID), "n"(N) : "memory"); }
template <int ID, int N> __device__ __forceinline__ void bar_arrive() { asm volatile("bar.arrive %0, %1;" ::"n"(ID), "n"(N) : "memory"); }
__device__ __forceinline__ void sts128(uint32_t addr, uint32_t a, uint32_t b, uint32_t c, uint32_t d) {
    asm volatile("st.shared.v4.b32 [%0], {%1,%2,%3,%4};" ::"r"(addr), "r"(a), "r"(b), "r"(c), "r"(d) : "memory");
}
__device__ __forceinline__ void lds128(uint32_t addr, uint32_t (&r)[4]) {
    asm volatile("ld.shared.v4.b32 {%0,%1,%2,%3}, [%4];" : "=r"(r[0]), "=r"(r[1]), "=r"(r[2]), "=r"(r[3]) : "r"(addr) : "memory");
}

__device__ __forceinline__ void wgmma_ss_n256_tb(float (&d)[128], uint64_t da, uint64_t db, int sd) {
    asm volatile("{\n.reg .pred p;\nsetp.ne.b32 p, %130, 0;\n"
        "wgmma.mma_async.sync.aligned.m64n256k16.f32.bf16.bf16 "
        "{%0, %1, %2, %3, %4, %5, %6, %7, %8, %9, %10, %11, %12, %13, %14, %15, %16, %17, %18, %19, %20, %21, %22, %23, %24, %25, %26, %27, %28, %29, %30, %31, %32, %33, %34, %35, %36, %37, %38, %39, %40, %41, %42, %43, %44, %45, %46, %47, %48, %49, %50, %51, %52, %53, %54, %55, %56, %57, %58, %59, %60, %61, %62, %63, %64, %65, %66, %67, %68, %69, %70, %71, %72, %73, %74, %75, %76, %77, %78, %79, %80, %81, %82, %83, %84, %85, %86, %87, %88, %89, %90, %91, %92, %93, %94, %95, %96, %97, %98, %99, %100, %101, %102, %103, %104, %105, %106, %107, %108, %109, %110, %111, %112, %113, %114, %115, %116, %117, %118, %119, %120, %121, %122, %123, %124, %125, %126, %127}, "
        "%128, %129, p, 1, 1, 0, 1;\n}\n"
        : "+f"(d[0]), "+f"(d[1]), "+f"(d[2]), "+f"(d[3]), "+f"(d[4]), "+f"(d[5]), "+f"(d[6]), "+f"(d[7]), "+f"(d[8]), "+f"(d[9]), "+f"(d[10]), "+f"(d[11]), "+f"(d[12]), "+f"(d[13]), "+f"(d[14]), "+f"(d[15]), "+f"(d[16]), "+f"(d[17]), "+f"(d[18]), "+f"(d[19]), "+f"(d[20]), "+f"(d[21]), "+f"(d[22]), "+f"(d[23]), "+f"(d[24]), "+f"(d[25]), "+f"(d[26]), "+f"(d[27]), "+f"(d[28]), "+f"(d[29]), "+f"(d[30]), "+f"(d[31]), "+f"(d[32]), "+f"(d[33]), "+f"(d[34]), "+f"(d[35]), "+f"(d[36]), "+f"(d[37]), "+f"(d[38]), "+f"(d[39]), "+f"(d[40]), "+f"(d[41]), "+f"(d[42]), "+f"(d[43]), "+f"(d[44]), "+f"(d[45]), "+f"(d[46]), "+f"(d[47]), "+f"(d[48]), "+f"(d[49]), "+f"(d[50]), "+f"(d[51]), "+f"(d[52]), "+f"(d[53]), "+f"(d[54]), "+f"(d[55]), "+f"(d[56]), "+f"(d[57]), "+f"(d[58]), "+f"(d[59]), "+f"(d[60]), "+f"(d[61]), "+f"(d[62]), "+f"(d[63]), "+f"(d[64]), "+f"(d[65]), "+f"(d[66]), "+f"(d[67]), "+f"(d[68]), "+f"(d[69]), "+f"(d[70]), "+f"(d[71]), "+f"(d[72]), "+f"(d[73]), "+f"(d[74]), "+f"(d[75]), "+f"(d[76]), "+f"(d[77]), "+f"(d[78]), "+f"(d[79]), "+f"(d[80]), "+f"(d[81]), "+f"(d[82]), "+f"(d[83]), "+f"(d[84]), "+f"(d[85]), "+f"(d[86]), "+f"(d[87]), "+f"(d[88]), "+f"(d[89]), "+f"(d[90]), "+f"(d[91]), "+f"(d[92]), "+f"(d[93]), "+f"(d[94]), "+f"(d[95]), "+f"(d[96]), "+f"(d[97]), "+f"(d[98]), "+f"(d[99]), "+f"(d[100]), "+f"(d[101]), "+f"(d[102]), "+f"(d[103]), "+f"(d[104]), "+f"(d[105]), "+f"(d[106]), "+f"(d[107]), "+f"(d[108]), "+f"(d[109]), "+f"(d[110]), "+f"(d[111]), "+f"(d[112]), "+f"(d[113]), "+f"(d[114]), "+f"(d[115]), "+f"(d[116]), "+f"(d[117]), "+f"(d[118]), "+f"(d[119]), "+f"(d[120]), "+f"(d[121]), "+f"(d[122]), "+f"(d[123]), "+f"(d[124]), "+f"(d[125]), "+f"(d[126]), "+f"(d[127])
        : "l"(da), "l"(db), "r"(sd));
}
__device__ __forceinline__ void wgmma_rs_n128(float (&d)[64], uint32_t a0, uint32_t a1, uint32_t a2, uint32_t a3, uint64_t db, int sd) {
    asm volatile("{\n.reg .pred p;\nsetp.ne.b32 p, %69, 0;\n"
        "wgmma.mma_async.sync.aligned.m64n128k16.f32.bf16.bf16 "
        "{%0, %1, %2, %3, %4, %5, %6, %7, %8, %9, %10, %11, %12, %13, %14, %15, %16, %17, %18, %19, %20, %21, %22, %23, %24, %25, %26, %27, %28, %29, %30, %31, %32, %33, %34, %35, %36, %37, %38, %39, %40, %41, %42, %43, %44, %45, %46, %47, %48, %49, %50, %51, %52, %53, %54, %55, %56, %57, %58, %59, %60, %61, %62, %63}, "
        "{%64, %65, %66, %67}, %68, p, 1, 1, 0;\n}\n"
        : "+f"(d[0]), "+f"(d[1]), "+f"(d[2]), "+f"(d[3]), "+f"(d[4]), "+f"(d[5]), "+f"(d[6]), "+f"(d[7]), "+f"(d[8]), "+f"(d[9]), "+f"(d[10]), "+f"(d[11]), "+f"(d[12]), "+f"(d[13]), "+f"(d[14]), "+f"(d[15]), "+f"(d[16]), "+f"(d[17]), "+f"(d[18]), "+f"(d[19]), "+f"(d[20]), "+f"(d[21]), "+f"(d[22]), "+f"(d[23]), "+f"(d[24]), "+f"(d[25]), "+f"(d[26]), "+f"(d[27]), "+f"(d[28]), "+f"(d[29]), "+f"(d[30]), "+f"(d[31]), "+f"(d[32]), "+f"(d[33]), "+f"(d[34]), "+f"(d[35]), "+f"(d[36]), "+f"(d[37]), "+f"(d[38]), "+f"(d[39]), "+f"(d[40]), "+f"(d[41]), "+f"(d[42]), "+f"(d[43]), "+f"(d[44]), "+f"(d[45]), "+f"(d[46]), "+f"(d[47]), "+f"(d[48]), "+f"(d[49]), "+f"(d[50]), "+f"(d[51]), "+f"(d[52]), "+f"(d[53]), "+f"(d[54]), "+f"(d[55]), "+f"(d[56]), "+f"(d[57]), "+f"(d[58]), "+f"(d[59]), "+f"(d[60]), "+f"(d[61]), "+f"(d[62]), "+f"(d[63])
        : "r"(a0), "r"(a1), "r"(a2), "r"(a3), "l"(db), "r"(sd));
}
__device__ __forceinline__ void wgmma_rs_n128_tb(float (&d)[64], uint32_t a0, uint32_t a1, uint32_t a2, uint32_t a3, uint64_t db, int sd) {
    asm volatile("{\n.reg .pred p;\nsetp.ne.b32 p, %69, 0;\n"
        "wgmma.mma_async.sync.aligned.m64n128k16.f32.bf16.bf16 "
        "{%0, %1, %2, %3, %4, %5, %6, %7, %8, %9, %10, %11, %12, %13, %14, %15, %16, %17, %18, %19, %20, %21, %22, %23, %24, %25, %26, %27, %28, %29, %30, %31, %32, %33, %34, %35, %36, %37, %38, %39, %40, %41, %42, %43, %44, %45, %46, %47, %48, %49, %50, %51, %52, %53, %54, %55, %56, %57, %58, %59, %60, %61, %62, %63}, "
        "{%64, %65, %66, %67}, %68, p, 1, 1, 1;\n}\n"
        : "+f"(d[0]), "+f"(d[1]), "+f"(d[2]), "+f"(d[3]), "+f"(d[4]), "+f"(d[5]), "+f"(d[6]), "+f"(d[7]), "+f"(d[8]), "+f"(d[9]), "+f"(d[10]), "+f"(d[11]), "+f"(d[12]), "+f"(d[13]), "+f"(d[14]), "+f"(d[15]), "+f"(d[16]), "+f"(d[17]), "+f"(d[18]), "+f"(d[19]), "+f"(d[20]), "+f"(d[21]), "+f"(d[22]), "+f"(d[23]), "+f"(d[24]), "+f"(d[25]), "+f"(d[26]), "+f"(d[27]), "+f"(d[28]), "+f"(d[29]), "+f"(d[30]), "+f"(d[31]), "+f"(d[32]), "+f"(d[33]), "+f"(d[34]), "+f"(d[35]), "+f"(d[36]), "+f"(d[37]), "+f"(d[38]), "+f"(d[39]), "+f"(d[40]), "+f"(d[41]), "+f"(d[42]), "+f"(d[43]), "+f"(d[44]), "+f"(d[45]), "+f"(d[46]), "+f"(d[47]), "+f"(d[48]), "+f"(d[49]), "+f"(d[50]), "+f"(d[51]), "+f"(d[52]), "+f"(d[53]), "+f"(d[54]), "+f"(d[55]), "+f"(d[56]), "+f"(d[57]), "+f"(d[58]), "+f"(d[59]), "+f"(d[60]), "+f"(d[61]), "+f"(d[62]), "+f"(d[63])
        : "r"(a0), "r"(a1), "r"(a2), "r"(a3), "l"(db), "r"(sd));
}
__device__ __forceinline__ void wgmma_rs_n64_tb(float (&d)[32], uint32_t a0, uint32_t a1, uint32_t a2, uint32_t a3, uint64_t db, int sd) {
    asm volatile("{\n.reg .pred p;\nsetp.ne.b32 p, %37, 0;\n"
        "wgmma.mma_async.sync.aligned.m64n64k16.f32.bf16.bf16 "
        "{%0, %1, %2, %3, %4, %5, %6, %7, %8, %9, %10, %11, %12, %13, %14, %15, %16, %17, %18, %19, %20, %21, %22, %23, %24, %25, %26, %27, %28, %29, %30, %31}, "
        "{%32, %33, %34, %35}, %36, p, 1, 1, 1;\n}\n"
        : "+f"(d[0]), "+f"(d[1]), "+f"(d[2]), "+f"(d[3]), "+f"(d[4]), "+f"(d[5]), "+f"(d[6]), "+f"(d[7]), "+f"(d[8]), "+f"(d[9]), "+f"(d[10]), "+f"(d[11]), "+f"(d[12]), "+f"(d[13]), "+f"(d[14]), "+f"(d[15]), "+f"(d[16]), "+f"(d[17]), "+f"(d[18]), "+f"(d[19]), "+f"(d[20]), "+f"(d[21]), "+f"(d[22]), "+f"(d[23]), "+f"(d[24]), "+f"(d[25]), "+f"(d[26]), "+f"(d[27]), "+f"(d[28]), "+f"(d[29]), "+f"(d[30]), "+f"(d[31])
        : "r"(a0), "r"(a1), "r"(a2), "r"(a3), "l"(db), "r"(sd));
}

__global__ void __launch_bounds__(384, 1) fused_gqa_kernel(const __grid_constant__ Params P) {
    extern __shared__ uint8_t smem_raw[];
    const uint32_t base = (smem_u32(smem_raw) + 1023u) & ~1023u;
    const uint32_t smR = base;
    const uint32_t smS = base + R_BYTES;
    const uint32_t bars = smS + NSTAGE * STAGE_BYTES;
    const uint32_t prog = bars + 8 * (2 * NSTAGE + 10);
    const int tid = threadIdx.x;
    const int wid = __shfl_sync(0xffffffffu, tid >> 5, 0);
    const int lane = tid & 31;

    const int cta = blockIdx.x;
    const int blk = cta >> 6;
    const int hp = (cta >> 3) & 7;
    const int b = cta & 7;
    const int grp = blk * 8 + b;

    if (tid == 0) {
        TS(0);
        for (int i = 0; i < NSTAGE; i++) {
            mbar_init(bars + 8 * i, 1);
            mbar_init(bars + 8 * (NSTAGE + i), 8);
        }
        for (int i = 0; i < 10; i++) mbar_init(bars + 8 * (2 * NSTAGE + i), 4);
        asm volatile("st.volatile.shared.u32 [%0], %1;" ::"r"(prog), "r"(0) : "memory");
        asm volatile("fence.mbarrier_init.release.cluster;" ::: "memory");
        asm volatile("fence.proxy.async.shared::cta;" ::: "memory");
    }
    __syncthreads();

    if (wid >= 8) {
        asm volatile("setmaxnreg.dec.sync.aligned.u32 40;");
        const char* kbase = (const char*)(P.kp[blk] + (size_t)(b * kHkv + hp * 2) * kSk * kDh);
        const char* vbase = (const char*)(P.vp[blk] + (size_t)(b * kHkv + hp * 2) * kSk * kDh);
        if (wid != 8) {
            const int hw = wid - 9;
            uint32_t sink = 0;
            if (PF_WQ) {
                const char* wqs = (const char*)(P.wqp[blk] + hp * 512) + (size_t)(b * 72 + hw * 24) * 8192;
#pragma unroll
                for (int i = 0; i < 3; i++) {
                    const int e = i * 32 + lane;
                    sink |= l2_touch(wqs + (size_t)(e >> 2) * 8192 + (e & 3) * 256);
                }
                asm volatile("" ::"r"(sink) : "memory");
            }
            const char* wos = (const char*)(P.wop[blk] + (size_t)hp * 512 * kD) + (size_t)b * 73728;
            if (PF_DIST > 0) {
                for (int i = hw; i < N_KV + 3; i += 3) {
                    if (i >= PF_DIST) {
                        uint32_t pr, n = 0;
                        while (true) {
                            asm volatile("ld.volatile.shared.u32 %0, [%1];" : "=r"(pr) : "r"(prog) : "memory");
                            if ((int)pr + PF_DIST >= i) break;
                            if (++n > (1u << 22)) break;
                            __nanosleep(64);
                        }
                    }
                    if (i < N_KV) {
                        const char* p = ((i & 1) ? vbase : kbase) + (size_t)(i >> 1) * 32768 + lane * 256;
#pragma unroll
                        for (int j = 0; j < 4; j++) sink |= l2_touch(p + j * 8192);
                    } else {
                        const char* p = wos + (i - N_KV) * 24576 + lane * 256;
#pragma unroll
                        for (int j = 0; j < 3; j++) sink |= l2_touch(p + j * 8192);
                    }
                    asm volatile("" ::"r"(sink) : "memory");
                }
            }
            if (hw < 2) {
                for (int k = 0; k < 5; k++) {
                    mbar_wait(bars + 8 * (2 * NSTAGE + hw * 5 + k), 0);
                    const int c = (k < 4) ? (2 * k + hw) : 8;
                    asm volatile("fence.acq_rel.gpu;" ::: "memory");
                    asm volatile("red.relaxed.gpu.global.add.u32 [%0], 1;" ::"l"(&g_cnt[(grp * 9 + c) * 32 + lane]) : "memory");
                }
            }
        } else if (wid == 8 && lane == 0) {
            int slot = 0, ph = 1;
            for (int s = 0; s < N_WQ; s++) {
                const uint32_t fb = bars + 8 * slot;
                mbar_wait(bars + 8 * (NSTAGE + slot), ph);
                const uint32_t dst = smS + slot * STAGE_BYTES;
                mbar_expect_tx(fb, (s & 1) ? STAGE_BYTES : STAGE_BYTES + 8192);
                if (!(s & 1)) tma_2d(smR + ((s >> 1) & 7) * 8192, &P.x[blk], (s >> 1) * 64, b * 64, fb);
#pragma unroll
                for (int p = 0; p < 8; p++) {
                    const int w = p >> 2, j = (p >> 1) & 1, glo = p & 1;
                    tma_2d(dst + p * 4096, &P.wq[blk], hp * 512 + (j * 4 + w * 2 + glo) * 64, s * 32, fb);
                }
                if (++slot == NSTAGE) { slot = 0; ph ^= 1; }
            }
            for (int i = 0; i < N_KV; i++) {
                const uint32_t fb = bars + 8 * slot;
                mbar_wait(bars + 8 * (NSTAGE + slot), ph);
                const uint32_t dst = smS + slot * STAGE_BYTES;
                mbar_expect_tx(fb, STAGE_BYTES);
                const int row = (b * kHkv + hp * 2) * kSk + (i >> 1) * 128;
                const CUtensorMap* tm = (i & 1) ? &P.v[blk] : &P.k[blk];
                tma_2d(dst, tm, 0, row, fb);
                tma_2d(dst + 16384, tm, 64, row, fb);
                asm volatile("st.volatile.shared.u32 [%0], %1;" ::"r"(prog), "r"(i + 1) : "memory");
                if (++slot == NSTAGE) { slot = 0; ph ^= 1; }
            }
            for (int i = 0; i < N_WO; i++) {
                const uint32_t fb = bars + 8 * slot;
                mbar_wait(bars + 8 * (NSTAGE + slot), ph);
                const uint32_t dst = smS + slot * STAGE_BYTES;
                mbar_expect_tx(fb, STAGE_BYTES);
                if (i < 16) {
                    tma_2d(dst, &P.wo[blk], (i >> 2) * 128, hp * 512 + (i & 3) * 128, fb);
                    tma_2d(dst + 16384, &P.wo[blk], (i >> 2) * 128 + 64, hp * 512 + ((i + 2) & 3) * 128, fb);
                } else {
                    const int row = hp * 512 + (i - 16) * 128;
                    tma_2d(dst, &P.wo[blk], 512, row, fb);
                    tma_2d(dst + 16384, &P.wo[blk], 512, row + 256, fb);
                }
                if (++slot == NSTAGE) { slot = 0; ph ^= 1; }
            }
        }
    } else {
        asm volatile("setmaxnreg.inc.sync.aligned.u32 232;");
        const int w = wid >> 2;
        const int t = tid & 127;
        int slot = 0, ph = 0;
        uint32_t qf[8][4];
        const uint32_t stash = smR + (1 + w) * 16384 + t * 16;
        {
            float acc[128];
            int pslot = 0;
            for (int s = 0; s < N_WQ; s++) {
                mbar_wait(bars + 8 * slot, ph);
                if (tid == 0 && s == 0) TS(20);
                if (tid == 0 && s == 5) TS(21);
                if (tid == 0 && s == 10) TS(22);
                const uint64_t da = mk_desc(smR + ((s >> 1) & 7) * 8192 + (s & 1) * 64, 16, 1024);
                const uint64_t db = mk_desc(smS + slot * STAGE_BYTES + w * 16384, 4096, 1024);
                wg_fence();
                wgmma_ss_n256_tb(acc, da, db, s != 0);
                wgmma_ss_n256_tb(acc, da + 2, db + 128, 1);
                wg_commit();
                if (s > 0) {
                    wg_wait<1>();
                    if (lane == 0) mbar_arrive(bars + 8 * (NSTAGE + pslot));
                }
                pslot = slot;
                if (++slot == NSTAGE) { slot = 0; ph ^= 1; }
            }
            wg_wait<0>();
            if (lane == 0) mbar_arrive(bars + 8 * (NSTAGE + pslot));
            fence_regs(acc);
            if (tid == 0) TS(1);
#pragma unroll
            for (int kk = 0; kk < 8; kk++) {
#pragma unroll
                for (int i = 0; i < 4; i++) qf[kk][i] = pack_bf16(acc[8 * kk + 2 * i], acc[8 * kk + 2 * i + 1]);
                sts128(stash + kk * 2048,
                       pack_bf16(acc[64 + 8 * kk + 0], acc[64 + 8 * kk + 1]), pack_bf16(acc[64 + 8 * kk + 2], acc[64 + 8 * kk + 3]),
                       pack_bf16(acc[64 + 8 * kk + 4], acc[64 + 8 * kk + 5]), pack_bf16(acc[64 + 8 * kk + 6], acc[64 + 8 * kk + 7]));
            }
        }
        if (w == 1) bar_arrive<5, 256>();
        const float sc = 0.08838834764831845f * 1.4426950408889634f;
#pragma unroll 1
        for (int u = 0; u < 2; u++) {
            if (u == 1) {
#pragma unroll
                for (int kk = 0; kk < 8; kk++) lds128(stash + kk * 2048, qf[kk]);
            }
            float o[64];
            float m0 = -INFINITY, m1 = -INFINITY, l0 = 0.f, l1 = 0.f;
            uint32_t pf[8][4];
#pragma unroll 1
            for (int tt = 0; tt <= 4; tt++) {
                float s[64];
                int vslot = slot;
                if (tt > 0) {
                    mbar_wait(bars + 8 * slot, ph);
                    if (++slot == NSTAGE) { slot = 0; ph ^= 1; }
                }
                if (tt < 4) mbar_wait(bars + 8 * slot, ph);
                if (tid == 0) TS(32 + u * 20 + tt * 4);
                if (w == 0) bar_sync<5, 256>(); else bar_sync<6, 256>();
                wg_fence();
                if (tt > 0) {
                    const uint64_t db = mk_desc(smS + vslot * STAGE_BYTES, 16384, 1024);
#pragma unroll
                    for (int kk = 0; kk < 8; kk++)
                        wgmma_rs_n128_tb(o, pf[kk][0], pf[kk][1], pf[kk][2], pf[kk][3], db + kk * 128, (tt > 1) || (kk != 0));
                    wg_commit();
                }
                if (tt < 4) {
                    const uint64_t db = mk_desc(smS + slot * STAGE_BYTES, 16, 1024);
#pragma unroll
                    for (int kk = 0; kk < 8; kk++)
                        wgmma_rs_n128(s, qf[kk][0], qf[kk][1], qf[kk][2], qf[kk][3], db + (kk >> 2) * 1024 + (kk & 3) * 2, kk != 0);
                    wg_commit();
                }
                if (w == 0) bar_arrive<6, 256>(); else if (!(u == 1 && tt == 4)) bar_arrive<5, 256>();
                if (tid == 0) TS(32 + u * 20 + tt * 4 + 1);
                wg_wait<0>();
                fence_regs(o);
                fence_regs(s);
                if (tid == 0) TS(32 + u * 20 + tt * 4 + 2);
                if (tt > 0 && lane == 0) mbar_arrive(bars + 8 * (NSTAGE + vslot));
                if (tt == 4) break;
                if (lane == 0) mbar_arrive(bars + 8 * (NSTAGE + slot));
                if (++slot == NSTAGE) { slot = 0; ph ^= 1; }
                float mx0 = s[0], mx1 = s[2];
#pragma unroll
                for (int j = 0; j < 16; j++) {
                    mx0 = fmaxf(mx0, fmaxf(s[4 * j], s[4 * j + 1]));
                    mx1 = fmaxf(mx1, fmaxf(s[4 * j + 2], s[4 * j + 3]));
                }
                mx0 = fmaxf(mx0, __shfl_xor_sync(0xffffffffu, mx0, 1));
                mx1 = fmaxf(mx1, __shfl_xor_sync(0xffffffffu, mx1, 1));
                mx0 = fmaxf(mx0, __shfl_xor_sync(0xffffffffu, mx0, 2));
                mx1 = fmaxf(mx1, __shfl_xor_sync(0xffffffffu, mx1, 2));
                const float mn0 = fmaxf(m0, mx0), mn1 = fmaxf(m1, mx1);
                const float al0 = ex2((m0 - mn0) * sc), al1 = ex2((m1 - mn1) * sc);
                m0 = mn0; m1 = mn1;
                const float ms0 = mn0 * sc, ms1 = mn1 * sc;
                float rs0 = 0.f, rs1 = 0.f;
#pragma unroll
                for (int j = 0; j < 16; j++) {
                    const float p0 = ex2(fmaf(s[4 * j], sc, -ms0)), p1 = ex2(fmaf(s[4 * j + 1], sc, -ms0));
                    const float p2 = ex2(fmaf(s[4 * j + 2], sc, -ms1)), p3 = ex2(fmaf(s[4 * j + 3], sc, -ms1));
                    rs0 += p0 + p1; rs1 += p2 + p3;
                    pf[j >> 1][(j & 1) * 2] = pack_bf16(p0, p1);
                    pf[j >> 1][(j & 1) * 2 + 1] = pack_bf16(p2, p3);
                }
                l0 = l0 * al0 + rs0; l1 = l1 * al1 + rs1;
                if (tt > 0) {
#pragma unroll
                    for (int j = 0; j < 16; j++) { o[4 * j] *= al0; o[4 * j + 1] *= al0; o[4 * j + 2] *= al1; o[4 * j + 3] *= al1; }
                }
                if (tid == 0) TS(32 + u * 20 + tt * 4 + 3);
            }
            if (tid == 0) TS(2 + u);
            l0 += __shfl_xor_sync(0xffffffffu, l0, 1);
            l1 += __shfl_xor_sync(0xffffffffu, l1, 1);
            l0 += __shfl_xor_sync(0xffffffffu, l0, 2);
            l1 += __shfl_xor_sync(0xffffffffu, l1, 2);
            const float i0 = 1.f / l0, i1 = 1.f / l1;
            const uint32_t zone = smR + ((u == 0) ? (w ? 3 : 0) : (w ? 2 : 1)) * 16384 + t * 16;
#pragma unroll
            for (int kk = 0; kk < 8; kk++)
                sts128(zone + kk * 2048,
                       pack_bf16(o[8 * kk + 0] * i0, o[8 * kk + 1] * i0), pack_bf16(o[8 * kk + 2] * i1, o[8 * kk + 3] * i1),
                       pack_bf16(o[8 * kk + 4] * i0, o[8 * kk + 5] * i0), pack_bf16(o[8 * kk + 6] * i1, o[8 * kk + 7] * i1));
        }
        bar_sync<4, 256>();
        uint32_t af[32][4];
#pragma unroll
        for (int hh = 0; hh < 4; hh++) {
            const int h2 = (hh + 2 * w) & 3;
            const int z = (0x2130 >> (h2 * 4)) & 3;
#pragma unroll
            for (int kk = 0; kk < 8; kk++) lds128(smR + z * 16384 + kk * 2048 + t * 16, af[hh * 8 + kk]);
        }
        {
            float acc[2][32];
            int pslot = 0;
            float4* dst0 = g_part + (size_t)(grp * 80 + w * 8 + hp) * 1024 + t;
            float4* dst8 = g_part + (size_t)(grp * 80 + 64 + hp * 2 + w) * 1024 + t;
#pragma unroll
            for (int st = 0; st <= N_WO; st++) {
                if (st < N_WO) {
                    const int kq = st & 3, ab = (st >> 2) & 1;
                    mbar_wait(bars + 8 * slot, ph);
                    const uint64_t db = mk_desc(smS + slot * STAGE_BYTES + w * 16384, 16384, 1024);
                    wg_fence();
#pragma unroll
                    for (int kk = 0; kk < 8; kk++)
                        wgmma_rs_n64_tb(acc[ab], af[kq * 8 + kk][0], af[kq * 8 + kk][1], af[kq * 8 + kk][2], af[kq * 8 + kk][3], db + kk * 128, (kq | kk) != 0);
                    wg_commit();
                }
                if (st > 0) {
                    if (st < N_WO) wg_wait<1>(); else wg_wait<0>();
                    if (lane == 0) mbar_arrive(bars + 8 * (NSTAGE + pslot));
                    if ((st & 3) == 0 || st == N_WO) {
                        const int k = (st - 1) >> 2, ab = k & 1;
                        fence_regs(acc[ab]);
                        float4* dst = (k < 4) ? (dst0 + (size_t)k * 16 * 1024) : dst8;
#pragma unroll
                        for (int j = 0; j < 8; j++) __stcg(dst + j * 128, make_float4(acc[ab][4 * j], acc[ab][4 * j + 1], acc[ab][4 * j + 2], acc[ab][4 * j + 3]));
                        __syncwarp();
                        if (lane == 0) mbar_arrive(bars + 8 * (2 * NSTAGE + w * 5 + k));
                        if (tid == 0) TS(4 + k);
                    }
                }
                pslot = slot;
                if (++slot == NSTAGE) { slot = 0; ph ^= 1; }
            }
        }
        {
            const int nch = (w == 0) ? 5 : 4;
            if (lane < nch) {
                const int c = (lane < 4) ? (2 * lane + w) : 8;
                const unsigned need = (lane < 4) ? 8u : 16u;
                unsigned* cp = &g_cnt[(grp * 9 + c) * 32 + hp * 4 + (wid & 3)];
                unsigned v, n = 0;
                while (true) {
                    asm volatile("ld.acquire.gpu.global.u32 %0, [%1];" : "=r"(v) : "l"(cp) : "memory");
                    if (v >= need) break;
                    if (++n > (1u << 21)) break;
                }
                *cp = 0;
            }
            __syncwarp();
            if (tid == 0) TS(10);
            __nv_bfloat16* orow = P.out + (size_t)(b * 64 + (t >> 5) * 16 + (lane >> 2)) * (2 * kD) + blk * kD + hp * 8 + (lane & 3) * 2;
            const float4* src = g_part + ((size_t)(grp * 80 + w * 8) * 8 + hp) * 128 + t;
            float4 v[4][8];
#pragma unroll
            for (int k = 0; k < 4; k++)
#pragma unroll
                for (int i = 0; i < 8; i++) v[k][i] = __ldcg(src + (size_t)(k * 16 + i) * 1024);
            if (w == 0) {
                const float4* src8 = g_part + ((size_t)(grp * 80 + 64) * 8 + hp) * 128 + t;
                float4 u[16];
#pragma unroll
                for (int i = 0; i < 16; i++) u[i] = __ldcg(src8 + (size_t)i * 1024);
                float4 a = u[0];
#pragma unroll
                for (int i = 1; i < 16; i++) { a.x += u[i].x; a.y += u[i].y; a.z += u[i].z; a.w += u[i].w; }
                *(uint32_t*)(orow + 512) = pack_bf16(a.x, a.y);
                *(uint32_t*)(orow + 512 + 8 * 2 * kD) = pack_bf16(a.z, a.w);
            }
#pragma unroll
            for (int k = 0; k < 4; k++) {
                float4 a = v[k][0];
#pragma unroll
                for (int i = 1; i < 8; i++) { a.x += v[k][i].x; a.y += v[k][i].y; a.z += v[k][i].z; a.w += v[k][i].w; }
                *(uint32_t*)(orow + (2 * k + w) * 64) = pack_bf16(a.x, a.y);
                *(uint32_t*)(orow + (2 * k + w) * 64 + 8 * 2 * kD) = pack_bf16(a.z, a.w);
            }
            if (tid == 0) TS(18);
        }
    }
}

typedef CUresult (*EncodeFn)(CUtensorMap*, CUtensorMapDataType, cuuint32_t, void*, const cuuint64_t*, const cuuint64_t*,
                             const cuuint32_t*, const cuuint32_t*, CUtensorMapInterleave, CUtensorMapSwizzle,
                             CUtensorMapL2promotion, CUtensorMapFloatOOBfill);

void make_map(EncodeFn fn, CUtensorMap* m, const void* ptr, uint64_t cols, uint64_t rows, uint32_t box_rows) {
    cuuint64_t dims[2] = {cols, rows};
    cuuint64_t strides[1] = {cols * 2};
    cuuint32_t box[2] = {64, box_rows};
    cuuint32_t es[2] = {1, 1};
    fn(m, CU_TENSOR_MAP_DATA_TYPE_BFLOAT16, 2, const_cast<void*>(ptr), dims, strides, box, es, CU_TENSOR_MAP_INTERLEAVE_NONE,
       CU_TENSOR_MAP_SWIZZLE_128B, CU_TENSOR_MAP_L2_PROMOTION_L2_256B, CU_TENSOR_MAP_FLOAT_OOB_FILL_NONE);
}

}

extern "C" void kernel_launch(void* const* d_in, const int* in_sizes, int n_in, void* d_out, int out_size) {
    static EncodeFn enc = nullptr;
    if (!enc) {
        void* fn = nullptr;
        cudaDriverEntryPointQueryResult st;
        cudaGetDriverEntryPoint("cuTensorMapEncodeTiled", &fn, cudaEnableDefault, &st);
        enc = (EncodeFn)fn;
        cudaFuncSetAttribute(fused_gqa_kernel, cudaFuncAttributeMaxDynamicSharedMemorySize, SMEM_BYTES);
    }
    Params P;
    for (int blk = 0; blk < 2; blk++) {
        const void* x = d_in[blk * 5 + 0];
        const void* k = d_in[blk * 5 + 1];
        const void* v = d_in[blk * 5 + 2];
        const void* wq = d_in[blk * 5 + 3];
        const void* wo = d_in[blk * 5 + 4];
        make_map(enc, &P.x[blk], x, kD, kB * kSq, 64);
        make_map(enc, &P.wq[blk], wq, kHq * kDh, kD, 32);
        make_map(enc, &P.k[blk], k, kDh, (uint64_t)kB * kHkv * kSk, 128);
        make_map(enc, &P.v[blk], v, kDh, (uint64_t)kB * kHkv * kSk, 128);
        make_map(enc, &P.wo[blk], wo, kD, kHq * kDh, 128);
        P.wqp[blk] = (const __nv_bfloat16*)wq;
        P.kp[blk] = (const __nv_bfloat16*)k;
        P.vp[blk] = (const __nv_bfloat16*)v;
        P.wop[blk] = (const __nv_bfloat16*)wo;
    }
    P.out = (__nv_bfloat16*)d_out;
    fused_gqa_kernel<<<128, 384, SMEM_BYTES>>>(P);
}
```

```cpp
#include <cuda_runtime.h>
#include <cuda_bf16.h>
#include <cuda.h>
#include <stdint.h>

namespace {

constexpr int kB = 8, kSq = 64, kD = 576, kHq = 32, kHkv = 16, kSk = 512, kDh = 128;
constexpr int NSTAGE = 5;
constexpr int STAGE_BYTES = 32768;
constexpr int R_BYTES = 65536;
constexpr int SMEM_BYTES = R_BYTES + NSTAGE * STAGE_BYTES + 1024   + 256  ;
constexpr int N_WQ = 18;
#define PF_DIST_V 4
#define PF_WQ 0
#define PF_SLEEP 1000
constexpr int PF_DIST = PF_DIST_V;

struct __align__(64) Params {
    CUtensorMap x[2], wq[2], k[2], v[2], wo[2];
    const __nv_bfloat16* wqp[2];
    const __nv_bfloat16* kp[2];
    const __nv_bfloat16* vp[2];
    const __nv_bfloat16* wop[2];
    __nv_bfloat16* out;
};

__device__ float4 g_part[16 * 80 * 8 * 128];
__device__ float4 g_own[128 * 2 * 5 * 8 * 128];
__device__ unsigned int g_cnt[16 * 9 * 32];
#define TS(k) do {} while (0)

__device__ __forceinline__ uint32_t smem_u32(const void* p) { return (uint32_t)__cvta_generic_to_shared(p); }
__device__ __forceinline__ void mbar_init(uint32_t bar, int cnt) {
    asm volatile("mbarrier.init.shared::cta.b64 [%0], %1;" ::"r"(bar), "r"(cnt));
}
__device__ __forceinline__ void mbar_expect_tx(uint32_t bar, uint32_t bytes) {
    asm volatile("mbarrier.arrive.expect_tx.shared::cta.b64 _, [%0], %1;" ::"r"(bar), "r"(bytes) : "memory");
}
__device__ __forceinline__ void mbar_arrive(uint32_t bar) {
    asm volatile("mbarrier.arrive.shared::cta.b64 _, [%0];" ::"r"(bar) : "memory");
}
__device__ __forceinline__ bool mbar_try(uint32_t bar, uint32_t parity) {
    uint32_t ok;
    asm volatile("{\n.reg .pred p;\nmbarrier.try_wait.parity.shared::cta.b64 p, [%1], %2;\nselp.u32 %0, 1, 0, p;\n}\n"
                 : "=r"(ok) : "r"(bar), "r"(parity) : "memory");
    return ok != 0;
}
__device__ __forceinline__ void mbar_wait(uint32_t bar, uint32_t parity) {
    if (mbar_try(bar, parity)) return;
    uint32_t n = 0;
    while (!mbar_try(bar, parity)) {
        if (++n > (1u << 20)) break;
    }
}
__device__ __forceinline__ void tma_2d(uint32_t dst, const CUtensorMap* tm, int c0, int c1, uint32_t bar) {
    asm volatile("cp.async.bulk.tensor.2d.shared::cluster.global.mbarrier::complete_tx::bytes [%0], [%1, {%3, %4}], [%2];"
                 ::"r"(dst), "l"(tm), "r"(bar), "r"(c0), "r"(c1) : "memory");
}
__device__ __forceinline__ void l2_prefetch(const void* p, uint32_t bytes) {
    asm volatile("cp.async.bulk.prefetch.L2.global [%0], %1;" ::"l"(p), "r"(bytes) : "memory");
}
__device__ __forceinline__ uint32_t l2_touch(const void* p) {
    uint32_t v;
    asm volatile("ld.global.L2::256B.b32 %0, [%1];" : "=r"(v) : "l"(p) : "memory");
    return v;
}
__device__ __forceinline__ void wg_fence() { asm volatile("wgmma.fence.sync.aligned;" ::: "memory"); }
__device__ __forceinline__ void wg_commit() { asm volatile("wgmma.commit_group.sync.aligned;" ::: "memory"); }
template <int N> __device__ __forceinline__ void wg_wait() { asm volatile("wgmma.wait_group.sync.aligned %0;" ::"n"(N) : "memory"); }
template <int N> __device__ __forceinline__ void fence_regs(float (&d)[N]) {
#pragma unroll
    for (int i = 0; i < N; i++) asm volatile("" : "+f"(d[i])::"memory");
}
__device__ __forceinline__ uint64_t mk_desc(uint32_t addr, uint32_t lbo, uint32_t sbo) {
    return (uint64_t)((addr & 0x3FFFF) >> 4) | ((uint64_t)(lbo >> 4) << 16) | ((uint64_t)(sbo >> 4) << 32) | (1ull << 62);
}
__device__ __forceinline__ uint32_t pack_bf16(float a, float b) {
    uint32_t r;
    asm("cvt.rn.bf16x2.f32 %0, %1, %2;" : "=r"(r) : "f"(b), "f"(a));
    return r;
}
__device__ __forceinline__ float ex2(float x) {
    float y;
    asm("ex2.approx.ftz.f32 %0, %1;" : "=f"(y) : "f"(x));
    return y;
}
template <int ID, int N> __device__ __forceinline__ void bar_sync() { asm volatile("bar.sync %0, %1;" ::"n"(ID), "n"(N) : "memory"); }
template <int ID, int N> __device__ __forceinline__ void bar_arrive() { asm volatile("bar.arrive %0, %1;" ::"n"(ID), "n"(N) : "memory"); }
__device__ __forceinline__ void sts128(uint32_t addr, uint32_t a, uint32_t b, uint32_t c, uint32_t d) {
    asm volatile("st.shared.v4.b32 [%0], {%1,%2,%3,%4};" ::"r"(addr), "r"(a), "r"(b), "r"(c), "r"(d) : "memory");
}
__device__ __forceinline__ void lds128(uint32_t addr, uint32_t (&r)[4]) {
    asm volatile("ld.shared.v4.b32 {%0,%1,%2,%3}, [%4];" : "=r"(r[0]), "=r"(r[1]), "=r"(r[2]), "=r"(r[3]) : "r"(addr) : "memory");
}

__device__ __forceinline__ void wgmma_ss_n256_tb(float (&d)[128], uint64_t da, uint64_t db, int sd) {
    asm volatile("{\n.reg .pred p;\nsetp.ne.b32 p, %130, 0;\n"
        "wgmma.mma_async.sync.aligned.m64n256k16.f32.bf16.bf16 "
        "{%0, %1, %2, %3, %4, %5, %6, %7, %8, %9, %10, %11, %12, %13, %14, %15, %16, %17, %18, %19, %20, %21, %22, %23, %24, %25, %26, %27, %28, %29, %30, %31, %32, %33, %34, %35, %36, %37, %38, %39, %40, %41, %42, %43, %44, %45, %46, %47, %48, %49, %50, %51, %52, %53, %54, %55, %56, %57, %58, %59, %60, %61, %62, %63, %64, %65, %66, %67, %68, %69, %70, %71, %72, %73, %74, %75, %76, %77, %78, %79, %80, %81, %82, %83, %84, %85, %86, %87, %88, %89, %90, %91, %92, %93, %94, %95, %96, %97, %98, %99, %100, %101, %102, %103, %104, %105, %106, %107, %108, %109, %110, %111, %112, %113, %114, %115, %116, %117, %118, %119, %120, %121, %122, %123, %124, %125, %126, %127}, "
        "%128, %129, p, 1, 1, 0, 1;\n}\n"
        : "+f"(d[0]), "+f"(d[1]), "+f"(d[2]), "+f"(d[3]), "+f"(d[4]), "+f"(d[5]), "+f"(d[6]), "+f"(d[7]), "+f"(d[8]), "+f"(d[9]), "+f"(d[10]), "+f"(d[11]), "+f"(d[12]), "+f"(d[13]), "+f"(d[14]), "+f"(d[15]), "+f"(d[16]), "+f"(d[17]), "+f"(d[18]), "+f"(d[19]), "+f"(d[20]), "+f"(d[21]), "+f"(d[22]), "+f"(d[23]), "+f"(d[24]), "+f"(d[25]), "+f"(d[26]), "+f"(d[27]), "+f"(d[28]), "+f"(d[29]), "+f"(d[30]), "+f"(d[31]), "+f"(d[32]), "+f"(d[33]), "+f"(d[34]), "+f"(d[35]), "+f"(d[36]), "+f"(d[37]), "+f"(d[38]), "+f"(d[39]), "+f"(d[40]), "+f"(d[41]), "+f"(d[42]), "+f"(d[43]), "+f"(d[44]), "+f"(d[45]), "+f"(d[46]), "+f"(d[47]), "+f"(d[48]), "+f"(d[49]), "+f"(d[50]), "+f"(d[51]), "+f"(d[52]), "+f"(d[53]), "+f"(d[54]), "+f"(d[55]), "+f"(d[56]), "+f"(d[57]), "+f"(d[58]), "+f"(d[59]), "+f"(d[60]), "+f"(d[61]), "+f"(d[62]), "+f"(d[63]), "+f"(d[64]), "+f"(d[65]), "+f"(d[66]), "+f"(d[67]), "+f"(d[68]), "+f"(d[69]), "+f"(d[70]), "+f"(d[71]), "+f"(d[72]), "+f"(d[73]), "+f"(d[74]), "+f"(d[75]), "+f"(d[76]), "+f"(d[77]), "+f"(d[78]), "+f"(d[79]), "+f"(d[80]), "+f"(d[81]), "+f"(d[82]), "+f"(d[83]), "+f"(d[84]), "+f"(d[85]), "+f"(d[86]), "+f"(d[87]), "+f"(d[88]), "+f"(d[89]), "+f"(d[90]), "+f"(d[91]), "+f"(d[92]), "+f"(d[93]), "+f"(d[94]), "+f"(d[95]), "+f"(d[96]), "+f"(d[97]), "+f"(d[98]), "+f"(d[99]), "+f"(d[100]), "+f"(d[101]), "+f"(d[102]), "+f"(d[103]), "+f"(d[104]), "+f"(d[105]), "+f"(d[106]), "+f"(d[107]), "+f"(d[108]), "+f"(d[109]), "+f"(d[110]), "+f"(d[111]), "+f"(d[112]), "+f"(d[113]), "+f"(d[114]), "+f"(d[115]), "+f"(d[116]), "+f"(d[117]), "+f"(d[118]), "+f"(d[119]), "+f"(d[120]), "+f"(d[121]), "+f"(d[122]), "+f"(d[123]), "+f"(d[124]), "+f"(d[125]), "+f"(d[126]), "+f"(d[127])
        : "l"(da), "l"(db), "r"(sd));
}
__device__ __forceinline__ void wgmma_rs_n128(float (&d)[64], uint32_t a0, uint32_t a1, uint32_t a2, uint32_t a3, uint64_t db, int sd) {
    asm volatile("{\n.reg .pred p;\nsetp.ne.b32 p, %69, 0;\n"
        "wgmma.mma_async.sync.aligned.m64n128k16.f32.bf16.bf16 "
        "{%0, %1, %2, %3, %4, %5, %6, %7, %8, %9, %10, %11, %12, %13, %14, %15, %16, %17, %18, %19, %20, %21, %22, %23, %24, %25, %26, %27, %28, %29, %30, %31, %32, %33, %34, %35, %36, %37, %38, %39, %40, %41, %42, %43, %44, %45, %46, %47, %48, %49, %50, %51, %52, %53, %54, %55, %56, %57, %58, %59, %60, %61, %62, %63}, "
        "{%64, %65, %66, %67}, %68, p, 1, 1, 0;\n}\n"
        : "+f"(d[0]), "+f"(d[1]), "+f"(d[2]), "+f"(d[3]), "+f"(d[4]), "+f"(d[5]), "+f"(d[6]), "+f"(d[7]), "+f"(d[8]), "+f"(d[9]), "+f"(d[10]), "+f"(d[11]), "+f"(d[12]), "+f"(d[13]), "+f"(d[14]), "+f"(d[15]), "+f"(d[16]), "+f"(d[17]), "+f"(d[18]), "+f"(d[19]), "+f"(d[20]), "+f"(d[21]), "+f"(d[22]), "+f"(d[23]), "+f"(d[24]), "+f"(d[25]), "+f"(d[26]), "+f"(d[27]), "+f"(d[28]), "+f"(d[29]), "+f"(d[30]), "+f"(d[31]), "+f"(d[32]), "+f"(d[33]), "+f"(d[34]), "+f"(d[35]), "+f"(d[36]), "+f"(d[37]), "+f"(d[38]), "+f"(d[39]), "+f"(d[40]), "+f"(d[41]), "+f"(d[42]), "+f"(d[43]), "+f"(d[44]), "+f"(d[45]), "+f"(d[46]), "+f"(d[47]), "+f"(d[48]), "+f"(d[49]), "+f"(d[50]), "+f"(d[51]), "+f"(d[52]), "+f"(d[53]), "+f"(d[54]), "+f"(d[55]), "+f"(d[56]), "+f"(d[57]), "+f"(d[58]), "+f"(d[59]), "+f"(d[60]), "+f"(d[61]), "+f"(d[62]), "+f"(d[63])
        : "r"(a0), "r"(a1), "r"(a2), "r"(a3), "l"(db), "r"(sd));
}
__device__ __forceinline__ void wgmma_rs_n128_tb(float (&d)[64], uint32_t a0, uint32_t a1, uint32_t a2, uint32_t a3, uint64_t db, int sd) {
    asm volatile("{\n.reg .pred p;\nsetp.ne.b32 p, %69, 0;\n"
        "wgmma.mma_async.sync.aligned.m64n128k16.f32.bf16.bf16 "
        "{%0, %1, %2, %3, %4, %5, %6, %7, %8, %9, %10, %11, %12, %13, %14, %15, %16, %17, %18, %19, %20, %21, %22, %23, %24, %25, %26, %27, %28, %29, %30, %31, %32, %33, %34, %35, %36, %37, %38, %39, %40, %41, %42, %43, %44, %45, %46, %47, %48, %49, %50, %51, %52, %53, %54, %55, %56, %57, %58, %59, %60, %61, %62, %63}, "
        "{%64, %65, %66, %67}, %68, p, 1, 1, 1;\n}\n"
        : "+f"(d[0]), "+f"(d[1]), "+f"(d[2]), "+f"(d[3]), "+f"(d[4]), "+f"(d[5]), "+f"(d[6]), "+f"(d[7]), "+f"(d[8]), "+f"(d[9]), "+f"(d[10]), "+f"(d[11]), "+f"(d[12]), "+f"(d[13]), "+f"(d[14]), "+f"(d[15]), "+f"(d[16]), "+f"(d[17]), "+f"(d[18]), "+f"(d[19]), "+f"(d[20]), "+f"(d[21]), "+f"(d[22]), "+f"(d[23]), "+f"(d[24]), "+f"(d[25]), "+f"(d[26]), "+f"(d[27]), "+f"(d[28]), "+f"(d[29]), "+f"(d[30]), "+f"(d[31]), "+f"(d[32]), "+f"(d[33]), "+f"(d[34]), "+f"(d[35]), "+f"(d[36]), "+f"(d[37]), "+f"(d[38]), "+f"(d[39]), "+f"(d[40]), "+f"(d[41]), "+f"(d[42]), "+f"(d[43]), "+f"(d[44]), "+f"(d[45]), "+f"(d[46]), "+f"(d[47]), "+f"(d[48]), "+f"(d[49]), "+f"(d[50]), "+f"(d[51]), "+f"(d[52]), "+f"(d[53]), "+f"(d[54]), "+f"(d[55]), "+f"(d[56]), "+f"(d[57]), "+f"(d[58]), "+f"(d[59]), "+f"(d[60]), "+f"(d[61]), "+f"(d[62]), "+f"(d[63])
        : "r"(a0), "r"(a1), "r"(a2), "r"(a3), "l"(db), "r"(sd));
}
__device__ __forceinline__ void wgmma_rs_n64_tb(float (&d)[32], uint32_t a0, uint32_t a1, uint32_t a2, uint32_t a3, uint64_t db, int sd) {
    asm volatile("{\n.reg .pred p;\nsetp.ne.b32 p, %37, 0;\n"
        "wgmma.mma_async.sync.aligned.m64n64k16.f32.bf16.bf16 "
        "{%0, %1, %2, %3, %4, %5, %6, %7, %8, %9, %10, %11, %12, %13, %14, %15, %16, %17, %18, %19, %20, %21, %22, %23, %24, %25, %26, %27, %28, %29, %30, %31}, "
        "{%32, %33, %34, %35}, %36, p, 1, 1, 1;\n}\n"
        : "+f"(d[0]), "+f"(d[1]), "+f"(d[2]), "+f"(d[3]), "+f"(d[4]), "+f"(d[5]), "+f"(d[6]), "+f"(d[7]), "+f"(d[8]), "+f"(d[9]), "+f"(d[10]), "+f"(d[11]), "+f"(d[12]), "+f"(d[13]), "+f"(d[14]), "+f"(d[15]), "+f"(d[16]), "+f"(d[17]), "+f"(d[18]), "+f"(d[19]), "+f"(d[20]), "+f"(d[21]), "+f"(d[22]), "+f"(d[23]), "+f"(d[24]), "+f"(d[25]), "+f"(d[26]), "+f"(d[27]), "+f"(d[28]), "+f"(d[29]), "+f"(d[30]), "+f"(d[31])
        : "r"(a0), "r"(a1), "r"(a2), "r"(a3), "l"(db), "r"(sd));
}

__global__ void __launch_bounds__(384, 1) fused_gqa_kernel(const __grid_constant__ Params P) {
    extern __shared__ uint8_t smem_raw[];
    const uint32_t base = (smem_u32(smem_raw) + 1023u) & ~1023u;
    const uint32_t smR = base;
    const uint32_t smS = base + R_BYTES;
    const uint32_t bars = smS + NSTAGE * STAGE_BYTES;
    const uint32_t prog = bars + 8 * (2 * NSTAGE + 10);
    const int tid = threadIdx.x;
    const int wid = __shfl_sync(0xffffffffu, tid >> 5, 0);
    const int lane = tid & 31;

    const int cta = blockIdx.x;
    const int blk = cta >> 6;
    const int hp = (cta >> 3) & 7;
    const int b = cta & 7;
    const int grp = blk * 8 + b;

    if (tid == 0) {
        TS(0);
        for (int i = 0; i < NSTAGE; i++) {
            mbar_init(bars + 8 * i, 1);
            mbar_init(bars + 8 * (NSTAGE + i), 8);
        }
        for (int i = 0; i < 10; i++) mbar_init(bars + 8 * (2 * NSTAGE + i), 4);
        asm volatile("st.volatile.shared.u32 [%0], %1;" ::"r"(prog), "r"(0) : "memory");
        asm volatile("fence.mbarrier_init.release.cluster;" ::: "memory");
        asm volatile("fence.proxy.async.shared::cta;" ::: "memory");
    }
    __syncthreads();

    if (wid >= 8) {
        asm volatile("setmaxnreg.dec.sync.aligned.u32 40;");
        if (wid == 8) {
            if (lane == 0) {
                int slot = 0, ph = 1;
                for (int s = 0; s < N_WQ; s++) {
                    const uint32_t fb = bars + 8 * slot;
                    mbar_wait(bars + 8 * (NSTAGE + slot), ph);
                    const uint32_t dst = smS + slot * STAGE_BYTES;
                    mbar_expect_tx(fb, (s & 1) ? STAGE_BYTES : STAGE_BYTES + 8192);
                    if (!(s & 1)) tma_2d(smR + ((s >> 1) & 7) * 8192, &P.x[blk], (s >> 1) * 64, b * 64, fb);
#pragma unroll
                    for (int p = 0; p < 8; p++) {
                        const int w = p >> 2, j = (p >> 1) & 1, glo = p & 1;
                        tma_2d(dst + p * 4096, &P.wq[blk], hp * 512 + (j * 4 + w * 2 + glo) * 64, s * 32, fb);
                    }
                    if (++slot == NSTAGE) { slot = 0; ph ^= 1; }
                }
                for (int i = 0; i < 34; i++) {
                    const int u = (i >= 17), r = i - 17 * u;
                    const uint32_t fb = bars + 8 * slot;
                    mbar_wait(bars + 8 * (NSTAGE + slot), ph);
                    const uint32_t dst = smS + slot * STAGE_BYTES;
                    mbar_expect_tx(fb, STAGE_BYTES);
                    if (r < 8) {
                        const int row = (b * kHkv + hp * 2 + u) * kSk + (r >> 1) * 128;
                        const CUtensorMap* tm = (r & 1) ? &P.v[blk] : &P.k[blk];
                        tma_2d(dst, tm, 0, row, fb);
                        tma_2d(dst + 16384, tm, 64, row, fb);
                    } else {
                        const int q = r - 8, kh = q & 1, row = hp * 512 + u * 256;
                        const int c0 = (q >> 1) * 128;
                        tma_2d(dst, &P.wo[blk], c0, row + kh * 128, fb);
                        tma_2d(dst + 16384, &P.wo[blk], (q < 8) ? c0 + 64 : c0, row + (kh ^ 1) * 128, fb);
                    }
                    asm volatile("st.volatile.shared.u32 [%0], %1;" ::"r"(prog), "r"(i + 1) : "memory");
                    if (++slot == NSTAGE) { slot = 0; ph ^= 1; }
                }
            }
        } else if (wid == 11) {
            if (PF_DIST > 0) {
                uint32_t sink = 0;
                if (PF_WQ) {
                    const char* wqs = (const char*)(P.wqp[blk] + hp * 512) + (size_t)(160 + b * 52) * 8192;
#pragma unroll
                    for (int h = 0; h < 2; h++) {
#pragma unroll
                        for (int j = 0; j < 4; j++) {
                            const int e = (h * 4 + j) * 32 + lane;
                            if (e < 208) sink |= l2_touch(wqs + (size_t)(e >> 2) * 8192 + (e & 3) * 256);
                        }
                        if (sink == 0x9E3779B9u) asm volatile("st.volatile.shared.u32 [%0], %1;" ::"r"(prog + 4), "r"(sink) : "memory");
                    }
                }
                const char* kbase = (const char*)(P.kp[blk] + (size_t)(b * kHkv + hp * 2) * kSk * kDh);
                const char* vbase = (const char*)(P.vp[blk] + (size_t)(b * kHkv + hp * 2) * kSk * kDh);
                const char* wos = (const char*)(P.wop[blk] + (size_t)hp * 512 * kD) + (size_t)b * 36864;
                for (int i = 0; i < 18; i++) {
                    const int u = (i >= 9), r = i - 9 * u;
                    const int pos = u * 17 + r;
                    if (pos >= PF_DIST) {
                        uint32_t pr, n = 0;
                        while (true) {
                            asm volatile("ld.volatile.shared.u32 %0, [%1];" : "=r"(pr) : "r"(prog) : "memory");
                            if ((int)pr + PF_DIST >= pos) break;
                            if (++n > (1u << 22)) break;
                            __nanosleep(100);
                        }
                    }
                    if (r < 8) {
                        const char* p = ((r & 1) ? vbase : kbase) + (size_t)(u * 4 + (r >> 1)) * 32768 + lane * 256;
#pragma unroll
                        for (int j = 0; j < 4; j++) sink |= l2_touch(p + j * 8192);
                    } else {
                        const char* p = wos + (size_t)u * 294912 + lane * 256;
#pragma unroll
                        for (int j = 0; j < 5; j++) if (j * 32 + lane < 144) sink |= l2_touch(p + j * 8192);
                    }
                    if (sink == 0x9E3779B9u) asm volatile("st.volatile.shared.u32 [%0], %1;" ::"r"(prog + 4), "r"(sink) : "memory");
                }
            }
        } else {
            const int hw = wid - 9;
            for (int k = 0; k < 5; k++) {
                mbar_wait(bars + 8 * (2 * NSTAGE + hw * 5 + k), 0);
                const int c = (k < 4) ? (2 * k + hw) : 8;
                asm volatile("fence.acq_rel.gpu;" ::: "memory");
                asm volatile("red.relaxed.gpu.global.add.u32 [%0], 1;" ::"l"(&g_cnt[(grp * 9 + c) * 32 + lane]) : "memory");
            }
        }
    } else {
        asm volatile("setmaxnreg.inc.sync.aligned.u32 232;");
        const int w = wid >> 2;
        const int t = tid & 127;
        int slot = 0, ph = 0;
        uint32_t qf[8][4];
        const uint32_t stash = smR + (1 + w) * 16384 + t * 16;
        {
            float acc[128];
            int pslot = 0;
            for (int s = 0; s < N_WQ; s++) {
                mbar_wait(bars + 8 * slot, ph);
                if (tid == 0 && s == 0) TS(20);
                if (tid == 0 && s == 5) TS(21);
                if (tid == 0 && s == 10) TS(22);
                const uint64_t da = mk_desc(smR + ((s >> 1) & 7) * 8192 + (s & 1) * 64, 16, 1024);
                const uint64_t db = mk_desc(smS + slot * STAGE_BYTES + w * 16384, 4096, 1024);
                wg_fence();
                wgmma_ss_n256_tb(acc, da, db, s != 0);
                wgmma_ss_n256_tb(acc, da + 2, db + 128, 1);
                wg_commit();
                if (s > 0) {
                    wg_wait<1>();
                    if (lane == 0) mbar_arrive(bars + 8 * (NSTAGE + pslot));
                }
                pslot = slot;
                if (++slot == NSTAGE) { slot = 0; ph ^= 1; }
            }
            wg_wait<0>();
            if (lane == 0) mbar_arrive(bars + 8 * (NSTAGE + pslot));
            fence_regs(acc);
            if (tid == 0) TS(1);
#pragma unroll
            for (int kk = 0; kk < 8; kk++) {
#pragma unroll
                for (int i = 0; i < 4; i++) qf[kk][i] = pack_bf16(acc[8 * kk + 2 * i], acc[8 * kk + 2 * i + 1]);
                sts128(stash + kk * 2048,
                       pack_bf16(acc[64 + 8 * kk + 0], acc[64 + 8 * kk + 1]), pack_bf16(acc[64 + 8 * kk + 2], acc[64 + 8 * kk + 3]),
                       pack_bf16(acc[64 + 8 * kk + 4], acc[64 + 8 * kk + 5]), pack_bf16(acc[64 + 8 * kk + 6], acc[64 + 8 * kk + 7]));
            }
        }
        if (w == 1) bar_arrive<5, 256>();
        const float sc = 0.08838834764831845f * 1.4426950408889634f;
        float4* own = g_own + (size_t)(cta * 2 + w) * 5 * 1024 + t;
#pragma unroll
        for (int u = 0; u < 2; u++) {
            uint32_t af[16][4];
            {
                if (u == 1) {
#pragma unroll
                    for (int kk = 0; kk < 8; kk++) lds128(stash + kk * 2048, qf[kk]);
                }
                float o[64];
                float m0 = -INFINITY, m1 = -INFINITY, l0 = 0.f, l1 = 0.f;
                uint32_t pf[8][4];
#pragma unroll 1
                for (int tt = 0; tt <= 4; tt++) {
                    float s[64];
                    int vslot = slot;
                    if (tt > 0) {
                        mbar_wait(bars + 8 * slot, ph);
                        if (++slot == NSTAGE) { slot = 0; ph ^= 1; }
                    }
                    if (tt < 4) mbar_wait(bars + 8 * slot, ph);
                    if (tid == 0) TS(32 + u * 20 + tt * 4);
                    if (w == 0) bar_sync<5, 256>(); else bar_sync<6, 256>();
                    wg_fence();
                    if (tt > 0) {
                        const uint64_t db = mk_desc(smS + vslot * STAGE_BYTES, 16384, 1024);
#pragma unroll
                        for (int kk = 0; kk < 8; kk++)
                            wgmma_rs_n128_tb(o, pf[kk][0], pf[kk][1], pf[kk][2], pf[kk][3], db + kk * 128, (tt > 1) || (kk != 0));
                        wg_commit();
                    }
                    if (tt < 4) {
                        const uint64_t db = mk_desc(smS + slot * STAGE_BYTES, 16, 1024);
#pragma unroll
                        for (int kk = 0; kk < 8; kk++)
                            wgmma_rs_n128(s, qf[kk][0], qf[kk][1], qf[kk][2], qf[kk][3], db + (kk >> 2) * 1024 + (kk & 3) * 2, kk != 0);
                        wg_commit();
                    }
                    if (w == 0) bar_arrive<6, 256>(); else if (!(u == 1 && tt == 4)) bar_arrive<5, 256>();
                    if (tid == 0) TS(32 + u * 20 + tt * 4 + 1);
                    wg_wait<0>();
                    fence_regs(o);
                    fence_regs(s);
                    if (tid == 0) TS(32 + u * 20 + tt * 4 + 2);
                    if (tt > 0 && lane == 0) mbar_arrive(bars + 8 * (NSTAGE + vslot));
                    if (tt == 4) break;
                    if (lane == 0) mbar_arrive(bars + 8 * (NSTAGE + slot));
                    if (++slot == NSTAGE) { slot = 0; ph ^= 1; }
                    float mx0 = s[0], mx1 = s[2];
#pragma unroll
                    for (int j = 0; j < 16; j++) {
                        mx0 = fmaxf(mx0, fmaxf(s[4 * j], s[4 * j + 1]));
                        mx1 = fmaxf(mx1, fmaxf(s[4 * j + 2], s[4 * j + 3]));
                    }
                    mx0 = fmaxf(mx0, __shfl_xor_sync(0xffffffffu, mx0, 1));
                    mx1 = fmaxf(mx1, __shfl_xor_sync(0xffffffffu, mx1, 1));
                    mx0 = fmaxf(mx0, __shfl_xor_sync(0xffffffffu, mx0, 2));
                    mx1 = fmaxf(mx1, __shfl_xor_sync(0xffffffffu, mx1, 2));
                    const float mn0 = fmaxf(m0, mx0), mn1 = fmaxf(m1, mx1);
                    const float al0 = ex2((m0 - mn0) * sc), al1 = ex2((m1 - mn1) * sc);
                    m0 = mn0; m1 = mn1;
                    const float ms0 = mn0 * sc, ms1 = mn1 * sc;
                    float rs0 = 0.f, rs1 = 0.f;
#pragma unroll
                    for (int j = 0; j < 16; j++) {
                        const float p0 = ex2(fmaf(s[4 * j], sc, -ms0)), p1 = ex2(fmaf(s[4 * j + 1], sc, -ms0));
                        const float p2 = ex2(fmaf(s[4 * j + 2], sc, -ms1)), p3 = ex2(fmaf(s[4 * j + 3], sc, -ms1));
                        rs0 += p0 + p1; rs1 += p2 + p3;
                        pf[j >> 1][(j & 1) * 2] = pack_bf16(p0, p1);
                        pf[j >> 1][(j & 1) * 2 + 1] = pack_bf16(p2, p3);
                    }
                    l0 = l0 * al0 + rs0; l1 = l1 * al1 + rs1;
                    if (tt > 0) {
#pragma unroll
                        for (int j = 0; j < 16; j++) { o[4 * j] *= al0; o[4 * j + 1] *= al0; o[4 * j + 2] *= al1; o[4 * j + 3] *= al1; }
                    }
                    if (tid == 0) TS(32 + u * 20 + tt * 4 + 3);
                }
                if (tid == 0) TS(2 + u);
                l0 += __shfl_xor_sync(0xffffffffu, l0, 1);
                l1 += __shfl_xor_sync(0xffffffffu, l1, 1);
                l0 += __shfl_xor_sync(0xffffffffu, l0, 2);
                l1 += __shfl_xor_sync(0xffffffffu, l1, 2);
                const float i0 = 1.f / l0, i1 = 1.f / l1;
                const uint32_t zown = smR + ((u == 0) ? (w ? 3 : 0) : (w ? 2 : 1)) * 16384 + t * 16;
#pragma unroll
                for (int kk = 0; kk < 8; kk++) {
                    af[kk][0] = pack_bf16(o[8 * kk + 0] * i0, o[8 * kk + 1] * i0);
                    af[kk][1] = pack_bf16(o[8 * kk + 2] * i1, o[8 * kk + 3] * i1);
                    af[kk][2] = pack_bf16(o[8 * kk + 4] * i0, o[8 * kk + 5] * i0);
                    af[kk][3] = pack_bf16(o[8 * kk + 6] * i1, o[8 * kk + 7] * i1);
                    sts128(zown + kk * 2048, af[kk][0], af[kk][1], af[kk][2], af[kk][3]);
                }
            }
            {
                float acc[2][32];
                float4 pre[2][8];
                if (u == 1) {
#pragma unroll
                    for (int k = 0; k < 2; k++)
#pragma unroll
                        for (int j = 0; j < 8; j++) pre[k][j] = __ldcg(own + (k * 8 + j) * 128);
                }
                bar_sync<4, 256>();
                const uint32_t zoth = smR + ((u == 0) ? (w ? 0 : 3) : (w ? 1 : 2)) * 16384 + t * 16;
#pragma unroll
                for (int kk = 0; kk < 8; kk++) lds128(zoth + kk * 2048, af[8 + kk]);
                int pslot = 0;
                float4* dst0 = g_part + (size_t)(grp * 80 + w * 8 + hp) * 1024 + t;
                float4* dst8 = g_part + (size_t)(grp * 80 + 64 + hp * 2 + w) * 1024 + t;
#pragma unroll
                for (int st = 0; st <= 9; st++) {
                    if (st < 9) {
                        const int kh = st & 1, ab = (st >> 1) & 1;
                        mbar_wait(bars + 8 * slot, ph);
                        const uint64_t db = mk_desc(smS + slot * STAGE_BYTES + w * 16384, 16384, 1024);
                        wg_fence();
#pragma unroll
                        for (int kk = 0; kk < 8; kk++)
                            wgmma_rs_n64_tb(acc[ab], af[kh * 8 + kk][0], af[kh * 8 + kk][1], af[kh * 8 + kk][2], af[kh * 8 + kk][3], db + kk * 128, (kh | kk) != 0);
                        wg_commit();
                    }
                    if (st > 0) {
                        if (st < 9) wg_wait<1>(); else wg_wait<0>();
                        if (lane == 0) mbar_arrive(bars + 8 * (NSTAGE + pslot));
                        if ((st & 1) == 0 || st == 9) {
                            const int k = (st - 1) >> 1, ab = k & 1;
                            fence_regs(acc[ab]);
                            if (u == 0) {
#pragma unroll
                                for (int j = 0; j < 8; j++) __stcg(own + (k * 8 + j) * 128, make_float4(acc[ab][4 * j], acc[ab][4 * j + 1], acc[ab][4 * j + 2], acc[ab][4 * j + 3]));
                            } else {
                                float4* dst = (k < 4) ? (dst0 + (size_t)k * 16 * 1024) : dst8;
#pragma unroll
                                for (int j = 0; j < 8; j++)
                                    __stcg(dst + j * 128, make_float4(acc[ab][4 * j] + pre[ab][j].x, acc[ab][4 * j + 1] + pre[ab][j].y,
                                                                      acc[ab][4 * j + 2] + pre[ab][j].z, acc[ab][4 * j + 3] + pre[ab][j].w));
                                __syncwarp();
                                if (lane == 0) mbar_arrive(bars + 8 * (2 * NSTAGE + w * 5 + k));
                                if (k + 2 < 5) {
#pragma unroll
                                    for (int j = 0; j < 8; j++) pre[ab][j] = __ldcg(own + ((k + 2) * 8 + j) * 128);
                                }
                            }
                            if (tid == 0) TS(4 + u * 8 + k);
                        }
                    }
                    if (st < 9) {
                        pslot = slot;
                        if (++slot == NSTAGE) { slot = 0; ph ^= 1; }
                    }
                }
            }
        }
        {
            const int nch = (w == 0) ? 5 : 4;
            if (lane < nch) {
                const int c = (lane < 4) ? (2 * lane + w) : 8;
                const unsigned need = (lane < 4) ? 8u : 16u;
                unsigned* cp = &g_cnt[(grp * 9 + c) * 32 + hp * 4 + (wid & 3)];
                unsigned v, n = 0;
                while (true) {
                    asm volatile("ld.acquire.gpu.global.u32 %0, [%1];" : "=r"(v) : "l"(cp) : "memory");
                    if (v >= need) break;
                    if (++n > (1u << 21)) break;
                }
                *cp = 0;
            }
            __syncwarp();
            if (tid == 0) TS(18);
            __nv_bfloat16* orow = P.out + (size_t)(b * 64 + (t >> 5) * 16 + (lane >> 2)) * (2 * kD) + blk * kD + hp * 8 + (lane & 3) * 2;
            const float4* src = g_part + ((size_t)(grp * 80 + w * 8) * 8 + hp) * 128 + t;
            float4 v[4][8];
#pragma unroll
            for (int k = 0; k < 4; k++)
#pragma unroll
                for (int i = 0; i < 8; i++) v[k][i] = __ldcg(src + (size_t)(k * 16 + i) * 1024);
            if (w == 0) {
                const float4* src8 = g_part + ((size_t)(grp * 80 + 64) * 8 + hp) * 128 + t;
                float4 u[16];
#pragma unroll
                for (int i = 0; i < 16; i++) u[i] = __ldcg(src8 + (size_t)i * 1024);
                float4 a = u[0];
#pragma unroll
                for (int i = 1; i < 16; i++) { a.x += u[i].x; a.y += u[i].y; a.z += u[i].z; a.w += u[i].w; }
                *(uint32_t*)(orow + 512) = pack_bf16(a.x, a.y);
                *(uint32_t*)(orow + 512 + 8 * 2 * kD) = pack_bf16(a.z, a.w);
            }
#pragma unroll
            for (int k = 0; k < 4; k++) {
                float4 a = v[k][0];
#pragma unroll
                for (int i = 1; i < 8; i++) { a.x += v[k][i].x; a.y += v[k][i].y; a.z += v[k][i].z; a.w += v[k][i].w; }
                *(uint32_t*)(orow + (2 * k + w) * 64) = pack_bf16(a.x, a.y);
                *(uint32_t*)(orow + (2 * k + w) * 64 + 8 * 2 * kD) = pack_bf16(a.z, a.w);
            }
            if (tid == 0) TS(19);
        }
    }
}

typedef CUresult (*EncodeFn)(CUtensorMap*, CUtensorMapDataType, cuuint32_t, void*, const cuuint64_t*, const cuuint64_t*,
                             const cuuint32_t*, const cuuint32_t*, CUtensorMapInterleave, CUtensorMapSwizzle,
                             CUtensorMapL2promotion, CUtensorMapFloatOOBfill);

void make_map(EncodeFn fn, CUtensorMap* m, const void* ptr, uint64_t cols, uint64_t rows, uint32_t box_rows) {
    cuuint64_t dims[2] = {cols, rows};
    cuuint64_t strides[1] = {cols * 2};
    cuuint32_t box[2] = {64, box_rows};
    cuuint32_t es[2] = {1, 1};
    fn(m, CU_TENSOR_MAP_DATA_TYPE_BFLOAT16, 2, const_cast<void*>(ptr), dims, strides, box, es, CU_TENSOR_MAP_INTERLEAVE_NONE,
       CU_TENSOR_MAP_SWIZZLE_128B, CU_TENSOR_MAP_L2_PROMOTION_L2_256B, CU_TENSOR_MAP_FLOAT_OOB_FILL_NONE);
}

}

extern "C" void kernel_launch(void* const* d_in, const int* in_sizes, int n_in, void* d_out, int out_size) {
    static EncodeFn enc = nullptr;
    if (!enc) {
        void* fn = nullptr;
        cudaDriverEntryPointQueryResult st;
        cudaGetDriverEntryPoint("cuTensorMapEncodeTiled", &fn, cudaEnableDefault, &st);
        enc = (EncodeFn)fn;
        cudaFuncSetAttribute(fused_gqa_kernel, cudaFuncAttributeMaxDynamicSharedMemorySize, SMEM_BYTES);
    }
    Params P;
    for (int blk = 0; blk < 2; blk++) {
        const void* x = d_in[blk * 5 + 0];
        const void* k = d_in[blk * 5 + 1];
        const void* v = d_in[blk * 5 + 2];
        const void* wq = d_in[blk * 5 + 3];
        const void* wo = d_in[blk * 5 + 4];
        make_map(enc, &P.x[blk], x, kD, kB * kSq, 64);
        make_map(enc, &P.wq[blk], wq, kHq * kDh, kD, 32);
        make_map(enc, &P.k[blk], k, kDh, (uint64_t)kB * kHkv * kSk, 128);
        make_map(enc, &P.v[blk], v, kDh, (uint64_t)kB * kHkv * kSk, 128);
        make_map(enc, &P.wo[blk], wo, kD, kHq * kDh, 128);
        P.wqp[blk] = (const __nv_bfloat16*)wq;
        P.kp[blk] = (const __nv_bfloat16*)k;
        P.vp[blk] = (const __nv_bfloat16*)v;
        P.wop[blk] = (const __nv_bfloat16*)wo;
    }
    P.out = (__nv_bfloat16*)d_out;
    fused_gqa_kernel<<<128, 384, SMEM_BYTES>>>(P);
}
```

```cpp
#include <cuda_runtime.h>
#include <cuda_bf16.h>
#include <cuda.h>
#include <stdint.h>

namespace {

constexpr int kB = 8, kSq = 64, kD = 576, kHq = 32, kHkv = 16, kSk = 512, kDh = 128;
constexpr int NSTAGE = 5;
constexpr int STAGE_BYTES = 32768;
constexpr int R_BYTES = 65536;
constexpr int SMEM_BYTES = R_BYTES + NSTAGE * STAGE_BYTES + 1024   + 256  ;
constexpr int N_WQ = 18;
#define PF_DIST_V 4
#define PF_WQ 0
#define PF_SLEEP 1000
constexpr int PF_DIST = PF_DIST_V;

struct __align__(64) Params {
    CUtensorMap x[2], wq[2], k[2], v[2], wo[2];
    const __nv_bfloat16* wqp[2];
    const __nv_bfloat16* kp[2];
    const __nv_bfloat16* vp[2];
    const __nv_bfloat16* wop[2];
    __nv_bfloat16* out;
};

__device__ float4 g_part[16 * 80 * 8 * 128];
__device__ float4 g_own[128 * 2 * 5 * 8 * 128];
__device__ unsigned int g_cnt[16 * 9 * 32];
#define TS(k) do {} while (0)

__device__ __forceinline__ uint32_t smem_u32(const void* p) { return (uint32_t)__cvta_generic_to_shared(p); }
__device__ __forceinline__ void mbar_init(uint32_t bar, int cnt) {
    asm volatile("mbarrier.init.shared::cta.b64 [%0], %1;" ::"r"(bar), "r"(cnt));
}
__device__ __forceinline__ void mbar_expect_tx(uint32_t bar, uint32_t bytes) {
    asm volatile("mbarrier.arrive.expect_tx.shared::cta.b64 _, [%0], %1;" ::"r"(bar), "r"(bytes) : "memory");
}
__device__ __forceinline__ void mbar_arrive(uint32_t bar) {
    asm volatile("mbarrier.arrive.shared::cta.b64 _, [%0];" ::"r"(bar) : "memory");
}
__device__ __forceinline__ bool mbar_try(uint32_t bar, uint32_t parity) {
    uint32_t ok;
    asm volatile("{\n.reg .pred p;\nmbarrier.try_wait.parity.shared::cta.b64 p, [%1], %2;\nselp.u32 %0, 1, 0, p;\n}\n"
                 : "=r"(ok) : "r"(bar), "r"(parity) : "memory");
    return ok != 0;
}
__device__ __forceinline__ void mbar_wait(uint32_t bar, uint32_t parity) {
    if (mbar_try(bar, parity)) return;
    uint32_t n = 0;
    while (!mbar_try(bar, parity)) {
        if (++n > (1u << 20)) break;
    }
}
__device__ __forceinline__ void tma_2d(uint32_t dst, const CUtensorMap* tm, int c0, int c1, uint32_t bar) {
    asm volatile("cp.async.bulk.tensor.2d.shared::cluster.global.mbarrier::complete_tx::bytes [%0], [%1, {%3, %4}], [%2];"
                 ::"r"(dst), "l"(tm), "r"(bar), "r"(c0), "r"(c1) : "memory");
}
__device__ __forceinline__ void l2_prefetch(const void* p, uint32_t bytes) {
    asm volatile("cp.async.bulk.prefetch.L2.global [%0], %1;" ::"l"(p), "r"(bytes) : "memory");
}
__device__ __forceinline__ uint32_t l2_touch(const void* p) {
    uint32_t v;
    asm volatile("ld.global.L2::256B.b32 %0, [%1];" : "=r"(v) : "l"(p) : "memory");
    return v;
}
__device__ __forceinline__ void wg_fence() { asm volatile("wgmma.fence.sync.aligned;" ::: "memory"); }
__device__ __forceinline__ void wg_commit() { asm volatile("wgmma.commit_group.sync.aligned;" ::: "memory"); }
template <int N> __device__ __forceinline__ void wg_wait() { asm volatile("wgmma.wait_group.sync.aligned %0;" ::"n"(N) : "memory"); }
template <int N> __device__ __forceinline__ void fence_regs(float (&d)[N]) {
#pragma unroll
    for (int i = 0; i < N; i++) asm volatile("" : "+f"(d[i])::"memory");
}
__device__ __forceinline__ uint64_t mk_desc(uint32_t addr, uint32_t lbo, uint32_t sbo) {
    return (uint64_t)((addr & 0x3FFFF) >> 4) | ((uint64_t)(lbo >> 4) << 16) | ((uint64_t)(sbo >> 4) << 32) | (1ull << 62);
}
__device__ __forceinline__ uint32_t pack_bf16(float a, float b) {
    uint32_t r;
    asm("cvt.rn.bf16x2.f32 %0, %1, %2;" : "=r"(r) : "f"(b), "f"(a));
    return r;
}
__device__ __forceinline__ float ex2(float x) {
    float y;
    asm("ex2.approx.ftz.f32 %0, %1;" : "=f"(y) : "f"(x));
    return y;
}
template <int ID, int N> __device__ __forceinline__ void bar_sync() { asm volatile("bar.sync %0, %1;" ::"n"(ID), "n"(N) : "memory"); }
template <int ID, int N> __device__ __forceinline__ void bar_arrive() { asm volatile("bar.arrive %0, %1;" ::"n"(ID), "n"(N) : "memory"); }
__device__ __forceinline__ void sts128(uint32_t addr, uint32_t a, uint32_t b, uint32_t c, uint32_t d) {
    asm volatile("st.shared.v4.b32 [%0], {%1,%2,%3,%4};" ::"r"(addr), "r"(a), "r"(b), "r"(c), "r"(d) : "memory");
}
__device__ __forceinline__ void lds128(uint32_t addr, uint32_t (&r)[4]) {
    asm volatile("ld.shared.v4.b32 {%0,%1,%2,%3}, [%4];" : "=r"(r[0]), "=r"(r[1]), "=r"(r[2]), "=r"(r[3]) : "r"(addr) : "memory");
}

__device__ __forceinline__ void wgmma_ss_n256_tb(float (&d)[128], uint64_t da, uint64_t db, int sd) {
    asm volatile("{\n.reg .pred p;\nsetp.ne.b32 p, %130, 0;\n"
        "wgmma.mma_async.sync.aligned.m64n256k16.f32.bf16.bf16 "
        "{%0, %1, %2, %3, %4, %5, %6, %7, %8, %9, %10, %11, %12, %13, %14, %15, %16, %17, %18, %19, %20, %21, %22, %23, %24, %25, %26, %27, %28, %29, %30, %31, %32, %33, %34, %35, %36, %37, %38, %39, %40, %41, %42, %43, %44, %45, %46, %47, %48, %49, %50, %51, %52, %53, %54, %55, %56, %57, %58, %59, %60, %61, %62, %63, %64, %65, %66, %67, %68, %69, %70, %71, %72, %73, %74, %75, %76, %77, %78, %79, %80, %81, %82, %83, %84, %85, %86, %87, %88, %89, %90, %91, %92, %93, %94, %95, %96, %97, %98, %99, %100, %101, %102, %103, %104, %105, %106, %107, %108, %109, %110, %111, %112, %113, %114, %115, %116, %117, %118, %119, %120, %121, %122, %123, %124, %125, %126, %127}, "
        "%128, %129, p, 1, 1, 0, 1;\n}\n"
        : "+f"(d[0]), "+f"(d[1]), "+f"(d[2]), "+f"(d[3]), "+f"(d[4]), "+f"(d[5]), "+f"(d[6]), "+f"(d[7]), "+f"(d[8]), "+f"(d[9]), "+f"(d[10]), "+f"(d[11]), "+f"(d[12]), "+f"(d[13]), "+f"(d[14]), "+f"(d[15]), "+f"(d[16]), "+f"(d[17]), "+f"(d[18]), "+f"(d[19]), "+f"(d[20]), "+f"(d[21]), "+f"(d[22]), "+f"(d[23]), "+f"(d[24]), "+f"(d[25]), "+f"(d[26]), "+f"(d[27]), "+f"(d[28]), "+f"(d[29]), "+f"(d[30]), "+f"(d[31]), "+f"(d[32]), "+f"(d[33]), "+f"(d[34]), "+f"(d[35]), "+f"(d[36]), "+f"(d[37]), "+f"(d[38]), "+f"(d[39]), "+f"(d[40]), "+f"(d[41]), "+f"(d[42]), "+f"(d[43]), "+f"(d[44]), "+f"(d[45]), "+f"(d[46]), "+f"(d[47]), "+f"(d[48]), "+f"(d[49]), "+f"(d[50]), "+f"(d[51]), "+f"(d[52]), "+f"(d[53]), "+f"(d[54]), "+f"(d[55]), "+f"(d[56]), "+f"(d[57]), "+f"(d[58]), "+f"(d[59]), "+f"(d[60]), "+f"(d[61]), "+f"(d[62]), "+f"(d[63]), "+f"(d[64]), "+f"(d[65]), "+f"(d[66]), "+f"(d[67]), "+f"(d[68]), "+f"(d[69]), "+f"(d[70]), "+f"(d[71]), "+f"(d[72]), "+f"(d[73]), "+f"(d[74]), "+f"(d[75]), "+f"(d[76]), "+f"(d[77]), "+f"(d[78]), "+f"(d[79]), "+f"(d[80]), "+f"(d[81]), "+f"(d[82]), "+f"(d[83]), "+f"(d[84]), "+f"(d[85]), "+f"(d[86]), "+f"(d[87]), "+f"(d[88]), "+f"(d[89]), "+f"(d[90]), "+f"(d[91]), "+f"(d[92]), "+f"(d[93]), "+f"(d[94]), "+f"(d[95]), "+f"(d[96]), "+f"(d[97]), "+f"(d[98]), "+f"(d[99]), "+f"(d[100]), "+f"(d[101]), "+f"(d[102]), "+f"(d[103]), "+f"(d[104]), "+f"(d[105]), "+f"(d[106]), "+f"(d[107]), "+f"(d[108]), "+f"(d[109]), "+f"(d[110]), "+f"(d[111]), "+f"(d[112]), "+f"(d[113]), "+f"(d[114]), "+f"(d[115]), "+f"(d[116]), "+f"(d[117]), "+f"(d[118]), "+f"(d[119]), "+f"(d[120]), "+f"(d[121]), "+f"(d[122]), "+f"(d[123]), "+f"(d[124]), "+f"(d[125]), "+f"(d[126]), "+f"(d[127])
        : "l"(da), "l"(db), "r"(sd));
}
__device__ __forceinline__ void wgmma_rs_n128(float (&d)[64], uint32_t a0, uint32_t a1, uint32_t a2, uint32_t a3, uint64_t db, int sd) {
    asm volatile("{\n.reg .pred p;\nsetp.ne.b32 p, %69, 0;\n"
        "wgmma.mma_async.sync.aligned.m64n128k16.f32.bf16.bf16 "
        "{%0, %1, %2, %3, %4, %5, %6, %7, %8, %9, %10, %11, %12, %13, %14, %15, %16, %17, %18, %19, %20, %21, %22, %23, %24, %25, %26, %27, %28, %29, %30, %31, %32, %33, %34, %35, %36, %37, %38, %39, %40, %41, %42, %43, %44, %45, %46, %47, %48, %49, %50, %51, %52, %53, %54, %55, %56, %57, %58, %59, %60, %61, %62, %63}, "
        "{%64, %65, %66, %67}, %68, p, 1, 1, 0;\n}\n"
        : "+f"(d[0]), "+f"(d[1]), "+f"(d[2]), "+f"(d[3]), "+f"(d[4]), "+f"(d[5]), "+f"(d[6]), "+f"(d[7]), "+f"(d[8]), "+f"(d[9]), "+f"(d[10]), "+f"(d[11]), "+f"(d[12]), "+f"(d[13]), "+f"(d[14]), "+f"(d[15]), "+f"(d[16]), "+f"(d[17]), "+f"(d[18]), "+f"(d[19]), "+f"(d[20]), "+f"(d[21]), "+f"(d[22]), "+f"(d[23]), "+f"(d[24]), "+f"(d[25]), "+f"(d[26]), "+f"(d[27]), "+f"(d[28]), "+f"(d[29]), "+f"(d[30]), "+f"(d[31]), "+f"(d[32]), "+f"(d[33]), "+f"(d[34]), "+f"(d[35]), "+f"(d[36]), "+f"(d[37]), "+f"(d[38]), "+f"(d[39]), "+f"(d[40]), "+f"(d[41]), "+f"(d[42]), "+f"(d[43]), "+f"(d[44]), "+f"(d[45]), "+f"(d[46]), "+f"(d[47]), "+f"(d[48]), "+f"(d[49]), "+f"(d[50]), "+f"(d[51]), "+f"(d[52]), "+f"(d[53]), "+f"(d[54]), "+f"(d[55]), "+f"(d[56]), "+f"(d[57]), "+f"(d[58]), "+f"(d[59]), "+f"(d[60]), "+f"(d[61]), "+f"(d[62]), "+f"(d[63])
        : "r"(a0), "r"(a1), "r"(a2), "r"(a3), "l"(db), "r"(sd));
}
__device__ __forceinline__ void wgmma_rs_n128_tb(float (&d)[64], uint32_t a0, uint32_t a1, uint32_t a2, uint32_t a3, uint64_t db, int sd) {
    asm volatile("{\n.reg .pred p;\nsetp.ne.b32 p, %69, 0;\n"
        "wgmma.mma_async.sync.aligned.m64n128k16.f32.bf16.bf16 "
        "{%0, %1, %2, %3, %4, %5, %6, %7, %8, %9, %10, %11, %12, %13, %14, %15, %16, %17, %18, %19, %20, %21, %22, %23, %24, %25, %26, %27, %28, %29, %30, %31, %32, %33, %34, %35, %36, %37, %38, %39, %40, %41, %42, %43, %44, %45, %46, %47, %48, %49, %50, %51, %52, %53, %54, %55, %56, %57, %58, %59, %60, %61, %62, %63}, "
        "{%64, %65, %66, %67}, %68, p, 1, 1, 1;\n}\n"
        : "+f"(d[0]), "+f"(d[1]), "+f"(d[2]), "+f"(d[3]), "+f"(d[4]), "+f"(d[5]), "+f"(d[6]), "+f"(d[7]), "+f"(d[8]), "+f"(d[9]), "+f"(d[10]), "+f"(d[11]), "+f"(d[12]), "+f"(d[13]), "+f"(d[14]), "+f"(d[15]), "+f"(d[16]), "+f"(d[17]), "+f"(d[18]), "+f"(d[19]), "+f"(d[20]), "+f"(d[21]), "+f"(d[22]), "+f"(d[23]), "+f"(d[24]), "+f"(d[25]), "+f"(d[26]), "+f"(d[27]), "+f"(d[28]), "+f"(d[29]), "+f"(d[30]), "+f"(d[31]), "+f"(d[32]), "+f"(d[33]), "+f"(d[34]), "+f"(d[35]), "+f"(d[36]), "+f"(d[37]), "+f"(d[38]), "+f"(d[39]), "+f"(d[40]), "+f"(d[41]), "+f"(d[42]), "+f"(d[43]), "+f"(d[44]), "+f"(d[45]), "+f"(d[46]), "+f"(d[47]), "+f"(d[48]), "+f"(d[49]), "+f"(d[50]), "+f"(d[51]), "+f"(d[52]), "+f"(d[53]), "+f"(d[54]), "+f"(d[55]), "+f"(d[56]), "+f"(d[57]), "+f"(d[58]), "+f"(d[59]), "+f"(d[60]), "+f"(d[61]), "+f"(d[62]), "+f"(d[63])
        : "r"(a0), "r"(a1), "r"(a2), "r"(a3), "l"(db), "r"(sd));
}
__device__ __forceinline__ void wgmma_rs_n64_tb(float (&d)[32], uint32_t a0, uint32_t a1, uint32_t a2, uint32_t a3, uint64_t db, int sd) {
    asm volatile("{\n.reg .pred p;\nsetp.ne.b32 p, %37, 0;\n"
        "wgmma.mma_async.sync.aligned.m64n64k16.f32.bf16.bf16 "
        "{%0, %1, %2, %3, %4, %5, %6, %7, %8, %9, %10, %11, %12, %13, %14, %15, %16, %17, %18, %19, %20, %21, %22, %23, %24, %25, %26, %27, %28, %29, %30, %31}, "
        "{%32, %33, %34, %35}, %36, p, 1, 1, 1;\n}\n"
        : "+f"(d[0]), "+f"(d[1]), "+f"(d[2]), "+f"(d[3]), "+f"(d[4]), "+f"(d[5]), "+f"(d[6]), "+f"(d[7]), "+f"(d[8]), "+f"(d[9]), "+f"(d[10]), "+f"(d[11]), "+f"(d[12]), "+f"(d[13]), "+f"(d[14]), "+f"(d[15]), "+f"(d[16]), "+f"(d[17]), "+f"(d[18]), "+f"(d[19]), "+f"(d[20]), "+f"(d[21]), "+f"(d[22]), "+f"(d[23]), "+f"(d[24]), "+f"(d[25]), "+f"(d[26]), "+f"(d[27]), "+f"(d[28]), "+f"(d[29]), "+f"(d[30]), "+f"(d[31])
        : "r"(a0), "r"(a1), "r"(a2), "r"(a3), "l"(db), "r"(sd));
}

__global__ void __launch_bounds__(384, 1) fused_gqa_kernel(const __grid_constant__ Params P) {
    extern __shared__ uint8_t smem_raw[];
    const uint32_t base = (smem_u32(smem_raw) + 1023u) & ~1023u;
    const uint32_t smR = base;
    const uint32_t smS = base + R_BYTES;
    const uint32_t bars = smS + NSTAGE * STAGE_BYTES;
    const uint32_t prog = bars + 8 * (2 * NSTAGE + 10);
    const int tid = threadIdx.x;
    const int wid = __shfl_sync(0xffffffffu, tid >> 5, 0);
    const int lane = tid & 31;

    const int cta = blockIdx.x;
    const int blk = cta >> 6;
    const int hp = (cta >> 3) & 7;
    const int b = cta & 7;
    const int grp = blk * 8 + b;

    if (tid == 0) {
        TS(0);
        for (int i = 0; i < NSTAGE; i++) {
            mbar_init(bars + 8 * i, 1);
            mbar_init(bars + 8 * (NSTAGE + i), 8);
        }
        for (int i = 0; i < 10; i++) mbar_init(bars + 8 * (2 * NSTAGE + i), 4);
        asm volatile("st.volatile.shared.u32 [%0], %1;" ::"r"(prog), "r"(0) : "memory");
        asm volatile("fence.mbarrier_init.release.cluster;" ::: "memory");
        asm volatile("fence.proxy.async.shared::cta;" ::: "memory");
    }
    __syncthreads();

    if (wid >= 8) {
        asm volatile("setmaxnreg.dec.sync.aligned.u32 40;");
        if (wid == 8) {
            if (lane == 0) {
                int slot = 0, ph = 1;
                for (int s = 0; s < N_WQ; s++) {
                    const uint32_t fb = bars + 8 * slot;
                    mbar_wait(bars + 8 * (NSTAGE + slot), ph);
                    const uint32_t dst = smS + slot * STAGE_BYTES;
                    mbar_expect_tx(fb, (s & 1) ? STAGE_BYTES : STAGE_BYTES + 8192);
                    if (!(s & 1)) tma_2d(smR + ((s >> 1) & 7) * 8192, &P.x[blk], (s >> 1) * 64, b * 64, fb);
#pragma unroll
                    for (int p = 0; p < 8; p++) {
                        const int w = p >> 2, j = (p >> 1) & 1, glo = p & 1;
                        tma_2d(dst + p * 4096, &P.wq[blk], hp * 512 + (j * 4 + w * 2 + glo) * 64, s * 32, fb);
                    }
                    if (++slot == NSTAGE) { slot = 0; ph ^= 1; }
                }
                for (int i = 0; i < 34; i++) {
                    const int u = (i >= 17), r = i - 17 * u;
                    const uint32_t fb = bars + 8 * slot;
                    mbar_wait(bars + 8 * (NSTAGE + slot), ph);
                    const uint32_t dst = smS + slot * STAGE_BYTES;
                    mbar_expect_tx(fb, STAGE_BYTES);
                    if (r < 8) {
                        const int row = (b * kHkv + hp * 2 + u) * kSk + (r >> 1) * 128;
                        const CUtensorMap* tm = (r & 1) ? &P.v[blk] : &P.k[blk];
                        tma_2d(dst, tm, 0, row, fb);
                        tma_2d(dst + 16384, tm, 64, row, fb);
                    } else {
                        const int q = r - 8, kh = q & 1, row = hp * 512 + u * 256;
                        const int c0 = (q >> 1) * 128;
                        tma_2d(dst, &P.wo[blk], c0, row + kh * 128, fb);
                        tma_2d(dst + 16384, &P.wo[blk], (q < 8) ? c0 + 64 : c0, row + (kh ^ 1) * 128, fb);
                    }
                    asm volatile("st.volatile.shared.u32 [%0], %1;" ::"r"(prog), "r"(i + 1) : "memory");
                    if (++slot == NSTAGE) { slot = 0; ph ^= 1; }
                }
            }
        } else if (wid == 11) {
            if (PF_DIST > 0) {
                uint32_t sink = 0;
                if (PF_WQ) {
                    const char* wqs = (const char*)(P.wqp[blk] + hp * 512) + (size_t)(160 + b * 52) * 8192;
#pragma unroll
                    for (int h = 0; h < 2; h++) {
#pragma unroll
                        for (int j = 0; j < 4; j++) {
                            const int e = (h * 4 + j) * 32 + lane;
                            if (e < 208) sink |= l2_touch(wqs + (size_t)(e >> 2) * 8192 + (e & 3) * 256);
                        }
                        if (sink == 0x9E3779B9u) asm volatile("st.volatile.shared.u32 [%0], %1;" ::"r"(prog + 4), "r"(sink) : "memory");
                    }
                }
                const char* kbase = (const char*)(P.kp[blk] + (size_t)(b * kHkv + hp * 2) * kSk * kDh);
                const char* vbase = (const char*)(P.vp[blk] + (size_t)(b * kHkv + hp * 2) * kSk * kDh);
                const char* wos = (const char*)(P.wop[blk] + (size_t)hp * 512 * kD) + (size_t)b * 36864;
                for (int i = 0; i < 18; i++) {
                    const int u = (i >= 9), r = i - 9 * u;
                    const int pos = u * 17 + r;
                    if (pos >= PF_DIST) {
                        uint32_t pr, n = 0;
                        while (true) {
                            asm volatile("ld.volatile.shared.u32 %0, [%1];" : "=r"(pr) : "r"(prog) : "memory");
                            if ((int)pr + PF_DIST >= pos) break;
                            if (++n > (1u << 22)) break;
                            __nanosleep(100);
                        }
                    }
                    if (r < 8) {
                        const char* p = ((r & 1) ? vbase : kbase) + (size_t)(u * 4 + (r >> 1)) * 32768 + lane * 256;
#pragma unroll
                        for (int j = 0; j < 4; j++) sink |= l2_touch(p + j * 8192);
                    } else {
                        const char* p = wos + (size_t)u * 294912 + lane * 256;
#pragma unroll
                        for (int j = 0; j < 5; j++) if (j * 32 + lane < 144) sink |= l2_touch(p + j * 8192);
                    }
                    if (sink == 0x9E3779B9u) asm volatile("st.volatile.shared.u32 [%0], %1;" ::"r"(prog + 4), "r"(sink) : "memory");
                }
            }
        } else {
            const int hw = wid - 9;
            for (int k = 0; k < 5; k++) {
                mbar_wait(bars + 8 * (2 * NSTAGE + hw * 5 + k), 0);
                const int c = (k < 4) ? (2 * k + hw) : 8;
                asm volatile("fence.acq_rel.gpu;" ::: "memory");
                asm volatile("red.relaxed.gpu.global.add.u32 [%0], 1;" ::"l"(&g_cnt[(grp * 9 + c) * 32 + lane]) : "memory");
            }
        }
    } else {
        asm volatile("setmaxnreg.inc.sync.aligned.u32 232;");
        const int w = wid >> 2;
        const int t = tid & 127;
        int slot = 0, ph = 0;
        uint32_t qf[8][4];
        const uint32_t stash = smR + (1 + w) * 16384 + t * 16;
        {
            float acc[128];
            int pslot = 0;
            for (int s = 0; s < N_WQ; s++) {
                mbar_wait(bars + 8 * slot, ph);
                if (tid == 0 && s == 0) TS(20);
                if (tid == 0 && s == 5) TS(21);
                if (tid == 0 && s == 10) TS(22);
                const uint64_t da = mk_desc(smR + ((s >> 1) & 7) * 8192 + (s & 1) * 64, 16, 1024);
                const uint64_t db = mk_desc(smS + slot * STAGE_BYTES + w * 16384, 4096, 1024);
                wg_fence();
                wgmma_ss_n256_tb(acc, da, db, s != 0);
                wgmma_ss_n256_tb(acc, da + 2, db + 128, 1);
                wg_commit();
                if (s > 0) {
                    wg_wait<1>();
                    if (lane == 0) mbar_arrive(bars + 8 * (NSTAGE + pslot));
                }
                pslot = slot;
                if (++slot == NSTAGE) { slot = 0; ph ^= 1; }
            }
            wg_wait<0>();
            if (lane == 0) mbar_arrive(bars + 8 * (NSTAGE + pslot));
            fence_regs(acc);
            if (tid == 0) TS(1);
#pragma unroll
            for (int kk = 0; kk < 8; kk++) {
#pragma unroll
                for (int i = 0; i < 4; i++) qf[kk][i] = pack_bf16(acc[8 * kk + 2 * i], acc[8 * kk + 2 * i + 1]);
                sts128(stash + kk * 2048,
                       pack_bf16(acc[64 + 8 * kk + 0], acc[64 + 8 * kk + 1]), pack_bf16(acc[64 + 8 * kk + 2], acc[64 + 8 * kk + 3]),
                       pack_bf16(acc[64 + 8 * kk + 4], acc[64 + 8 * kk + 5]), pack_bf16(acc[64 + 8 * kk + 6], acc[64 + 8 * kk + 7]));
            }
        }
        if (w == 1) bar_arrive<5, 256>();
        const float sc = 0.08838834764831845f * 1.4426950408889634f;
        float4* own = g_own + (size_t)(cta * 2 + w) * 5 * 1024 + t;
#pragma unroll
        for (int u = 0; u < 2; u++) {
            uint32_t af[16][4];
            {
                if (u == 1) {
#pragma unroll
                    for (int kk = 0; kk < 8; kk++) lds128(stash + kk * 2048, qf[kk]);
                }
                float o[64], s[64];
                float m0 = -INFINITY, m1 = -INFINITY, l0 = 0.f, l1 = 0.f;
                uint32_t pf[8][4];
#pragma unroll
                for (int i = 0; i < 64; i++) { o[i] = 0.f; s[i] = 0.f; }
#pragma unroll
                for (int i = 0; i < 32; i++) pf[i >> 2][i & 3] = 0u;
#pragma unroll 1
                for (int tt = 0; tt <= 4; tt++) {
                    int vslot = slot;
                    if (tt > 0) {
                        mbar_wait(bars + 8 * slot, ph);
                        if (++slot == NSTAGE) { slot = 0; ph ^= 1; }
                    }
                    if (tt < 4) mbar_wait(bars + 8 * slot, ph);
                    if (tid == 0) TS(32 + u * 20 + tt * 4);
                    if (w == 0) bar_sync<5, 256>(); else bar_sync<6, 256>();
                    wg_fence();
                    if (tt > 0) {
                        const uint64_t db = mk_desc(smS + vslot * STAGE_BYTES, 16384, 1024);
#pragma unroll
                        for (int kk = 0; kk < 8; kk++)
                            wgmma_rs_n128_tb(o, pf[kk][0], pf[kk][1], pf[kk][2], pf[kk][3], db + kk * 128, (tt > 1) || (kk != 0));
                        wg_commit();
                    }
                    if (tt < 4) {
                        const uint64_t db = mk_desc(smS + slot * STAGE_BYTES, 16, 1024);
#pragma unroll
                        for (int kk = 0; kk < 8; kk++)
                            wgmma_rs_n128(s, qf[kk][0], qf[kk][1], qf[kk][2], qf[kk][3], db + (kk >> 2) * 1024 + (kk & 3) * 2, kk != 0);
                        wg_commit();
                    }
                    if (w == 0) bar_arrive<6, 256>(); else if (!(u == 1 && tt == 4)) bar_arrive<5, 256>();
                    if (tid == 0) TS(32 + u * 20 + tt * 4 + 1);
                    wg_wait<0>();
                    fence_regs(o);
                    fence_regs(s);
                    if (tid == 0) TS(32 + u * 20 + tt * 4 + 2);
                    if (tt > 0 && lane == 0) mbar_arrive(bars + 8 * (NSTAGE + vslot));
                    if (tt == 4) break;
                    if (lane == 0) mbar_arrive(bars + 8 * (NSTAGE + slot));
                    if (++slot == NSTAGE) { slot = 0; ph ^= 1; }
                    float mx0 = s[0], mx1 = s[2];
#pragma unroll
                    for (int j = 0; j < 16; j++) {
                        mx0 = fmaxf(mx0, fmaxf(s[4 * j], s[4 * j + 1]));
                        mx1 = fmaxf(mx1, fmaxf(s[4 * j + 2], s[4 * j + 3]));
                    }
                    mx0 = fmaxf(mx0, __shfl_xor_sync(0xffffffffu, mx0, 1));
                    mx1 = fmaxf(mx1, __shfl_xor_sync(0xffffffffu, mx1, 1));
                    mx0 = fmaxf(mx0, __shfl_xor_sync(0xffffffffu, mx0, 2));
                    mx1 = fmaxf(mx1, __shfl_xor_sync(0xffffffffu, mx1, 2));
                    const float mn0 = fmaxf(m0, mx0), mn1 = fmaxf(m1, mx1);
                    const float al0 = ex2((m0 - mn0) * sc), al1 = ex2((m1 - mn1) * sc);
                    m0 = mn0; m1 = mn1;
                    const float ms0 = mn0 * sc, ms1 = mn1 * sc;
                    float rs0 = 0.f, rs1 = 0.f;
#pragma unroll
                    for (int j = 0; j < 16; j++) {
                        const float p0 = ex2(fmaf(s[4 * j], sc, -ms0)), p1 = ex2(fmaf(s[4 * j + 1], sc, -ms0));
                        const float p2 = ex2(fmaf(s[4 * j + 2], sc, -ms1)), p3 = ex2(fmaf(s[4 * j + 3], sc, -ms1));
                        rs0 += p0 + p1; rs1 += p2 + p3;
                        pf[j >> 1][(j & 1) * 2] = pack_bf16(p0, p1);
                        pf[j >> 1][(j & 1) * 2 + 1] = pack_bf16(p2, p3);
                    }
                    l0 = l0 * al0 + rs0; l1 = l1 * al1 + rs1;
                    if (tt > 0) {
#pragma unroll
                        for (int j = 0; j < 16; j++) { o[4 * j] *= al0; o[4 * j + 1] *= al0; o[4 * j + 2] *= al1; o[4 * j + 3] *= al1; }
                    }
                    if (tid == 0) TS(32 + u * 20 + tt * 4 + 3);
                }
                if (tid == 0) TS(2 + u);
                l0 += __shfl_xor_sync(0xffffffffu, l0, 1);
                l1 += __shfl_xor_sync(0xffffffffu, l1, 1);
                l0 += __shfl_xor_sync(0xffffffffu, l0, 2);
                l1 += __shfl_xor_sync(0xffffffffu, l1, 2);
                const float i0 = 1.f / l0, i1 = 1.f / l1;
                const uint32_t zown = smR + ((u == 0) ? (w ? 3 : 0) : (w ? 2 : 1)) * 16384 + t * 16;
#pragma unroll
                for (int kk = 0; kk < 8; kk++) {
                    af[kk][0] = pack_bf16(o[8 * kk + 0] * i0, o[8 * kk + 1] * i0);
                    af[kk][1] = pack_bf16(o[8 * kk + 2] * i1, o[8 * kk + 3] * i1);
                    af[kk][2] = pack_bf16(o[8 * kk + 4] * i0, o[8 * kk + 5] * i0);
                    af[kk][3] = pack_bf16(o[8 * kk + 6] * i1, o[8 * kk + 7] * i1);
                    sts128(zown + kk * 2048, af[kk][0], af[kk][1], af[kk][2], af[kk][3]);
                }
            }
            {
                float acc[2][32];
                float4 pre[2][8];
#pragma unroll
                for (int i = 0; i < 32; i++) { acc[0][i] = 0.f; acc[1][i] = 0.f; }
                if (u == 1) {
#pragma unroll
                    for (int k = 0; k < 2; k++)
#pragma unroll
                        for (int j = 0; j < 8; j++) pre[k][j] = __ldcg(own + (k * 8 + j) * 128);
                }
                bar_sync<4, 256>();
                const uint32_t zoth = smR + ((u == 0) ? (w ? 0 : 3) : (w ? 1 : 2)) * 16384 + t * 16;
#pragma unroll
                for (int kk = 0; kk < 8; kk++) lds128(zoth + kk * 2048, af[8 + kk]);
                int pslot = 0;
                float4* dst0 = g_part + (size_t)(grp * 80 + w * 8 + hp) * 1024 + t;
                float4* dst8 = g_part + (size_t)(grp * 80 + 64 + hp * 2 + w) * 1024 + t;
#pragma unroll
                for (int st = 0; st <= 9; st++) {
                    if (st < 9) {
                        const int kh = st & 1, ab = (st >> 1) & 1;
                        mbar_wait(bars + 8 * slot, ph);
                        const uint64_t db = mk_desc(smS + slot * STAGE_BYTES + w * 16384, 16384, 1024);
                        wg_fence();
#pragma unroll
                        for (int kk = 0; kk < 8; kk++)
                            wgmma_rs_n64_tb(acc[ab], af[kh * 8 + kk][0], af[kh * 8 + kk][1], af[kh * 8 + kk][2], af[kh * 8 + kk][3], db + kk * 128, (kh | kk) != 0);
                        wg_commit();
                    }
                    if (st > 0) {
                        if (st < 9) wg_wait<1>(); else wg_wait<0>();
                        if (lane == 0) mbar_arrive(bars + 8 * (NSTAGE + pslot));
                        if ((st & 1) == 0 || st == 9) {
                            const int k = (st - 1) >> 1, ab = k & 1;
                            fence_regs(acc[ab]);
                            if (u == 0) {
#pragma unroll
                                for (int j = 0; j < 8; j++) __stcg(own + (k * 8 + j) * 128, make_float4(acc[ab][4 * j], acc[ab][4 * j + 1], acc[ab][4 * j + 2], acc[ab][4 * j + 3]));
                            } else {
                                float4* dst = (k < 4) ? (dst0 + (size_t)k * 16 * 1024) : dst8;
#pragma unroll
                                for (int j = 0; j < 8; j++)
                                    __stcg(dst + j * 128, make_float4(acc[ab][4 * j] + pre[ab][j].x, acc[ab][4 * j + 1] + pre[ab][j].y,
                                                                      acc[ab][4 * j + 2] + pre[ab][j].z, acc[ab][4 * j + 3] + pre[ab][j].w));
                                __syncwarp();
                                if (lane == 0) mbar_arrive(bars + 8 * (2 * NSTAGE + w * 5 + k));
                                if (k + 2 < 5) {
#pragma unroll
                                    for (int j = 0; j < 8; j++) pre[ab][j] = __ldcg(own + ((k + 2) * 8 + j) * 128);
                                }
                            }
                            if (tid == 0) TS(4 + u * 8 + k);
                        }
                    }
                    if (st < 9) {
                        pslot = slot;
                        if (++slot == NSTAGE) { slot = 0; ph ^= 1; }
                    }
                }
            }
        }
        {
            const int nch = (w == 0) ? 5 : 4;
            if (lane < nch) {
                const int c = (lane < 4) ? (2 * lane + w) : 8;
                const unsigned need = (lane < 4) ? 8u : 16u;
                unsigned* cp = &g_cnt[(grp * 9 + c) * 32 + hp * 4 + (wid & 3)];
                unsigned v, n = 0;
                while (true) {
                    asm volatile("ld.acquire.gpu.global.u32 %0, [%1];" : "=r"(v) : "l"(cp) : "memory");
                    if (v >= need) break;
                    if (++n > (1u << 21)) break;
                }
                *cp = 0;
            }
            __syncwarp();
            if (tid == 0) TS(18);
            __nv_bfloat16* orow = P.out + (size_t)(b * 64 + (t >> 5) * 16 + (lane >> 2)) * (2 * kD) + blk * kD + hp * 8 + (lane & 3) * 2;
            const float4* src = g_part + ((size_t)(grp * 80 + w * 8) * 8 + hp) * 128 + t;
            float4 v[4][8];
#pragma unroll
            for (int k = 0; k < 4; k++)
#pragma unroll
                for (int i = 0; i < 8; i++) v[k][i] = __ldcg(src + (size_t)(k * 16 + i) * 1024);
            if (w == 0) {
                const float4* src8 = g_part + ((size_t)(grp * 80 + 64) * 8 + hp) * 128 + t;
                float4 u[16];
#pragma unroll
                for (int i = 0; i < 16; i++) u[i] = __ldcg(src8 + (size_t)i * 1024);
                float4 a = u[0];
#pragma unroll
                for (int i = 1; i < 16; i++) { a.x += u[i].x; a.y += u[i].y; a.z += u[i].z; a.w += u[i].w; }
                *(uint32_t*)(orow + 512) = pack_bf16(a.x, a.y);
                *(uint32_t*)(orow + 512 + 8 * 2 * kD) = pack_bf16(a.z, a.w);
            }
#pragma unroll
            for (int k = 0; k < 4; k++) {
                float4 a = v[k][0];
#pragma unroll
                for (int i = 1; i < 8; i++) { a.x += v[k][i].x; a.y += v[k][i].y; a.z += v[k][i].z; a.w += v[k][i].w; }
                *(uint32_t*)(orow + (2 * k + w) * 64) = pack_bf16(a.x, a.y);
                *(uint32_t*)(orow + (2 * k + w) * 64 + 8 * 2 * kD) = pack_bf16(a.z, a.w);
            }
            if (tid == 0) TS(19);
        }
    }
}

typedef CUresult (*EncodeFn)(CUtensorMap*, CUtensorMapDataType, cuuint32_t, void*, const cuuint64_t*, const cuuint64_t*,
                             const cuuint32_t*, const cuuint32_t*, CUtensorMapInterleave, CUtensorMapSwizzle,
                             CUtensorMapL2promotion, CUtensorMapFloatOOBfill);

void make_map(EncodeFn fn, CUtensorMap* m, const void* ptr, uint64_t cols, uint64_t rows, uint32_t box_rows) {
    cuuint64_t dims[2] = {cols, rows};
    cuuint64_t strides[1] = {cols * 2};
    cuuint32_t box[2] = {64, box_rows};
    cuuint32_t es[2] = {1, 1};
    fn(m, CU_TENSOR_MAP_DATA_TYPE_BFLOAT16, 2, const_cast<void*>(ptr), dims, strides, box, es, CU_TENSOR_MAP_INTERLEAVE_NONE,
       CU_TENSOR_MAP_SWIZZLE_128B, CU_TENSOR_MAP_L2_PROMOTION_L2_256B, CU_TENSOR_MAP_FLOAT_OOB_FILL_NONE);
}

}

extern "C" void kernel_launch(void* const* d_in, const int* in_sizes, int n_in, void* d_out, int out_size) {
    static EncodeFn enc = nullptr;
    if (!enc) {
        void* fn = nullptr;
        cudaDriverEntryPointQueryResult st;
        cudaGetDriverEntryPoint("cuTensorMapEncodeTiled", &fn, cudaEnableDefault, &st);
        enc = (EncodeFn)fn;
        cudaFuncSetAttribute(fused_gqa_kernel, cudaFuncAttributeMaxDynamicSharedMemorySize, SMEM_BYTES);
    }
    Params P;
    for (int blk = 0; blk < 2; blk++) {
        const void* x = d_in[blk * 5 + 0];
        const void* k = d_in[blk * 5 + 1];
        const void* v = d_in[blk * 5 + 2];
        const void* wq = d_in[blk * 5 + 3];
        const void* wo = d_in[blk * 5 + 4];
        make_map(enc, &P.x[blk], x, kD, kB * kSq, 64);
        make_map(enc, &P.wq[blk], wq, kHq * kDh, kD, 32);
        make_map(enc, &P.k[blk], k, kDh, (uint64_t)kB * kHkv * kSk, 128);
        make_map(enc, &P.v[blk], v, kDh, (uint64_t)kB * kHkv * kSk, 128);
        make_map(enc, &P.wo[blk], wo, kD, kHq * kDh, 128);
        P.wqp[blk] = (const __nv_bfloat16*)wq;
        P.kp[blk] = (const __nv_bfloat16*)k;
        P.vp[blk] = (const __nv_bfloat16*)v;
        P.wop[blk] = (const __nv_bfloat16*)wo;
    }
    P.out = (__nv_bfloat16*)d_out;
    fused_gqa_kernel<<<128, 384, SMEM_BYTES>>>(P);
}
```

```cpp
#include <cuda_runtime.h>
#include <cuda_bf16.h>
#include <cuda.h>
#include <stdint.h>

namespace {

constexpr int kB = 8, kSq = 64, kD = 576, kHq = 32, kHkv = 16, kSk = 512, kDh = 128;
constexpr int NSTAGE = 5;
constexpr int STAGE_BYTES = 32768;
constexpr int R_BYTES = 65536;
constexpr int SMEM_BYTES = R_BYTES + NSTAGE * STAGE_BYTES + 1024   + 256  ;
constexpr int N_WQ = 18;
#define PF_DIST_V 4
#define PF_WQ 0
#define PF_SLEEP 1000
constexpr int PF_DIST = PF_DIST_V;

struct __align__(64) Params {
    CUtensorMap x[2], wq[2], k[2], v[2], wo[2];
    const __nv_bfloat16* wqp[2];
    const __nv_bfloat16* kp[2];
    const __nv_bfloat16* vp[2];
    const __nv_bfloat16* wop[2];
    __nv_bfloat16* out;
};

__device__ uint2 g_part[16 * 80 * 8 * 128];
__device__ unsigned int g_cnt[16 * 9 * 32];
#define TS(k) do {} while (0)

__device__ __forceinline__ uint32_t smem_u32(const void* p) { return (uint32_t)__cvta_generic_to_shared(p); }
__device__ __forceinline__ void mbar_init(uint32_t bar, int cnt) {
    asm volatile("mbarrier.init.shared::cta.b64 [%0], %1;" ::"r"(bar), "r"(cnt));
}
__device__ __forceinline__ void mbar_expect_tx(uint32_t bar, uint32_t bytes) {
    asm volatile("mbarrier.arrive.expect_tx.shared::cta.b64 _, [%0], %1;" ::"r"(bar), "r"(bytes) : "memory");
}
__device__ __forceinline__ void mbar_arrive(uint32_t bar) {
    asm volatile("mbarrier.arrive.shared::cta.b64 _, [%0];" ::"r"(bar) : "memory");
}
__device__ __forceinline__ bool mbar_try(uint32_t bar, uint32_t parity) {
    uint32_t ok;
    asm volatile("{\n.reg .pred p;\nmbarrier.try_wait.parity.shared::cta.b64 p, [%1], %2;\nselp.u32 %0, 1, 0, p;\n}\n"
                 : "=r"(ok) : "r"(bar), "r"(parity) : "memory");
    return ok != 0;
}
__device__ __forceinline__ void mbar_wait(uint32_t bar, uint32_t parity) {
    if (mbar_try(bar, parity)) return;
    uint32_t n = 0;
    while (!mbar_try(bar, parity)) {
        if (++n > (1u << 20)) break;
    }
}
__device__ __forceinline__ void tma_2d(uint32_t dst, const CUtensorMap* tm, int c0, int c1, uint32_t bar) {
    asm volatile("cp.async.bulk.tensor.2d.shared::cluster.global.mbarrier::complete_tx::bytes [%0], [%1, {%3, %4}], [%2];"
                 ::"r"(dst), "l"(tm), "r"(bar), "r"(c0), "r"(c1) : "memory");
}
__device__ __forceinline__ void l2_prefetch(const void* p, uint32_t bytes) {
    asm volatile("cp.async.bulk.prefetch.L2.global [%0], %1;" ::"l"(p), "r"(bytes) : "memory");
}
__device__ __forceinline__ uint32_t l2_touch(const void* p) {
    uint32_t v;
    asm volatile("ld.global.L2::256B.b32 %0, [%1];" : "=r"(v) : "l"(p) : "memory");
    return v;
}
__device__ __forceinline__ void wg_fence() { asm volatile("wgmma.fence.sync.aligned;" ::: "memory"); }
__device__ __forceinline__ void wg_commit() { asm volatile("wgmma.commit_group.sync.aligned;" ::: "memory"); }
template <int N> __device__ __forceinline__ void wg_wait() { asm volatile("wgmma.wait_group.sync.aligned %0;" ::"n"(N) : "memory"); }
template <int N> __device__ __forceinline__ void fence_regs(float (&d)[N]) {
#pragma unroll
    for (int i = 0; i < N; i++) asm volatile("" : "+f"(d[i])::"memory");
}
__device__ __forceinline__ uint64_t mk_desc(uint32_t addr, uint32_t lbo, uint32_t sbo) {
    return (uint64_t)((addr & 0x3FFFF) >> 4) | ((uint64_t)(lbo >> 4) << 16) | ((uint64_t)(sbo >> 4) << 32) | (1ull << 62);
}
__device__ __forceinline__ uint32_t pack_bf16(float a, float b) {
    uint32_t r;
    asm("cvt.rn.bf16x2.f32 %0, %1, %2;" : "=r"(r) : "f"(b), "f"(a));
    return r;
}
__device__ __forceinline__ float ex2(float x) {
    float y;
    asm("ex2.approx.ftz.f32 %0, %1;" : "=f"(y) : "f"(x));
    return y;
}
template <int ID, int N> __device__ __forceinline__ void bar_sync() { asm volatile("bar.sync %0, %1;" ::"n"(ID), "n"(N) : "memory"); }
template <int ID, int N> __device__ __forceinline__ void bar_arrive() { asm volatile("bar.arrive %0, %1;" ::"n"(ID), "n"(N) : "memory"); }
__device__ __forceinline__ void sts128(uint32_t addr, uint32_t a, uint32_t b, uint32_t c, uint32_t d) {
    asm volatile("st.shared.v4.b32 [%0], {%1,%2,%3,%4};" ::"r"(addr), "r"(a), "r"(b), "r"(c), "r"(d) : "memory");
}
__device__ __forceinline__ void lds128(uint32_t addr, uint32_t (&r)[4]) {
    asm volatile("ld.shared.v4.b32 {%0,%1,%2,%3}, [%4];" : "=r"(r[0]), "=r"(r[1]), "=r"(r[2]), "=r"(r[3]) : "r"(addr) : "memory");
}

__device__ __forceinline__ void wgmma_ss_n256_tb(float (&d)[128], uint64_t da, uint64_t db, int sd) {
    asm volatile("{\n.reg .pred p;\nsetp.ne.b32 p, %130, 0;\n"
        "wgmma.mma_async.sync.aligned.m64n256k16.f32.bf16.bf16 "
        "{%0, %1, %2, %3, %4, %5, %6, %7, %8, %9, %10, %11, %12, %13, %14, %15, %16, %17, %18, %19, %20, %21, %22, %23, %24, %25, %26, %27, %28, %29, %30, %31, %32, %33, %34, %35, %36, %37, %38, %39, %40, %41, %42, %43, %44, %45, %46, %47, %48, %49, %50, %51, %52, %53, %54, %55, %56, %57, %58, %59, %60, %61, %62, %63, %64, %65, %66, %67, %68, %69, %70, %71, %72, %73, %74, %75, %76, %77, %78, %79, %80, %81, %82, %83, %84, %85, %86, %87, %88, %89, %90, %91, %92, %93, %94, %95, %96, %97, %98, %99, %100, %101, %102, %103, %104, %105, %106, %107, %108, %109, %110, %111, %112, %113, %114, %115, %116, %117, %118, %119, %120, %121, %122, %123, %124, %125, %126, %127}, "
        "%128, %129, p, 1, 1, 0, 1;\n}\n"
        : "+f"(d[0]), "+f"(d[1]), "+f"(d[2]), "+f"(d[3]), "+f"(d[4]), "+f"(d[5]), "+f"(d[6]), "+f"(d[7]), "+f"(d[8]), "+f"(d[9]), "+f"(d[10]), "+f"(d[11]), "+f"(d[12]), "+f"(d[13]), "+f"(d[14]), "+f"(d[15]), "+f"(d[16]), "+f"(d[17]), "+f"(d[18]), "+f"(d[19]), "+f"(d[20]), "+f"(d[21]), "+f"(d[22]), "+f"(d[23]), "+f"(d[24]), "+f"(d[25]), "+f"(d[26]), "+f"(d[27]), "+f"(d[28]), "+f"(d[29]), "+f"(d[30]), "+f"(d[31]), "+f"(d[32]), "+f"(d[33]), "+f"(d[34]), "+f"(d[35]), "+f"(d[36]), "+f"(d[37]), "+f"(d[38]), "+f"(d[39]), "+f"(d[40]), "+f"(d[41]), "+f"(d[42]), "+f"(d[43]), "+f"(d[44]), "+f"(d[45]), "+f"(d[46]), "+f"(d[47]), "+f"(d[48]), "+f"(d[49]), "+f"(d[50]), "+f"(d[51]), "+f"(d[52]), "+f"(d[53]), "+f"(d[54]), "+f"(d[55]), "+f"(d[56]), "+f"(d[57]), "+f"(d[58]), "+f"(d[59]), "+f"(d[60]), "+f"(d[61]), "+f"(d[62]), "+f"(d[63]), "+f"(d[64]), "+f"(d[65]), "+f"(d[66]), "+f"(d[67]), "+f"(d[68]), "+f"(d[69]), "+f"(d[70]), "+f"(d[71]), "+f"(d[72]), "+f"(d[73]), "+f"(d[74]), "+f"(d[75]), "+f"(d[76]), "+f"(d[77]), "+f"(d[78]), "+f"(d[79]), "+f"(d[80]), "+f"(d[81]), "+f"(d[82]), "+f"(d[83]), "+f"(d[84]), "+f"(d[85]), "+f"(d[86]), "+f"(d[87]), "+f"(d[88]), "+f"(d[89]), "+f"(d[90]), "+f"(d[91]), "+f"(d[92]), "+f"(d[93]), "+f"(d[94]), "+f"(d[95]), "+f"(d[96]), "+f"(d[97]), "+f"(d[98]), "+f"(d[99]), "+f"(d[100]), "+f"(d[101]), "+f"(d[102]), "+f"(d[103]), "+f"(d[104]), "+f"(d[105]), "+f"(d[106]), "+f"(d[107]), "+f"(d[108]), "+f"(d[109]), "+f"(d[110]), "+f"(d[111]), "+f"(d[112]), "+f"(d[113]), "+f"(d[114]), "+f"(d[115]), "+f"(d[116]), "+f"(d[117]), "+f"(d[118]), "+f"(d[119]), "+f"(d[120]), "+f"(d[121]), "+f"(d[122]), "+f"(d[123]), "+f"(d[124]), "+f"(d[125]), "+f"(d[126]), "+f"(d[127])
        : "l"(da), "l"(db), "r"(sd));
}
__device__ __forceinline__ void wgmma_rs_n128(float (&d)[64], uint32_t a0, uint32_t a1, uint32_t a2, uint32_t a3, uint64_t db, int sd) {
    asm volatile("{\n.reg .pred p;\nsetp.ne.b32 p, %69, 0;\n"
        "wgmma.mma_async.sync.aligned.m64n128k16.f32.bf16.bf16 "
        "{%0, %1, %2, %3, %4, %5, %6, %7, %8, %9, %10, %11, %12, %13, %14, %15, %16, %17, %18, %19, %20, %21, %22, %23, %24, %25, %26, %27, %28, %29, %30, %31, %32, %33, %34, %35, %36, %37, %38, %39, %40, %41, %42, %43, %44, %45, %46, %47, %48, %49, %50, %51, %52, %53, %54, %55, %56, %57, %58, %59, %60, %61, %62, %63}, "
        "{%64, %65, %66, %67}, %68, p, 1, 1, 0;\n}\n"
        : "+f"(d[0]), "+f"(d[1]), "+f"(d[2]), "+f"(d[3]), "+f"(d[4]), "+f"(d[5]), "+f"(d[6]), "+f"(d[7]), "+f"(d[8]), "+f"(d[9]), "+f"(d[10]), "+f"(d[11]), "+f"(d[12]), "+f"(d[13]), "+f"(d[14]), "+f"(d[15]), "+f"(d[16]), "+f"(d[17]), "+f"(d[18]), "+f"(d[19]), "+f"(d[20]), "+f"(d[21]), "+f"(d[22]), "+f"(d[23]), "+f"(d[24]), "+f"(d[25]), "+f"(d[26]), "+f"(d[27]), "+f"(d[28]), "+f"(d[29]), "+f"(d[30]), "+f"(d[31]), "+f"(d[32]), "+f"(d[33]), "+f"(d[34]), "+f"(d[35]), "+f"(d[36]), "+f"(d[37]), "+f"(d[38]), "+f"(d[39]), "+f"(d[40]), "+f"(d[41]), "+f"(d[42]), "+f"(d[43]), "+f"(d[44]), "+f"(d[45]), "+f"(d[46]), "+f"(d[47]), "+f"(d[48]), "+f"(d[49]), "+f"(d[50]), "+f"(d[51]), "+f"(d[52]), "+f"(d[53]), "+f"(d[54]), "+f"(d[55]), "+f"(d[56]), "+f"(d[57]), "+f"(d[58]), "+f"(d[59]), "+f"(d[60]), "+f"(d[61]), "+f"(d[62]), "+f"(d[63])
        : "r"(a0), "r"(a1), "r"(a2), "r"(a3), "l"(db), "r"(sd));
}
__device__ __forceinline__ void wgmma_rs_n128_tb(float (&d)[64], uint32_t a0, uint32_t a1, uint32_t a2, uint32_t a3, uint64_t db, int sd) {
    asm volatile("{\n.reg .pred p;\nsetp.ne.b32 p, %69, 0;\n"
        "wgmma.mma_async.sync.aligned.m64n128k16.f32.bf16.bf16 "
        "{%0, %1, %2, %3, %4, %5, %6, %7, %8, %9, %10, %11, %12, %13, %14, %15, %16, %17, %18, %19, %20, %21, %22, %23, %24, %25, %26, %27, %28, %29, %30, %31, %32, %33, %34, %35, %36, %37, %38, %39, %40, %41, %42, %43, %44, %45, %46, %47, %48, %49, %50, %51, %52, %53, %54, %55, %56, %57, %58, %59, %60, %61, %62, %63}, "
        "{%64, %65, %66, %67}, %68, p, 1, 1, 1;\n}\n"
        : "+f"(d[0]), "+f"(d[1]), "+f"(d[2]), "+f"(d[3]), "+f"(d[4]), "+f"(d[5]), "+f"(d[6]), "+f"(d[7]), "+f"(d[8]), "+f"(d[9]), "+f"(d[10]), "+f"(d[11]), "+f"(d[12]), "+f"(d[13]), "+f"(d[14]), "+f"(d[15]), "+f"(d[16]), "+f"(d[17]), "+f"(d[18]), "+f"(d[19]), "+f"(d[20]), "+f"(d[21]), "+f"(d[22]), "+f"(d[23]), "+f"(d[24]), "+f"(d[25]), "+f"(d[26]), "+f"(d[27]), "+f"(d[28]), "+f"(d[29]), "+f"(d[30]), "+f"(d[31]), "+f"(d[32]), "+f"(d[33]), "+f"(d[34]), "+f"(d[35]), "+f"(d[36]), "+f"(d[37]), "+f"(d[38]), "+f"(d[39]), "+f"(d[40]), "+f"(d[41]), "+f"(d[42]), "+f"(d[43]), "+f"(d[44]), "+f"(d[45]), "+f"(d[46]), "+f"(d[47]), "+f"(d[48]), "+f"(d[49]), "+f"(d[50]), "+f"(d[51]), "+f"(d[52]), "+f"(d[53]), "+f"(d[54]), "+f"(d[55]), "+f"(d[56]), "+f"(d[57]), "+f"(d[58]), "+f"(d[59]), "+f"(d[60]), "+f"(d[61]), "+f"(d[62]), "+f"(d[63])
        : "r"(a0), "r"(a1), "r"(a2), "r"(a3), "l"(db), "r"(sd));
}
__device__ __forceinline__ void wgmma_rs_n64_tb(float (&d)[32], uint32_t a0, uint32_t a1, uint32_t a2, uint32_t a3, uint64_t db, int sd) {
    asm volatile("{\n.reg .pred p;\nsetp.ne.b32 p, %37, 0;\n"
        "wgmma.mma_async.sync.aligned.m64n64k16.f32.bf16.bf16 "
        "{%0, %1, %2, %3, %4, %5, %6, %7, %8, %9, %10, %11, %12, %13, %14, %15, %16, %17, %18, %19, %20, %21, %22, %23, %24, %25, %26, %27, %28, %29, %30, %31}, "
        "{%32, %33, %34, %35}, %36, p, 1, 1, 1;\n}\n"
        : "+f"(d[0]), "+f"(d[1]), "+f"(d[2]), "+f"(d[3]), "+f"(d[4]), "+f"(d[5]), "+f"(d[6]), "+f"(d[7]), "+f"(d[8]), "+f"(d[9]), "+f"(d[10]), "+f"(d[11]), "+f"(d[12]), "+f"(d[13]), "+f"(d[14]), "+f"(d[15]), "+f"(d[16]), "+f"(d[17]), "+f"(d[18]), "+f"(d[19]), "+f"(d[20]), "+f"(d[21]), "+f"(d[22]), "+f"(d[23]), "+f"(d[24]), "+f"(d[25]), "+f"(d[26]), "+f"(d[27]), "+f"(d[28]), "+f"(d[29]), "+f"(d[30]), "+f"(d[31])
        : "r"(a0), "r"(a1), "r"(a2), "r"(a3), "l"(db), "r"(sd));
}

__global__ void __launch_bounds__(384, 1) fused_gqa_kernel(const __grid_constant__ Params P) {
    extern __shared__ uint8_t smem_raw[];
    const uint32_t base = (smem_u32(smem_raw) + 1023u) & ~1023u;
    const uint32_t smR = base;
    const uint32_t smS = base + R_BYTES;
    const uint32_t bars = smS + NSTAGE * STAGE_BYTES;
    const uint32_t prog = bars + 8 * (2 * NSTAGE + 10);
    const int tid = threadIdx.x;
    const int wid = __shfl_sync(0xffffffffu, tid >> 5, 0);
    const int lane = tid & 31;

    const int cta = blockIdx.x;
    const int blk = cta >> 6;
    const int hp = (cta >> 3) & 7;
    const int b = cta & 7;
    const int grp = blk * 8 + b;

    if (tid == 0) {
        TS(0);
        for (int i = 0; i < NSTAGE; i++) {
            mbar_init(bars + 8 * i, 1);
            mbar_init(bars + 8 * (NSTAGE + i), 8);
        }
        for (int i = 0; i < 10; i++) mbar_init(bars + 8 * (2 * NSTAGE + i), 4);
        asm volatile("st.volatile.shared.u32 [%0], %1;" ::"r"(prog), "r"(0) : "memory");
        asm volatile("fence.mbarrier_init.release.cluster;" ::: "memory");
        asm volatile("fence.proxy.async.shared::cta;" ::: "memory");
    }
    __syncthreads();

    if (wid >= 8) {
        asm volatile("setmaxnreg.dec.sync.aligned.u32 40;");
        if (wid == 8) {
            if (lane == 0) {
                int slot = 0, ph = 1;
                for (int s = 0; s < N_WQ; s++) {
                    const uint32_t fb = bars + 8 * slot;
                    mbar_wait(bars + 8 * (NSTAGE + slot), ph);
                    const uint32_t dst = smS + slot * STAGE_BYTES;
                    mbar_expect_tx(fb, (s & 1) ? STAGE_BYTES : STAGE_BYTES + 8192);
                    if (!(s & 1)) tma_2d(smR + ((s >> 1) & 7) * 8192, &P.x[blk], (s >> 1) * 64, b * 64, fb);
#pragma unroll
                    for (int p = 0; p < 8; p++) {
                        const int w = p >> 2, j = (p >> 1) & 1, glo = p & 1;
                        tma_2d(dst + p * 4096, &P.wq[blk], hp * 512 + (j * 4 + w * 2 + glo) * 64, s * 32, fb);
                    }
                    if (++slot == NSTAGE) { slot = 0; ph ^= 1; }
                }
                for (int i = 0; i < 34; i++) {
                    const uint32_t fb = bars + 8 * slot;
                    mbar_wait(bars + 8 * (NSTAGE + slot), ph);
                    const uint32_t dst = smS + slot * STAGE_BYTES;
                    mbar_expect_tx(fb, STAGE_BYTES);
                    if (i < 16) {
                        const int row = (b * kHkv + hp * 2) * kSk + (i >> 1) * 128;
                        const CUtensorMap* tm = (i & 1) ? &P.v[blk] : &P.k[blk];
                        tma_2d(dst, tm, 0, row, fb);
                        tma_2d(dst + 16384, tm, 64, row, fb);
                    } else {
                        const int q = i - 16;
                        const int c0 = (q >> 2) * 128;
                        tma_2d(dst, &P.wo[blk], c0, hp * 512 + (q & 3) * 128, fb);
                        tma_2d(dst + 16384, &P.wo[blk], (q < 16) ? c0 + 64 : c0, hp * 512 + ((q + 2) & 3) * 128, fb);
                    }
                    asm volatile("st.volatile.shared.u32 [%0], %1;" ::"r"(prog), "r"(i + 1) : "memory");
                    if (++slot == NSTAGE) { slot = 0; ph ^= 1; }
                }
            }
        } else if (wid == 11) {
            if (PF_DIST > 0) {
                uint32_t sink = 0;
                if (PF_WQ) {
                    const char* wqs = (const char*)(P.wqp[blk] + hp * 512) + (size_t)(160 + b * 52) * 8192;
#pragma unroll
                    for (int h = 0; h < 2; h++) {
#pragma unroll
                        for (int j = 0; j < 4; j++) {
                            const int e = (h * 4 + j) * 32 + lane;
                            if (e < 208) sink |= l2_touch(wqs + (size_t)(e >> 2) * 8192 + (e & 3) * 256);
                        }
                        if (sink == 0x9E3779B9u) asm volatile("st.volatile.shared.u32 [%0], %1;" ::"r"(prog + 4), "r"(sink) : "memory");
                    }
                }
                const char* kbase = (const char*)(P.kp[blk] + (size_t)(b * kHkv + hp * 2) * kSk * kDh);
                const char* vbase = (const char*)(P.vp[blk] + (size_t)(b * kHkv + hp * 2) * kSk * kDh);
                const char* wos = (const char*)(P.wop[blk] + (size_t)hp * 512 * kD) + (size_t)b * 73728;
                for (int i = 0; i < 19; i++) {
                    if (i >= PF_DIST) {
                        uint32_t pr, n = 0;
                        while (true) {
                            asm volatile("ld.volatile.shared.u32 %0, [%1];" : "=r"(pr) : "r"(prog) : "memory");
                            if ((int)pr + PF_DIST >= i) break;
                            if (++n > (1u << 22)) break;
                            __nanosleep(100);
                        }
                    }
                    if (i < 16) {
                        const char* p = ((i & 1) ? vbase : kbase) + (size_t)(i >> 1) * 32768 + lane * 256;
#pragma unroll
                        for (int j = 0; j < 4; j++) sink |= l2_touch(p + j * 8192);
                    } else {
                        const char* p = wos + (size_t)(i - 16) * 24576 + lane * 256;
#pragma unroll
                        for (int j = 0; j < 3; j++) sink |= l2_touch(p + j * 8192);
                    }
                    if (sink == 0x9E3779B9u) asm volatile("st.volatile.shared.u32 [%0], %1;" ::"r"(prog + 4), "r"(sink) : "memory");
                }
            }
        } else {
            const int hw = wid - 9;
            for (int k = 0; k < 5; k++) {
                mbar_wait(bars + 8 * (2 * NSTAGE + hw * 5 + k), 0);
                const int c = (k < 4) ? (2 * k + hw) : 8;
                asm volatile("fence.acq_rel.gpu;" ::: "memory");
                asm volatile("red.relaxed.gpu.global.add.u32 [%0], 1;" ::"l"(&g_cnt[(grp * 9 + c) * 32 + lane]) : "memory");
            }
        }
    } else {
        asm volatile("setmaxnreg.inc.sync.aligned.u32 232;");
        const int w = wid >> 2;
        const int t = tid & 127;
        int slot = 0, ph = 0;
        uint32_t qf[8][4];
        const uint32_t stash = smR + (1 + w) * 16384 + t * 16;
        {
            float acc[128];
            int pslot = 0;
            for (int s = 0; s < N_WQ; s++) {
                mbar_wait(bars + 8 * slot, ph);
                if (tid == 0 && s == 0) TS(20);
                if (tid == 0 && s == 5) TS(21);
                if (tid == 0 && s == 10) TS(22);
                const uint64_t da = mk_desc(smR + ((s >> 1) & 7) * 8192 + (s & 1) * 64, 16, 1024);
                const uint64_t db = mk_desc(smS + slot * STAGE_BYTES + w * 16384, 4096, 1024);
                wg_fence();
                wgmma_ss_n256_tb(acc, da, db, s != 0);
                wgmma_ss_n256_tb(acc, da + 2, db + 128, 1);
                wg_commit();
                if (s > 0) {
                    wg_wait<1>();
                    if (lane == 0) mbar_arrive(bars + 8 * (NSTAGE + pslot));
                }
                pslot = slot;
                if (++slot == NSTAGE) { slot = 0; ph ^= 1; }
            }
            wg_wait<0>();
            if (lane == 0) mbar_arrive(bars + 8 * (NSTAGE + pslot));
            fence_regs(acc);
            if (tid == 0) TS(1);
#pragma unroll
            for (int kk = 0; kk < 8; kk++) {
#pragma unroll
                for (int i = 0; i < 4; i++) qf[kk][i] = pack_bf16(acc[8 * kk + 2 * i], acc[8 * kk + 2 * i + 1]);
                sts128(stash + kk * 2048,
                       pack_bf16(acc[64 + 8 * kk + 0], acc[64 + 8 * kk + 1]), pack_bf16(acc[64 + 8 * kk + 2], acc[64 + 8 * kk + 3]),
                       pack_bf16(acc[64 + 8 * kk + 4], acc[64 + 8 * kk + 5]), pack_bf16(acc[64 + 8 * kk + 6], acc[64 + 8 * kk + 7]));
            }
        }
        if (w == 1) bar_arrive<5, 256>();
        const float sc = 0.08838834764831845f * 1.4426950408889634f;
#pragma unroll 1
        for (int u = 0; u < 2; u++) {
            {
                if (u == 1) {
#pragma unroll
                    for (int kk = 0; kk < 8; kk++) lds128(stash + kk * 2048, qf[kk]);
                }
                float o[64], s[64];
                float m0 = -INFINITY, m1 = -INFINITY, l0 = 0.f, l1 = 0.f;
                uint32_t pf[8][4];
#pragma unroll
                for (int i = 0; i < 64; i++) { o[i] = 0.f; s[i] = 0.f; }
#pragma unroll
                for (int i = 0; i < 32; i++) pf[i >> 2][i & 3] = 0u;
#pragma unroll 1
                for (int tt = 0; tt <= 4; tt++) {
                    int vslot = slot;
                    if (tt > 0) {
                        mbar_wait(bars + 8 * slot, ph);
                        if (++slot == NSTAGE) { slot = 0; ph ^= 1; }
                    }
                    if (tt < 4) mbar_wait(bars + 8 * slot, ph);
                    if (tid == 0) TS(32 + u * 20 + tt * 4);
                    if (w == 0) bar_sync<5, 256>(); else bar_sync<6, 256>();
                    wg_fence();
                    if (tt > 0) {
                        const uint64_t db = mk_desc(smS + vslot * STAGE_BYTES, 16384, 1024);
#pragma unroll
                        for (int kk = 0; kk < 8; kk++)
                            wgmma_rs_n128_tb(o, pf[kk][0], pf[kk][1], pf[kk][2], pf[kk][3], db + kk * 128, (tt > 1) || (kk != 0));
                        wg_commit();
                    }
                    if (tt < 4) {
                        const uint64_t db = mk_desc(smS + slot * STAGE_BYTES, 16, 1024);
#pragma unroll
                        for (int kk = 0; kk < 8; kk++)
                            wgmma_rs_n128(s, qf[kk][0], qf[kk][1], qf[kk][2], qf[kk][3], db + (kk >> 2) * 1024 + (kk & 3) * 2, kk != 0);
                        wg_commit();
                    }
                    if (w == 0) bar_arrive<6, 256>(); else if (!(u == 1 && tt == 4)) bar_arrive<5, 256>();
                    if (tid == 0) TS(32 + u * 20 + tt * 4 + 1);
                    wg_wait<0>();
                    fence_regs(o);
                    fence_regs(s);
                    if (tid == 0) TS(32 + u * 20 + tt * 4 + 2);
                    if (tt > 0 && lane == 0) mbar_arrive(bars + 8 * (NSTAGE + vslot));
                    if (tt == 4) break;
                    if (lane == 0) mbar_arrive(bars + 8 * (NSTAGE + slot));
                    if (++slot == NSTAGE) { slot = 0; ph ^= 1; }
                    float mx0 = s[0], mx1 = s[2];
#pragma unroll
                    for (int j = 0; j < 16; j++) {
                        mx0 = fmaxf(mx0, fmaxf(s[4 * j], s[4 * j + 1]));
                        mx1 = fmaxf(mx1, fmaxf(s[4 * j + 2], s[4 * j + 3]));
                    }
                    mx0 = fmaxf(mx0, __shfl_xor_sync(0xffffffffu, mx0, 1));
                    mx1 = fmaxf(mx1, __shfl_xor_sync(0xffffffffu, mx1, 1));
                    mx0 = fmaxf(mx0, __shfl_xor_sync(0xffffffffu, mx0, 2));
                    mx1 = fmaxf(mx1, __shfl_xor_sync(0xffffffffu, mx1, 2));
                    const float mn0 = fmaxf(m0, mx0), mn1 = fmaxf(m1, mx1);
                    const float al0 = ex2((m0 - mn0) * sc), al1 = ex2((m1 - mn1) * sc);
                    m0 = mn0; m1 = mn1;
                    const float ms0 = mn0 * sc, ms1 = mn1 * sc;
                    float rs0 = 0.f, rs1 = 0.f;
#pragma unroll
                    for (int j = 0; j < 16; j++) {
                        const float p0 = ex2(fmaf(s[4 * j], sc, -ms0)), p1 = ex2(fmaf(s[4 * j + 1], sc, -ms0));
                        const float p2 = ex2(fmaf(s[4 * j + 2], sc, -ms1)), p3 = ex2(fmaf(s[4 * j + 3], sc, -ms1));
                        rs0 += p0 + p1; rs1 += p2 + p3;
                        pf[j >> 1][(j & 1) * 2] = pack_bf16(p0, p1);
                        pf[j >> 1][(j & 1) * 2 + 1] = pack_bf16(p2, p3);
                    }
                    l0 = l0 * al0 + rs0; l1 = l1 * al1 + rs1;
                    if (tt > 0) {
#pragma unroll
                        for (int j = 0; j < 16; j++) { o[4 * j] *= al0; o[4 * j + 1] *= al0; o[4 * j + 2] *= al1; o[4 * j + 3] *= al1; }
                    }
                    if (tid == 0) TS(32 + u * 20 + tt * 4 + 3);
                }
                if (tid == 0) TS(2 + u);
                l0 += __shfl_xor_sync(0xffffffffu, l0, 1);
                l1 += __shfl_xor_sync(0xffffffffu, l1, 1);
                l0 += __shfl_xor_sync(0xffffffffu, l0, 2);
                l1 += __shfl_xor_sync(0xffffffffu, l1, 2);
                const float i0 = 1.f / l0, i1 = 1.f / l1;
                const uint32_t zown = smR + ((u == 0) ? (w ? 3 : 0) : (w ? 2 : 1)) * 16384 + t * 16;
#pragma unroll
                for (int kk = 0; kk < 8; kk++)
                    sts128(zown + kk * 2048,
                           pack_bf16(o[8 * kk + 0] * i0, o[8 * kk + 1] * i0), pack_bf16(o[8 * kk + 2] * i1, o[8 * kk + 3] * i1),
                           pack_bf16(o[8 * kk + 4] * i0, o[8 * kk + 5] * i0), pack_bf16(o[8 * kk + 6] * i1, o[8 * kk + 7] * i1));
            }
        }
        bar_sync<4, 256>();
        {
            uint32_t af[32][4];
#pragma unroll
            for (int hh = 0; hh < 4; hh++) {
                const int h2 = (hh + 2 * w) & 3;
                const int z = (0x2130 >> (h2 * 4)) & 3;
#pragma unroll
                for (int kk = 0; kk < 8; kk++) lds128(smR + z * 16384 + kk * 2048 + t * 16, af[hh * 8 + kk]);
            }
            float acc[2][32];
#pragma unroll
            for (int i = 0; i < 32; i++) { acc[0][i] = 0.f; acc[1][i] = 0.f; }
            int pslot = 0;
            uint2* dst0 = g_part + (size_t)(grp * 80 + w * 8 + hp) * 1024 + t;
            uint2* dst8 = g_part + (size_t)(grp * 80 + 64 + hp * 2 + w) * 1024 + t;
#pragma unroll
            for (int st = 0; st <= 18; st++) {
                if (st < 18) {
                    const int kq = st & 3, ab = (st >> 2) & 1;
                    mbar_wait(bars + 8 * slot, ph);
                    const uint64_t db = mk_desc(smS + slot * STAGE_BYTES + w * 16384, 16384, 1024);
                    wg_fence();
#pragma unroll
                    for (int kk = 0; kk < 8; kk++)
                        wgmma_rs_n64_tb(acc[ab], af[kq * 8 + kk][0], af[kq * 8 + kk][1], af[kq * 8 + kk][2], af[kq * 8 + kk][3], db + kk * 128, (kq | kk) != 0);
                    wg_commit();
                }
                if (st > 0) {
                    if (st < 18) wg_wait<1>(); else wg_wait<0>();
                    if (lane == 0) mbar_arrive(bars + 8 * (NSTAGE + pslot));
                    if ((st & 3) == 0 || st == 18) {
                        const int k = (st - 1) >> 2, ab = k & 1;
                        fence_regs(acc[ab]);
                        uint2* dst = (k < 4) ? (dst0 + (size_t)k * 16 * 1024) : dst8;
#pragma unroll
                        for (int j = 0; j < 8; j++)
                            __stcg(dst + j * 128, make_uint2(pack_bf16(acc[ab][4 * j], acc[ab][4 * j + 1]), pack_bf16(acc[ab][4 * j + 2], acc[ab][4 * j + 3])));
                        __syncwarp();
                        if (lane == 0) mbar_arrive(bars + 8 * (2 * NSTAGE + w * 5 + k));
                        if (tid == 0) TS(4 + k);
                    }
                }
                pslot = slot;
                if (++slot == NSTAGE) { slot = 0; ph ^= 1; }
            }
        }
        {
            const int nch = (w == 0) ? 5 : 4;
            if (lane < nch) {
                const int c = (lane < 4) ? (2 * lane + w) : 8;
                const unsigned need = (lane < 4) ? 8u : 16u;
                unsigned* cp = &g_cnt[(grp * 9 + c) * 32 + hp * 4 + (wid & 3)];
                unsigned v, n = 0;
                while (true) {
                    asm volatile("ld.acquire.gpu.global.u32 %0, [%1];" : "=r"(v) : "l"(cp) : "memory");
                    if (v >= need) break;
                    if (++n > (1u << 21)) break;
                }
                *cp = 0;
            }
            __syncwarp();
            if (tid == 0) TS(18);
            __nv_bfloat16* orow = P.out + (size_t)(b * 64 + (t >> 5) * 16 + (lane >> 2)) * (2 * kD) + blk * kD + hp * 8 + (lane & 3) * 2;
            const uint2* src = g_part + ((size_t)(grp * 80 + w * 8) * 8 + hp) * 128 + t;
            uint2 v[4][8];
#pragma unroll
            for (int k = 0; k < 4; k++)
#pragma unroll
                for (int i = 0; i < 8; i++) v[k][i] = __ldcg(src + (size_t)(k * 16 + i) * 1024);
            if (w == 0) {
                const uint2* src8 = g_part + ((size_t)(grp * 80 + 64) * 8 + hp) * 128 + t;
                uint2 u[16];
#pragma unroll
                for (int i = 0; i < 16; i++) u[i] = __ldcg(src8 + (size_t)i * 1024);
                float a0 = 0.f, a1 = 0.f, a2 = 0.f, a3 = 0.f;
#pragma unroll
                for (int i = 0; i < 16; i++) {
                    a0 += __uint_as_float(u[i].x << 16); a1 += __uint_as_float(u[i].x & 0xffff0000u);
                    a2 += __uint_as_float(u[i].y << 16); a3 += __uint_as_float(u[i].y & 0xffff0000u);
                }
                *(uint32_t*)(orow + 512) = pack_bf16(a0, a1);
                *(uint32_t*)(orow + 512 + 8 * 2 * kD) = pack_bf16(a2, a3);
            }
#pragma unroll
            for (int k = 0; k < 4; k++) {
                float a0 = 0.f, a1 = 0.f, a2 = 0.f, a3 = 0.f;
#pragma unroll
                for (int i = 0; i < 8; i++) {
                    a0 += __uint_as_float(v[k][i].x << 16); a1 += __uint_as_float(v[k][i].x & 0xffff0000u);
                    a2 += __uint_as_float(v[k][i].y << 16); a3 += __uint_as_float(v[k][i].y & 0xffff0000u);
                }
                *(uint32_t*)(orow + (2 * k + w) * 64) = pack_bf16(a0, a1);
                *(uint32_t*)(orow + (2 * k + w) * 64 + 8 * 2 * kD) = pack_bf16(a2, a3);
            }
            if (tid == 0) TS(19);
        }
    }
}

typedef CUresult (*EncodeFn)(CUtensorMap*, CUtensorMapDataType, cuuint32_t, void*, const cuuint64_t*, const cuuint64_t*,
                             const cuuint32_t*, const cuuint32_t*, CUtensorMapInterleave, CUtensorMapSwizzle,
                             CUtensorMapL2promotion, CUtensorMapFloatOOBfill);

void make_map(EncodeFn fn, CUtensorMap* m, const void* ptr, uint64_t cols, uint64_t rows, uint32_t box_rows) {
    cuuint64_t dims[2] = {cols, rows};
    cuuint64_t strides[1] = {cols * 2};
    cuuint32_t box[2] = {64, box_rows};
    cuuint32_t es[2] = {1, 1};
    fn(m, CU_TENSOR_MAP_DATA_TYPE_BFLOAT16, 2, const_cast<void*>(ptr), dims, strides, box, es, CU_TENSOR_MAP_INTERLEAVE_NONE,
       CU_TENSOR_MAP_SWIZZLE_128B, CU_TENSOR_MAP_L2_PROMOTION_L2_256B, CU_TENSOR_MAP_FLOAT_OOB_FILL_NONE);
}

}

extern "C" void kernel_launch(void* const* d_in, const int* in_sizes, int n_in, void* d_out, int out_size) {
    static EncodeFn enc = nullptr;
    if (!enc) {
        void* fn = nullptr;
        cudaDriverEntryPointQueryResult st;
        cudaGetDriverEntryPoint("cuTensorMapEncodeTiled", &fn, cudaEnableDefault, &st);
        enc = (EncodeFn)fn;
        cudaFuncSetAttribute(fused_gqa_kernel, cudaFuncAttributeMaxDynamicSharedMemorySize, SMEM_BYTES);
    }
    Params P;
    for (int blk = 0; blk < 2; blk++) {
        const void* x = d_in[blk * 5 + 0];
        const void* k = d_in[blk * 5 + 1];
        const void* v = d_in[blk * 5 + 2];
        const void* wq = d_in[blk * 5 + 3];
        const void* wo = d_in[blk * 5 + 4];
        make_map(enc, &P.x[blk], x, kD, kB * kSq, 64);
        make_map(enc, &P.wq[blk], wq, kHq * kDh, kD, 32);
        make_map(enc, &P.k[blk], k, kDh, (uint64_t)kB * kHkv * kSk, 128);
        make_map(enc, &P.v[blk], v, kDh, (uint64_t)kB * kHkv * kSk, 128);
        make_map(enc, &P.wo[blk], wo, kD, kHq * kDh, 128);
        P.wqp[blk] = (const __nv_bfloat16*)wq;
        P.kp[blk] = (const __nv_bfloat16*)k;
        P.vp[blk] = (const __nv_bfloat16*)v;
        P.wop[blk] = (const __nv_bfloat16*)wo;
    }
    P.out = (__nv_bfloat16*)d_out;
    fused_gqa_kernel<<<128, 384, SMEM_BYTES>>>(P);
}
```

```cpp
#include <cuda_runtime.h>
#include <cuda_bf16.h>
#include <cuda.h>
#include <stdint.h>

namespace {

constexpr int kB = 8, kSq = 64, kD = 576, kHq = 32, kHkv = 16, kSk = 512, kDh = 128;
constexpr int NSTAGE = 5;
constexpr int STAGE_BYTES = 32768;
constexpr int R_BYTES = 65536;
constexpr int SMEM_BYTES = R_BYTES + NSTAGE * STAGE_BYTES + 1024   + 256  ;
constexpr int N_WQ = 18;
#define PF_DIST_V 4
#define PF_WQ 0
#define PF_SLEEP 1000
constexpr int PF_DIST = PF_DIST_V;

struct __align__(64) Params {
    CUtensorMap x[2], wq[2], k[2], v[2], wo[2];
    const __nv_bfloat16* wqp[2];
    const __nv_bfloat16* kp[2];
    const __nv_bfloat16* vp[2];
    const __nv_bfloat16* wop[2];
    __nv_bfloat16* out;
};

__device__ uint2 g_part[16 * 80 * 8 * 128];
__device__ unsigned int g_cnt[16 * 9 * 32];
#define TS(k) do {} while (0)

__device__ __forceinline__ uint32_t smem_u32(const void* p) { return (uint32_t)__cvta_generic_to_shared(p); }
__device__ __forceinline__ void mbar_init(uint32_t bar, int cnt) {
    asm volatile("mbarrier.init.shared::cta.b64 [%0], %1;" ::"r"(bar), "r"(cnt));
}
__device__ __forceinline__ void mbar_expect_tx(uint32_t bar, uint32_t bytes) {
    asm volatile("mbarrier.arrive.expect_tx.shared::cta.b64 _, [%0], %1;" ::"r"(bar), "r"(bytes) : "memory");
}
__device__ __forceinline__ void mbar_arrive(uint32_t bar) {
    asm volatile("mbarrier.arrive.shared::cta.b64 _, [%0];" ::"r"(bar) : "memory");
}
__device__ __forceinline__ bool mbar_try(uint32_t bar, uint32_t parity) {
    uint32_t ok;
    asm volatile("{\n.reg .pred p;\nmbarrier.try_wait.parity.shared::cta.b64 p, [%1], %2;\nselp.u32 %0, 1, 0, p;\n}\n"
                 : "=r"(ok) : "r"(bar), "r"(parity) : "memory");
    return ok != 0;
}
__device__ __forceinline__ void mbar_wait(uint32_t bar, uint32_t parity) {
    if (mbar_try(bar, parity)) return;
    uint32_t n = 0;
    while (!mbar_try(bar, parity)) {
        if (++n > (1u << 20)) break;
    }
}
__device__ __forceinline__ void tma_2d(uint32_t dst, const CUtensorMap* tm, int c0, int c1, uint32_t bar) {
    asm volatile("cp.async.bulk.tensor.2d.shared::cluster.global.mbarrier::complete_tx::bytes [%0], [%1, {%3, %4}], [%2];"
                 ::"r"(dst), "l"(tm), "r"(bar), "r"(c0), "r"(c1) : "memory");
}
__device__ __forceinline__ void l2_prefetch(const void* p, uint32_t bytes) {
    asm volatile("cp.async.bulk.prefetch.L2.global [%0], %1;" ::"l"(p), "r"(bytes) : "memory");
}
__device__ __forceinline__ uint32_t l2_touch(const void* p) {
    uint32_t v;
    asm volatile("ld.global.L2::256B.b32 %0, [%1];" : "=r"(v) : "l"(p) : "memory");
    return v;
}
__device__ __forceinline__ void wg_fence() { asm volatile("wgmma.fence.sync.aligned;" ::: "memory"); }
__device__ __forceinline__ void wg_commit() { asm volatile("wgmma.commit_group.sync.aligned;" ::: "memory"); }
template <int N> __device__ __forceinline__ void wg_wait() { asm volatile("wgmma.wait_group.sync.aligned %0;" ::"n"(N) : "memory"); }
template <int N> __device__ __forceinline__ void fence_regs(float (&d)[N]) {
#pragma unroll
    for (int i = 0; i < N; i++) asm volatile("" : "+f"(d[i])::"memory");
}
__device__ __forceinline__ uint64_t mk_desc(uint32_t addr, uint32_t lbo, uint32_t sbo) {
    return (uint64_t)((addr & 0x3FFFF) >> 4) | ((uint64_t)(lbo >> 4) << 16) | ((uint64_t)(sbo >> 4) << 32) | (1ull << 62);
}
__device__ __forceinline__ uint32_t pack_bf16(float a, float b) {
    uint32_t r;
    asm("cvt.rn.bf16x2.f32 %0, %1, %2;" : "=r"(r) : "f"(b), "f"(a));
    return r;
}
__device__ __forceinline__ float ex2(float x) {
    float y;
    asm("ex2.approx.ftz.f32 %0, %1;" : "=f"(y) : "f"(x));
    return y;
}
template <int ID, int N> __device__ __forceinline__ void bar_sync() { asm volatile("bar.sync %0, %1;" ::"n"(ID), "n"(N) : "memory"); }
template <int ID, int N> __device__ __forceinline__ void bar_arrive() { asm volatile("bar.arrive %0, %1;" ::"n"(ID), "n"(N) : "memory"); }
__device__ __forceinline__ void sts128(uint32_t addr, uint32_t a, uint32_t b, uint32_t c, uint32_t d) {
    asm volatile("st.shared.v4.b32 [%0], {%1,%2,%3,%4};" ::"r"(addr), "r"(a), "r"(b), "r"(c), "r"(d) : "memory");
}
__device__ __forceinline__ void lds128(uint32_t addr, uint32_t (&r)[4]) {
    asm volatile("ld.shared.v4.b32 {%0,%1,%2,%3}, [%4];" : "=r"(r[0]), "=r"(r[1]), "=r"(r[2]), "=r"(r[3]) : "r"(addr) : "memory");
}

__device__ __forceinline__ void wgmma_ss_n256_tb(float (&d)[128], uint64_t da, uint64_t db, int sd) {
    asm volatile("{\n.reg .pred p;\nsetp.ne.b32 p, %130, 0;\n"
        "wgmma.mma_async.sync.aligned.m64n256k16.f32.bf16.bf16 "
        "{%0, %1, %2, %3, %4, %5, %6, %7, %8, %9, %10, %11, %12, %13, %14, %15, %16, %17, %18, %19, %20, %21, %22, %23, %24, %25, %26, %27, %28, %29, %30, %31, %32, %33, %34, %35, %36, %37, %38, %39, %40, %41, %42, %43, %44, %45, %46, %47, %48, %49, %50, %51, %52, %53, %54, %55, %56, %57, %58, %59, %60, %61, %62, %63, %64, %65, %66, %67, %68, %69, %70, %71, %72, %73, %74, %75, %76, %77, %78, %79, %80, %81, %82, %83, %84, %85, %86, %87, %88, %89, %90, %91, %92, %93, %94, %95, %96, %97, %98, %99, %100, %101, %102, %103, %104, %105, %106, %107, %108, %109, %110, %111, %112, %113, %114, %115, %116, %117, %118, %119, %120, %121, %122, %123, %124, %125, %126, %127}, "
        "%128, %129, p, 1, 1, 0, 1;\n}\n"
        : "+f"(d[0]), "+f"(d[1]), "+f"(d[2]), "+f"(d[3]), "+f"(d[4]), "+f"(d[5]), "+f"(d[6]), "+f"(d[7]), "+f"(d[8]), "+f"(d[9]), "+f"(d[10]), "+f"(d[11]), "+f"(d[12]), "+f"(d[13]), "+f"(d[14]), "+f"(d[15]), "+f"(d[16]), "+f"(d[17]), "+f"(d[18]), "+f"(d[19]), "+f"(d[20]), "+f"(d[21]), "+f"(d[22]), "+f"(d[23]), "+f"(d[24]), "+f"(d[25]), "+f"(d[26]), "+f"(d[27]), "+f"(d[28]), "+f"(d[29]), "+f"(d[30]), "+f"(d[31]), "+f"(d[32]), "+f"(d[33]), "+f"(d[34]), "+f"(d[35]), "+f"(d[36]), "+f"(d[37]), "+f"(d[38]), "+f"(d[39]), "+f"(d[40]), "+f"(d[41]), "+f"(d[42]), "+f"(d[43]), "+f"(d[44]), "+f"(d[45]), "+f"(d[46]), "+f"(d[47]), "+f"(d[48]), "+f"(d[49]), "+f"(d[50]), "+f"(d[51]), "+f"(d[52]), "+f"(d[53]), "+f"(d[54]), "+f"(d[55]), "+f"(d[56]), "+f"(d[57]), "+f"(d[58]), "+f"(d[59]), "+f"(d[60]), "+f"(d[61]), "+f"(d[62]), "+f"(d[63]), "+f"(d[64]), "+f"(d[65]), "+f"(d[66]), "+f"(d[67]), "+f"(d[68]), "+f"(d[69]), "+f"(d[70]), "+f"(d[71]), "+f"(d[72]), "+f"(d[73]), "+f"(d[74]), "+f"(d[75]), "+f"(d[76]), "+f"(d[77]), "+f"(d[78]), "+f"(d[79]), "+f"(d[80]), "+f"(d[81]), "+f"(d[82]), "+f"(d[83]), "+f"(d[84]), "+f"(d[85]), "+f"(d[86]), "+f"(d[87]), "+f"(d[88]), "+f"(d[89]), "+f"(d[90]), "+f"(d[91]), "+f"(d[92]), "+f"(d[93]), "+f"(d[94]), "+f"(d[95]), "+f"(d[96]), "+f"(d[97]), "+f"(d[98]), "+f"(d[99]), "+f"(d[100]), "+f"(d[101]), "+f"(d[102]), "+f"(d[103]), "+f"(d[104]), "+f"(d[105]), "+f"(d[106]), "+f"(d[107]), "+f"(d[108]), "+f"(d[109]), "+f"(d[110]), "+f"(d[111]), "+f"(d[112]), "+f"(d[113]), "+f"(d[114]), "+f"(d[115]), "+f"(d[116]), "+f"(d[117]), "+f"(d[118]), "+f"(d[119]), "+f"(d[120]), "+f"(d[121]), "+f"(d[122]), "+f"(d[123]), "+f"(d[124]), "+f"(d[125]), "+f"(d[126]), "+f"(d[127])
        : "l"(da), "l"(db), "r"(sd));
}
__device__ __forceinline__ void wgmma_rs_n128(float (&d)[64], uint32_t a0, uint32_t a1, uint32_t a2, uint32_t a3, uint64_t db, int sd) {
    asm volatile("{\n.reg .pred p;\nsetp.ne.b32 p, %69, 0;\n"
        "wgmma.mma_async.sync.aligned.m64n128k16.f32.bf16.bf16 "
        "{%0, %1, %2, %3, %4, %5, %6, %7, %8, %9, %10, %11, %12, %13, %14, %15, %16, %17, %18, %19, %20, %21, %22, %23, %24, %25, %26, %27, %28, %29, %30, %31, %32, %33, %34, %35, %36, %37, %38, %39, %40, %41, %42, %43, %44, %45, %46, %47, %48, %49, %50, %51, %52, %53, %54, %55, %56, %57, %58, %59, %60, %61, %62, %63}, "
        "{%64, %65, %66, %67}, %68, p, 1, 1, 0;\n}\n"
        : "+f"(d[0]), "+f"(d[1]), "+f"(d[2]), "+f"(d[3]), "+f"(d[4]), "+f"(d[5]), "+f"(d[6]), "+f"(d[7]), "+f"(d[8]), "+f"(d[9]), "+f"(d[10]), "+f"(d[11]), "+f"(d[12]), "+f"(d[13]), "+f"(d[14]), "+f"(d[15]), "+f"(d[16]), "+f"(d[17]), "+f"(d[18]), "+f"(d[19]), "+f"(d[20]), "+f"(d[21]), "+f"(d[22]), "+f"(d[23]), "+f"(d[24]), "+f"(d[25]), "+f"(d[26]), "+f"(d[27]), "+f"(d[28]), "+f"(d[29]), "+f"(d[30]), "+f"(d[31]), "+f"(d[32]), "+f"(d[33]), "+f"(d[34]), "+f"(d[35]), "+f"(d[36]), "+f"(d[37]), "+f"(d[38]), "+f"(d[39]), "+f"(d[40]), "+f"(d[41]), "+f"(d[42]), "+f"(d[43]), "+f"(d[44]), "+f"(d[45]), "+f"(d[46]), "+f"(d[47]), "+f"(d[48]), "+f"(d[49]), "+f"(d[50]), "+f"(d[51]), "+f"(d[52]), "+f"(d[53]), "+f"(d[54]), "+f"(d[55]), "+f"(d[56]), "+f"(d[57]), "+f"(d[58]), "+f"(d[59]), "+f"(d[60]), "+f"(d[61]), "+f"(d[62]), "+f"(d[63])
        : "r"(a0), "r"(a1), "r"(a2), "r"(a3), "l"(db), "r"(sd));
}
__device__ __forceinline__ void wgmma_rs_n128_tb(float (&d)[64], uint32_t a0, uint32_t a1, uint32_t a2, uint32_t a3, uint64_t db, int sd) {
    asm volatile("{\n.reg .pred p;\nsetp.ne.b32 p, %69, 0;\n"
        "wgmma.mma_async.sync.aligned.m64n128k16.f32.bf16.bf16 "
        "{%0, %1, %2, %3, %4, %5, %6, %7, %8, %9, %10, %11, %12, %13, %14, %15, %16, %17, %18, %19, %20, %21, %22, %23, %24, %25, %26, %27, %28, %29, %30, %31, %32, %33, %34, %35, %36, %37, %38, %39, %40, %41, %42, %43, %44, %45, %46, %47, %48, %49, %50, %51, %52, %53, %54, %55, %56, %57, %58, %59, %60, %61, %62, %63}, "
        "{%64, %65, %66, %67}, %68, p, 1, 1, 1;\n}\n"
        : "+f"(d[0]), "+f"(d[1]), "+f"(d[2]), "+f"(d[3]), "+f"(d[4]), "+f"(d[5]), "+f"(d[6]), "+f"(d[7]), "+f"(d[8]), "+f"(d[9]), "+f"(d[10]), "+f"(d[11]), "+f"(d[12]), "+f"(d[13]), "+f"(d[14]), "+f"(d[15]), "+f"(d[16]), "+f"(d[17]), "+f"(d[18]), "+f"(d[19]), "+f"(d[20]), "+f"(d[21]), "+f"(d[22]), "+f"(d[23]), "+f"(d[24]), "+f"(d[25]), "+f"(d[26]), "+f"(d[27]), "+f"(d[28]), "+f"(d[29]), "+f"(d[30]), "+f"(d[31]), "+f"(d[32]), "+f"(d[33]), "+f"(d[34]), "+f"(d[35]), "+f"(d[36]), "+f"(d[37]), "+f"(d[38]), "+f"(d[39]), "+f"(d[40]), "+f"(d[41]), "+f"(d[42]), "+f"(d[43]), "+f"(d[44]), "+f"(d[45]), "+f"(d[46]), "+f"(d[47]), "+f"(d[48]), "+f"(d[49]), "+f"(d[50]), "+f"(d[51]), "+f"(d[52]), "+f"(d[53]), "+f"(d[54]), "+f"(d[55]), "+f"(d[56]), "+f"(d[57]), "+f"(d[58]), "+f"(d[59]), "+f"(d[60]), "+f"(d[61]), "+f"(d[62]), "+f"(d[63])
        : "r"(a0), "r"(a1), "r"(a2), "r"(a3), "l"(db), "r"(sd));
}
__device__ __forceinline__ void wgmma_rs_n64_tb(float (&d)[32], uint32_t a0, uint32_t a1, uint32_t a2, uint32_t a3, uint64_t db, int sd) {
    asm volatile("{\n.reg .pred p;\nsetp.ne.b32 p, %37, 0;\n"
        "wgmma.mma_async.sync.aligned.m64n64k16.f32.bf16.bf16 "
        "{%0, %1, %2, %3, %4, %5, %6, %7, %8, %9, %10, %11, %12, %13, %14, %15, %16, %17, %18, %19, %20, %21, %22, %23, %24, %25, %26, %27, %28, %29, %30, %31}, "
        "{%32, %33, %34, %35}, %36, p, 1, 1, 1;\n}\n"
        : "+f"(d[0]), "+f"(d[1]), "+f"(d[2]), "+f"(d[3]), "+f"(d[4]), "+f"(d[5]), "+f"(d[6]), "+f"(d[7]), "+f"(d[8]), "+f"(d[9]), "+f"(d[10]), "+f"(d[11]), "+f"(d[12]), "+f"(d[13]), "+f"(d[14]), "+f"(d[15]), "+f"(d[16]), "+f"(d[17]), "+f"(d[18]), "+f"(d[19]), "+f"(d[20]), "+f"(d[21]), "+f"(d[22]), "+f"(d[23]), "+f"(d[24]), "+f"(d[25]), "+f"(d[26]), "+f"(d[27]), "+f"(d[28]), "+f"(d[29]), "+f"(d[30]), "+f"(d[31])
        : "r"(a0), "r"(a1), "r"(a2), "r"(a3), "l"(db), "r"(sd));
}

__global__ void __launch_bounds__(384, 1) fused_gqa_kernel(const __grid_constant__ Params P) {
    extern __shared__ uint8_t smem_raw[];
    const uint32_t base = (smem_u32(smem_raw) + 1023u) & ~1023u;
    const uint32_t smR = base;
    const uint32_t smS = base + R_BYTES;
    const uint32_t bars = smS + NSTAGE * STAGE_BYTES;
    const uint32_t prog = bars + 8 * (2 * NSTAGE + 10);
    const int tid = threadIdx.x;
    const int wid = __shfl_sync(0xffffffffu, tid >> 5, 0);
    const int lane = tid & 31;

    const int cta = blockIdx.x;
    const int blk = cta >> 6;
    const int hp = (cta >> 3) & 7;
    const int b = cta & 7;
    const int grp = blk * 8 + b;

    if (tid == 0) {
        TS(0);
        for (int i = 0; i < NSTAGE; i++) {
            mbar_init(bars + 8 * i, 1);
            mbar_init(bars + 8 * (NSTAGE + i), 8);
        }
        for (int i = 0; i < 10; i++) mbar_init(bars + 8 * (2 * NSTAGE + i), 4);
        asm volatile("st.volatile.shared.u32 [%0], %1;" ::"r"(prog), "r"(0) : "memory");
        asm volatile("fence.mbarrier_init.release.cluster;" ::: "memory");
        asm volatile("fence.proxy.async.shared::cta;" ::: "memory");
    }
    __syncthreads();

    if (wid >= 8) {
        asm volatile("setmaxnreg.dec.sync.aligned.u32 40;");
        if (wid == 8) {
            if (lane == 0) {
                int slot = 0, ph = 1;
                for (int s = 0; s < N_WQ; s++) {
                    const uint32_t fb = bars + 8 * slot;
                    mbar_wait(bars + 8 * (NSTAGE + slot), ph);
                    const uint32_t dst = smS + slot * STAGE_BYTES;
                    mbar_expect_tx(fb, (s & 1) ? STAGE_BYTES : STAGE_BYTES + 8192);
                    if (!(s & 1)) tma_2d(smR + ((s >> 1) & 7) * 8192, &P.x[blk], (s >> 1) * 64, b * 64, fb);
#pragma unroll
                    for (int p = 0; p < 8; p++) {
                        const int w = p >> 2, j = (p >> 1) & 1, glo = p & 1;
                        tma_2d(dst + p * 4096, &P.wq[blk], hp * 512 + (j * 4 + w * 2 + glo) * 64, s * 32, fb);
                    }
                    if (++slot == NSTAGE) { slot = 0; ph ^= 1; }
                }
                for (int i = 0; i < 34; i++) {
                    const uint32_t fb = bars + 8 * slot;
                    mbar_wait(bars + 8 * (NSTAGE + slot), ph);
                    const uint32_t dst = smS + slot * STAGE_BYTES;
                    mbar_expect_tx(fb, STAGE_BYTES);
                    if (i < 16) {
                        const int row = (b * kHkv + hp * 2) * kSk + (i >> 1) * 128;
                        const CUtensorMap* tm = (i & 1) ? &P.v[blk] : &P.k[blk];
                        tma_2d(dst, tm, 0, row, fb);
                        tma_2d(dst + 16384, tm, 64, row, fb);
                    } else {
                        const int q = i - 16;
                        if (q < 16) {
                            const int c0 = (q >> 3) * 256, r0 = hp * 512 + (q & 7) * 64, r1 = hp * 512 + ((q + 4) & 7) * 64;
                            tma_2d(dst, &P.wo[blk], c0, r0, fb);
                            tma_2d(dst + 8192, &P.wo[blk], c0 + 64, r0, fb);
                            tma_2d(dst + 16384, &P.wo[blk], c0 + 128, r1, fb);
                            tma_2d(dst + 24576, &P.wo[blk], c0 + 192, r1, fb);
                        } else {
                            const int r0 = hp * 512 + (q - 16) * 128;
                            tma_2d(dst, &P.wo[blk], 512, r0, fb);
                            tma_2d(dst + 8192, &P.wo[blk], 512, r0 + 64, fb);
                            tma_2d(dst + 16384, &P.wo[blk], 512, r0 + 256, fb);
                            tma_2d(dst + 24576, &P.wo[blk], 512, r0 + 320, fb);
                        }
                    }
                    asm volatile("st.volatile.shared.u32 [%0], %1;" ::"r"(prog), "r"(i + 1) : "memory");
                    if (++slot == NSTAGE) { slot = 0; ph ^= 1; }
                }
            }
        } else if (wid == 11) {
            if (PF_DIST > 0) {
                uint32_t sink = 0;
                mbar_wait(bars, 0);
                if (PF_WQ) {
                    const char* wqs = (const char*)(P.wqp[blk] + hp * 512) + (size_t)(160 + b * 52) * 8192;
#pragma unroll
                    for (int h = 0; h < 2; h++) {
#pragma unroll
                        for (int j = 0; j < 4; j++) {
                            const int e = (h * 4 + j) * 32 + lane;
                            if (e < 208) sink |= l2_touch(wqs + (size_t)(e >> 2) * 8192 + (e & 3) * 256);
                        }
                        if (sink == 0x9E3779B9u) asm volatile("st.volatile.shared.u32 [%0], %1;" ::"r"(prog + 4), "r"(sink) : "memory");
                    }
                }
                const char* kbase = (const char*)(P.kp[blk] + (size_t)(b * kHkv + hp * 2) * kSk * kDh);
                const char* vbase = (const char*)(P.vp[blk] + (size_t)(b * kHkv + hp * 2) * kSk * kDh);
                const char* wos = (const char*)(P.wop[blk] + (size_t)hp * 512 * kD) + (size_t)b * 73728;
                for (int i = 0; i < 19; i++) {
                    if (i >= PF_DIST) {
                        uint32_t pr, n = 0;
                        while (true) {
                            asm volatile("ld.volatile.shared.u32 %0, [%1];" : "=r"(pr) : "r"(prog) : "memory");
                            if ((int)pr + PF_DIST >= i) break;
                            if (++n > (1u << 22)) break;
                            __nanosleep(100);
                        }
                    }
                    if (i < 16) {
                        const char* p = ((i & 1) ? vbase : kbase) + (size_t)(i >> 1) * 32768 + lane * 256;
#pragma unroll
                        for (int j = 0; j < 4; j++) sink |= l2_touch(p + j * 8192);
                    } else {
                        const char* p = wos + (size_t)(i - 16) * 24576 + lane * 256;
#pragma unroll
                        for (int j = 0; j < 3; j++) sink |= l2_touch(p + j * 8192);
                    }
                    if (sink == 0x9E3779B9u) asm volatile("st.volatile.shared.u32 [%0], %1;" ::"r"(prog + 4), "r"(sink) : "memory");
                }
            }
        } else {
            const int hw = wid - 9;
            for (int k = 0; k < 3; k++) {
                mbar_wait(bars + 8 * (2 * NSTAGE + hw * 5 + k), 0);
                const int c = (k < 2) ? (2 * k + hw) : 4;
                asm volatile("fence.acq_rel.gpu;" ::: "memory");
                asm volatile("red.relaxed.gpu.global.add.u32 [%0], 1;" ::"l"(&g_cnt[(grp * 9 + c) * 32 + lane]) : "memory");
            }
        }
    } else {
        asm volatile("setmaxnreg.inc.sync.aligned.u32 232;");
        const int w = wid >> 2;
        const int t = tid & 127;
        int slot = 0, ph = 0;
        uint32_t qf[8][4];
        const uint32_t stash = smR + (1 + w) * 16384 + t * 16;
        {
            float acc[128];
            int pslot = 0;
            for (int s = 0; s < N_WQ; s++) {
                mbar_wait(bars + 8 * slot, ph);
                if (tid == 0 && s == 0) TS(20);
                if (tid == 0 && s == 5) TS(21);
                if (tid == 0 && s == 10) TS(22);
                const uint64_t da = mk_desc(smR + ((s >> 1) & 7) * 8192 + (s & 1) * 64, 16, 1024);
                const uint64_t db = mk_desc(smS + slot * STAGE_BYTES + w * 16384, 4096, 1024);
                wg_fence();
                wgmma_ss_n256_tb(acc, da, db, s != 0);
                wgmma_ss_n256_tb(acc, da + 2, db + 128, 1);
                wg_commit();
                if (s > 0) {
                    wg_wait<1>();
                    if (lane == 0) mbar_arrive(bars + 8 * (NSTAGE + pslot));
                }
                pslot = slot;
                if (++slot == NSTAGE) { slot = 0; ph ^= 1; }
            }
            wg_wait<0>();
            if (lane == 0) mbar_arrive(bars + 8 * (NSTAGE + pslot));
            fence_regs(acc);
            if (tid == 0) TS(1);
#pragma unroll
            for (int kk = 0; kk < 8; kk++) {
#pragma unroll
                for (int i = 0; i < 4; i++) qf[kk][i] = pack_bf16(acc[8 * kk + 2 * i], acc[8 * kk + 2 * i + 1]);
                sts128(stash + kk * 2048,
                       pack_bf16(acc[64 + 8 * kk + 0], acc[64 + 8 * kk + 1]), pack_bf16(acc[64 + 8 * kk + 2], acc[64 + 8 * kk + 3]),
                       pack_bf16(acc[64 + 8 * kk + 4], acc[64 + 8 * kk + 5]), pack_bf16(acc[64 + 8 * kk + 6], acc[64 + 8 * kk + 7]));
            }
        }
        if (w == 1) bar_arrive<5, 256>();
        const float sc = 0.08838834764831845f * 1.4426950408889634f;
#pragma unroll 1
        for (int u = 0; u < 2; u++) {
            {
                if (u == 1) {
#pragma unroll
                    for (int kk = 0; kk < 8; kk++) lds128(stash + kk * 2048, qf[kk]);
                }
                float o[64], s[64];
                float m0 = -INFINITY, m1 = -INFINITY, l0 = 0.f, l1 = 0.f;
                uint32_t pf[8][4];
#pragma unroll
                for (int i = 0; i < 64; i++) { o[i] = 0.f; s[i] = 0.f; }
#pragma unroll
                for (int i = 0; i < 32; i++) pf[i >> 2][i & 3] = 0u;
#pragma unroll 1
                for (int tt = 0; tt <= 4; tt++) {
                    int vslot = slot;
                    if (tt > 0) {
                        mbar_wait(bars + 8 * slot, ph);
                        if (++slot == NSTAGE) { slot = 0; ph ^= 1; }
                    }
                    if (tt < 4) mbar_wait(bars + 8 * slot, ph);
                    if (tid == 0) TS(32 + u * 20 + tt * 4);
                    if (w == 0) bar_sync<5, 256>(); else bar_sync<6, 256>();
                    wg_fence();
                    if (tt > 0) {
                        const uint64_t db = mk_desc(smS + vslot * STAGE_BYTES, 16384, 1024);
#pragma unroll
                        for (int kk = 0; kk < 8; kk++)
                            wgmma_rs_n128_tb(o, pf[kk][0], pf[kk][1], pf[kk][2], pf[kk][3], db + kk * 128, (tt > 1) || (kk != 0));
                        wg_commit();
                    }
                    if (tt < 4) {
                        const uint64_t db = mk_desc(smS + slot * STAGE_BYTES, 16, 1024);
#pragma unroll
                        for (int kk = 0; kk < 8; kk++)
                            wgmma_rs_n128(s, qf[kk][0], qf[kk][1], qf[kk][2], qf[kk][3], db + (kk >> 2) * 1024 + (kk & 3) * 2, kk != 0);
                        wg_commit();
                    }
                    if (w == 0) bar_arrive<6, 256>(); else if (!(u == 1 && tt == 4)) bar_arrive<5, 256>();
                    if (tid == 0) TS(32 + u * 20 + tt * 4 + 1);
                    wg_wait<0>();
                    fence_regs(o);
                    fence_regs(s);
                    if (tid == 0) TS(32 + u * 20 + tt * 4 + 2);
                    if (tt > 0 && lane == 0) mbar_arrive(bars + 8 * (NSTAGE + vslot));
                    if (tt == 4) break;
                    if (lane == 0) mbar_arrive(bars + 8 * (NSTAGE + slot));
                    if (++slot == NSTAGE) { slot = 0; ph ^= 1; }
                    float mx0 = s[0], mx1 = s[2];
#pragma unroll
                    for (int j = 0; j < 16; j++) {
                        mx0 = fmaxf(mx0, fmaxf(s[4 * j], s[4 * j + 1]));
                        mx1 = fmaxf(mx1, fmaxf(s[4 * j + 2], s[4 * j + 3]));
                    }
                    mx0 = fmaxf(mx0, __shfl_xor_sync(0xffffffffu, mx0, 1));
                    mx1 = fmaxf(mx1, __shfl_xor_sync(0xffffffffu, mx1, 1));
                    mx0 = fmaxf(mx0, __shfl_xor_sync(0xffffffffu, mx0, 2));
                    mx1 = fmaxf(mx1, __shfl_xor_sync(0xffffffffu, mx1, 2));
                    const float mn0 = fmaxf(m0, mx0), mn1 = fmaxf(m1, mx1);
                    const float al0 = ex2((m0 - mn0) * sc), al1 = ex2((m1 - mn1) * sc);
                    m0 = mn0; m1 = mn1;
                    const float ms0 = mn0 * sc, ms1 = mn1 * sc;
                    float rs0 = 0.f, rs1 = 0.f;
#pragma unroll
                    for (int j = 0; j < 16; j++) {
                        const float p0 = ex2(fmaf(s[4 * j], sc, -ms0)), p1 = ex2(fmaf(s[4 * j + 1], sc, -ms0));
                        const float p2 = ex2(fmaf(s[4 * j + 2], sc, -ms1)), p3 = ex2(fmaf(s[4 * j + 3], sc, -ms1));
                        rs0 += p0 + p1; rs1 += p2 + p3;
                        pf[j >> 1][(j & 1) * 2] = pack_bf16(p0, p1);
                        pf[j >> 1][(j & 1) * 2 + 1] = pack_bf16(p2, p3);
                    }
                    l0 = l0 * al0 + rs0; l1 = l1 * al1 + rs1;
                    if (tt > 0) {
#pragma unroll
                        for (int j = 0; j < 16; j++) { o[4 * j] *= al0; o[4 * j + 1] *= al0; o[4 * j + 2] *= al1; o[4 * j + 3] *= al1; }
                    }
                    if (tid == 0) TS(32 + u * 20 + tt * 4 + 3);
                }
                if (tid == 0) TS(2 + u);
                l0 += __shfl_xor_sync(0xffffffffu, l0, 1);
                l1 += __shfl_xor_sync(0xffffffffu, l1, 1);
                l0 += __shfl_xor_sync(0xffffffffu, l0, 2);
                l1 += __shfl_xor_sync(0xffffffffu, l1, 2);
                const float i0 = 1.f / l0, i1 = 1.f / l1;
                const uint32_t zown = smR + ((u == 0) ? (w ? 3 : 0) : (w ? 2 : 1)) * 16384 + t * 16;
#pragma unroll
                for (int kk = 0; kk < 8; kk++)
                    sts128(zown + kk * 2048,
                           pack_bf16(o[8 * kk + 0] * i0, o[8 * kk + 1] * i0), pack_bf16(o[8 * kk + 2] * i1, o[8 * kk + 3] * i1),
                           pack_bf16(o[8 * kk + 4] * i0, o[8 * kk + 5] * i0), pack_bf16(o[8 * kk + 6] * i1, o[8 * kk + 7] * i1));
            }
        }
        bar_sync<4, 256>();
        {
            uint32_t af[32][4];
#pragma unroll
            for (int hh = 0; hh < 4; hh++) {
                const int h2 = (hh + 2 * w) & 3;
                const int z = (0x2130 >> (h2 * 4)) & 3;
#pragma unroll
                for (int kk = 0; kk < 8; kk++) lds128(smR + z * 16384 + kk * 2048 + t * 16, af[hh * 8 + kk]);
            }
            uint2* dst0 = g_part + (size_t)(grp * 80 + 2 * w * 8 + hp) * 1024 + t;
            uint2* dst8 = g_part + (size_t)(grp * 80 + 64 + hp * 2 + w) * 1024 + t;
#pragma unroll
            for (int ps = 0; ps < 2; ps++) {
                float acc[64];
#pragma unroll
                for (int i = 0; i < 64; i++) acc[i] = 0.f;
                int pslot = 0;
#pragma unroll
                for (int st = 0; st < 8; st++) {
                    mbar_wait(bars + 8 * slot, ph);
                    const uint64_t db = mk_desc(smS + slot * STAGE_BYTES + w * 16384, 8192, 1024);
                    wg_fence();
#pragma unroll
                    for (int kk = 0; kk < 4; kk++)
                        wgmma_rs_n128_tb(acc, af[st * 4 + kk][0], af[st * 4 + kk][1], af[st * 4 + kk][2], af[st * 4 + kk][3], db + kk * 128, (st | kk) != 0);
                    wg_commit();
                    if (st > 0) {
                        wg_wait<1>();
                        if (lane == 0) mbar_arrive(bars + 8 * (NSTAGE + pslot));
                    }
                    pslot = slot;
                    if (++slot == NSTAGE) { slot = 0; ph ^= 1; }
                }
                wg_wait<0>();
                if (lane == 0) mbar_arrive(bars + 8 * (NSTAGE + pslot));
                fence_regs(acc);
                uint2* dst = dst0 + (size_t)ps * 32 * 1024;
#pragma unroll
                for (int j = 0; j < 16; j++)
                    __stcg(dst + (j >> 3) * 8192 + (j & 7) * 128, make_uint2(pack_bf16(acc[4 * j], acc[4 * j + 1]), pack_bf16(acc[4 * j + 2], acc[4 * j + 3])));
                __syncwarp();
                if (lane == 0) mbar_arrive(bars + 8 * (2 * NSTAGE + w * 5 + ps));
                if (tid == 0) TS(4 + ps);
            }
            {
                float acc[32];
#pragma unroll
                for (int i = 0; i < 32; i++) acc[i] = 0.f;
                int pslot = slot;
#pragma unroll
                for (int st = 0; st < 2; st++) {
                    mbar_wait(bars + 8 * slot, ph);
                    const uint64_t db = mk_desc(smS + slot * STAGE_BYTES + w * 16384, 8192, 1024);
                    wg_fence();
#pragma unroll
                    for (int kk = 0; kk < 8; kk++)
                        wgmma_rs_n64_tb(acc, af[st * 8 + kk][0], af[st * 8 + kk][1], af[st * 8 + kk][2], af[st * 8 + kk][3], db + kk * 128, (st | kk) != 0);
                    wg_commit();
                    if (++slot == NSTAGE) { slot = 0; ph ^= 1; }
                }
                wg_wait<0>();
                (void)pslot;
                fence_regs(acc);
#pragma unroll
                for (int j = 0; j < 8; j++)
                    __stcg(dst8 + j * 128, make_uint2(pack_bf16(acc[4 * j], acc[4 * j + 1]), pack_bf16(acc[4 * j + 2], acc[4 * j + 3])));
                __syncwarp();
                if (lane == 0) mbar_arrive(bars + 8 * (2 * NSTAGE + w * 5 + 2));
                if (tid == 0) TS(8);
            }
        }
        {
            const int nch = (w == 0) ? 3 : 2;
            if (lane < nch) {
                const int c = (lane < 2) ? (2 * lane + w) : 4;
                const unsigned need = (lane < 2) ? 8u : 16u;
                unsigned* cp = &g_cnt[(grp * 9 + c) * 32 + hp * 4 + (wid & 3)];
                unsigned v, n = 0;
                while (true) {
                    asm volatile("ld.acquire.gpu.global.u32 %0, [%1];" : "=r"(v) : "l"(cp) : "memory");
                    if (v >= need) break;
                    if (++n > (1u << 21)) break;
                }
                *cp = 0;
            }
            __syncwarp();
            if (tid == 0) TS(18);
            __nv_bfloat16* orow = P.out + (size_t)(b * 64 + (t >> 5) * 16 + (lane >> 2)) * (2 * kD) + blk * kD + hp * 8 + (lane & 3) * 2;
            const uint2* src = g_part + ((size_t)(grp * 80 + 2 * w * 8) * 8 + hp) * 128 + t;
            uint2 v[4][8];
#pragma unroll
            for (int k = 0; k < 4; k++)
#pragma unroll
                for (int i = 0; i < 8; i++) v[k][i] = __ldcg(src + (size_t)((k >> 1) * 32 + (k & 1) * 8 + i) * 1024);
            if (w == 0) {
                const uint2* src8 = g_part + ((size_t)(grp * 80 + 64) * 8 + hp) * 128 + t;
                uint2 u[16];
#pragma unroll
                for (int i = 0; i < 16; i++) u[i] = __ldcg(src8 + (size_t)i * 1024);
                float a0 = 0.f, a1 = 0.f, a2 = 0.f, a3 = 0.f;
#pragma unroll
                for (int i = 0; i < 16; i++) {
                    a0 += __uint_as_float(u[i].x << 16); a1 += __uint_as_float(u[i].x & 0xffff0000u);
                    a2 += __uint_as_float(u[i].y << 16); a3 += __uint_as_float(u[i].y & 0xffff0000u);
                }
                *(uint32_t*)(orow + 512) = pack_bf16(a0, a1);
                *(uint32_t*)(orow + 512 + 8 * 2 * kD) = pack_bf16(a2, a3);
            }
#pragma unroll
            for (int k = 0; k < 4; k++) {
                float a0 = 0.f, a1 = 0.f, a2 = 0.f, a3 = 0.f;
#pragma unroll
                for (int i = 0; i < 8; i++) {
                    a0 += __uint_as_float(v[k][i].x << 16); a1 += __uint_as_float(v[k][i].x & 0xffff0000u);
                    a2 += __uint_as_float(v[k][i].y << 16); a3 += __uint_as_float(v[k][i].y & 0xffff0000u);
                }
                *(uint32_t*)(orow + ((k >> 1) * 4 + 2 * w + (k & 1)) * 64) = pack_bf16(a0, a1);
                *(uint32_t*)(orow + ((k >> 1) * 4 + 2 * w + (k & 1)) * 64 + 8 * 2 * kD) = pack_bf16(a2, a3);
            }
            if (tid == 0) TS(19);
        }
    }
}

typedef CUresult (*EncodeFn)(CUtensorMap*, CUtensorMapDataType, cuuint32_t, void*, const cuuint64_t*, const cuuint64_t*,
                             const cuuint32_t*, const cuuint32_t*, CUtensorMapInterleave, CUtensorMapSwizzle,
                             CUtensorMapL2promotion, CUtensorMapFloatOOBfill);

void make_map(EncodeFn fn, CUtensorMap* m, const void* ptr, uint64_t cols, uint64_t rows, uint32_t box_rows) {
    cuuint64_t dims[2] = {cols, rows};
    cuuint64_t strides[1] = {cols * 2};
    cuuint32_t box[2] = {64, box_rows};
    cuuint32_t es[2] = {1, 1};
    fn(m, CU_TENSOR_MAP_DATA_TYPE_BFLOAT16, 2, const_cast<void*>(ptr), dims, strides, box, es, CU_TENSOR_MAP_INTERLEAVE_NONE,
       CU_TENSOR_MAP_SWIZZLE_128B, CU_TENSOR_MAP_L2_PROMOTION_L2_256B, CU_TENSOR_MAP_FLOAT_OOB_FILL_NONE);
}

}

extern "C" void kernel_launch(void* const* d_in, const int* in_sizes, int n_in, void* d_out, int out_size) {
    static EncodeFn enc = nullptr;
    if (!enc) {
        void* fn = nullptr;
        cudaDriverEntryPointQueryResult st;
        cudaGetDriverEntryPoint("cuTensorMapEncodeTiled", &fn, cudaEnableDefault, &st);
        enc = (EncodeFn)fn;
        cudaFuncSetAttribute(fused_gqa_kernel, cudaFuncAttributeMaxDynamicSharedMemorySize, SMEM_BYTES);
    }
    Params P;
    for (int blk = 0; blk < 2; blk++) {
        const void* x = d_in[blk * 5 + 0];
        const void* k = d_in[blk * 5 + 1];
        const void* v = d_in[blk * 5 + 2];
        const void* wq = d_in[blk * 5 + 3];
        const void* wo = d_in[blk * 5 + 4];
        make_map(enc, &P.x[blk], x, kD, kB * kSq, 64);
        make_map(enc, &P.wq[blk], wq, kHq * kDh, kD, 32);
        make_map(enc, &P.k[blk], k, kDh, (uint64_t)kB * kHkv * kSk, 128);
        make_map(enc, &P.v[blk], v, kDh, (uint64_t)kB * kHkv * kSk, 128);
        make_map(enc, &P.wo[blk], wo, kD, kHq * kDh, 64);
        P.wqp[blk] = (const __nv_bfloat16*)wq;
        P.kp[blk] = (const __nv_bfloat16*)k;
        P.vp[blk] = (const __nv_bfloat16*)v;
        P.wop[blk] = (const __nv_bfloat16*)wo;
    }
    P.out = (__nv_bfloat16*)d_out;
    fused_gqa_kernel<<<128, 384, SMEM_BYTES>>>(P);
}
```

```cpp
#include <cuda_runtime.h>
#include <cuda_bf16.h>
#include <cuda.h>
#include <stdint.h>

namespace {

constexpr int kB = 8, kSq = 64, kD = 576, kHq = 32, kHkv = 16, kSk = 512, kDh = 128;
constexpr int NSTAGE = 5;
constexpr int STAGE_BYTES = 32768;
constexpr int R_BYTES = 65536;
constexpr int SMEM_BYTES = R_BYTES + NSTAGE * STAGE_BYTES + 1024   + 256  ;
constexpr int N_WQ = 18;
#define PF_DIST_V 4
#define PF_WQ 0
#define PF_SLEEP 1000
constexpr int PF_DIST = PF_DIST_V;

struct __align__(64) Params {
    CUtensorMap x[2], wq[2], k[2], v[2], wo[2], wo8[2];
    const __nv_bfloat16* wqp[2];
    const __nv_bfloat16* kp[2];
    const __nv_bfloat16* vp[2];
    const __nv_bfloat16* wop[2];
    __nv_bfloat16* out;
};

__device__ uint2 g_part[16 * 80 * 8 * 128];
__device__ unsigned int g_cnt[16 * 9 * 32];
#define TS(k) do {} while (0)

__device__ __forceinline__ uint32_t smem_u32(const void* p) { return (uint32_t)__cvta_generic_to_shared(p); }
__device__ __forceinline__ void mbar_init(uint32_t bar, int cnt) {
    asm volatile("mbarrier.init.shared::cta.b64 [%0], %1;" ::"r"(bar), "r"(cnt));
}
__device__ __forceinline__ void mbar_expect_tx(uint32_t bar, uint32_t bytes) {
    asm volatile("mbarrier.arrive.expect_tx.shared::cta.b64 _, [%0], %1;" ::"r"(bar), "r"(bytes) : "memory");
}
__device__ __forceinline__ void mbar_arrive(uint32_t bar) {
    asm volatile("mbarrier.arrive.shared::cta.b64 _, [%0];" ::"r"(bar) : "memory");
}
__device__ __forceinline__ bool mbar_try(uint32_t bar, uint32_t parity) {
    uint32_t ok;
    asm volatile("{\n.reg .pred p;\nmbarrier.try_wait.parity.shared::cta.b64 p, [%1], %2;\nselp.u32 %0, 1, 0, p;\n}\n"
                 : "=r"(ok) : "r"(bar), "r"(parity) : "memory");
    return ok != 0;
}
__device__ __forceinline__ void mbar_wait(uint32_t bar, uint32_t parity) {
    if (mbar_try(bar, parity)) return;
    uint32_t n = 0;
    while (!mbar_try(bar, parity)) {
        if (++n > (1u << 20)) break;
    }
}
__device__ __forceinline__ void tma_2d(uint32_t dst, const CUtensorMap* tm, int c0, int c1, uint32_t bar) {
    asm volatile("cp.async.bulk.tensor.2d.shared::cluster.global.mbarrier::complete_tx::bytes [%0], [%1, {%3, %4}], [%2];"
                 ::"r"(dst), "l"(tm), "r"(bar), "r"(c0), "r"(c1) : "memory");
}
__device__ __forceinline__ void tma_3d(uint32_t dst, const CUtensorMap* tm, int c0, int c1, int c2, uint32_t bar) {
    asm volatile("cp.async.bulk.tensor.3d.shared::cluster.global.mbarrier::complete_tx::bytes [%0], [%1, {%3, %4, %5}], [%2];"
                 ::"r"(dst), "l"(tm), "r"(bar), "r"(c0), "r"(c1), "r"(c2) : "memory");
}
__device__ __forceinline__ void l2_prefetch(const void* p, uint32_t bytes) {
    asm volatile("cp.async.bulk.prefetch.L2.global [%0], %1;" ::"l"(p), "r"(bytes) : "memory");
}
__device__ __forceinline__ uint32_t l2_touch(const void* p) {
    uint32_t v;
    asm volatile("ld.global.L2::256B.b32 %0, [%1];" : "=r"(v) : "l"(p) : "memory");
    return v;
}
__device__ __forceinline__ void wg_fence() { asm volatile("wgmma.fence.sync.aligned;" ::: "memory"); }
__device__ __forceinline__ void wg_commit() { asm volatile("wgmma.commit_group.sync.aligned;" ::: "memory"); }
template <int N> __device__ __forceinline__ void wg_wait() { asm volatile("wgmma.wait_group.sync.aligned %0;" ::"n"(N) : "memory"); }
template <int N> __device__ __forceinline__ void fence_regs(float (&d)[N]) {
#pragma unroll
    for (int i = 0; i < N; i++) asm volatile("" : "+f"(d[i])::"memory");
}
__device__ __forceinline__ uint64_t mk_desc(uint32_t addr, uint32_t lbo, uint32_t sbo) {
    return (uint64_t)((addr & 0x3FFFF) >> 4) | ((uint64_t)(lbo >> 4) << 16) | ((uint64_t)(sbo >> 4) << 32) | (1ull << 62);
}
__device__ __forceinline__ uint32_t pack_bf16(float a, float b) {
    uint32_t r;
    asm("cvt.rn.bf16x2.f32 %0, %1, %2;" : "=r"(r) : "f"(b), "f"(a));
    return r;
}
__device__ __forceinline__ float ex2(float x) {
    float y;
    asm("ex2.approx.ftz.f32 %0, %1;" : "=f"(y) : "f"(x));
    return y;
}
template <int ID, int N> __device__ __forceinline__ void bar_sync() { asm volatile("bar.sync %0, %1;" ::"n"(ID), "n"(N) : "memory"); }
template <int ID, int N> __device__ __forceinline__ void bar_arrive() { asm volatile("bar.arrive %0, %1;" ::"n"(ID), "n"(N) : "memory"); }
__device__ __forceinline__ void sts128(uint32_t addr, uint32_t a, uint32_t b, uint32_t c, uint32_t d) {
    asm volatile("st.shared.v4.b32 [%0], {%1,%2,%3,%4};" ::"r"(addr), "r"(a), "r"(b), "r"(c), "r"(d) : "memory");
}
__device__ __forceinline__ void lds128(uint32_t addr, uint32_t (&r)[4]) {
    asm volatile("ld.shared.v4.b32 {%0,%1,%2,%3}, [%4];" : "=r"(r[0]), "=r"(r[1]), "=r"(r[2]), "=r"(r[3]) : "r"(addr) : "memory");
}

__device__ __forceinline__ void wgmma_ss_n256_tb(float (&d)[128], uint64_t da, uint64_t db, int sd) {
    asm volatile("{\n.reg .pred p;\nsetp.ne.b32 p, %130, 0;\n"
        "wgmma.mma_async.sync.aligned.m64n256k16.f32.bf16.bf16 "
        "{%0, %1, %2, %3, %4, %5, %6, %7, %8, %9, %10, %11, %12, %13, %14, %15, %16, %17, %18, %19, %20, %21, %22, %23, %24, %25, %26, %27, %28, %29, %30, %31, %32, %33, %34, %35, %36, %37, %38, %39, %40, %41, %42, %43, %44, %45, %46, %47, %48, %49, %50, %51, %52, %53, %54, %55, %56, %57, %58, %59, %60, %61, %62, %63, %64, %65, %66, %67, %68, %69, %70, %71, %72, %73, %74, %75, %76, %77, %78, %79, %80, %81, %82, %83, %84, %85, %86, %87, %88, %89, %90, %91, %92, %93, %94, %95, %96, %97, %98, %99, %100, %101, %102, %103, %104, %105, %106, %107, %108, %109, %110, %111, %112, %113, %114, %115, %116, %117, %118, %119, %120, %121, %122, %123, %124, %125, %126, %127}, "
        "%128, %129, p, 1, 1, 0, 1;\n}\n"
        : "+f"(d[0]), "+f"(d[1]), "+f"(d[2]), "+f"(d[3]), "+f"(d[4]), "+f"(d[5]), "+f"(d[6]), "+f"(d[7]), "+f"(d[8]), "+f"(d[9]), "+f"(d[10]), "+f"(d[11]), "+f"(d[12]), "+f"(d[13]), "+f"(d[14]), "+f"(d[15]), "+f"(d[16]), "+f"(d[17]), "+f"(d[18]), "+f"(d[19]), "+f"(d[20]), "+f"(d[21]), "+f"(d[22]), "+f"(d[23]), "+f"(d[24]), "+f"(d[25]), "+f"(d[26]), "+f"(d[27]), "+f"(d[28]), "+f"(d[29]), "+f"(d[30]), "+f"(d[31]), "+f"(d[32]), "+f"(d[33]), "+f"(d[34]), "+f"(d[35]), "+f"(d[36]), "+f"(d[37]), "+f"(d[38]), "+f"(d[39]), "+f"(d[40]), "+f"(d[41]), "+f"(d[42]), "+f"(d[43]), "+f"(d[44]), "+f"(d[45]), "+f"(d[46]), "+f"(d[47]), "+f"(d[48]), "+f"(d[49]), "+f"(d[50]), "+f"(d[51]), "+f"(d[52]), "+f"(d[53]), "+f"(d[54]), "+f"(d[55]), "+f"(d[56]), "+f"(d[57]), "+f"(d[58]), "+f"(d[59]), "+f"(d[60]), "+f"(d[61]), "+f"(d[62]), "+f"(d[63]), "+f"(d[64]), "+f"(d[65]), "+f"(d[66]), "+f"(d[67]), "+f"(d[68]), "+f"(d[69]), "+f"(d[70]), "+f"(d[71]), "+f"(d[72]), "+f"(d[73]), "+f"(d[74]), "+f"(d[75]), "+f"(d[76]), "+f"(d[77]), "+f"(d[78]), "+f"(d[79]), "+f"(d[80]), "+f"(d[81]), "+f"(d[82]), "+f"(d[83]), "+f"(d[84]), "+f"(d[85]), "+f"(d[86]), "+f"(d[87]), "+f"(d[88]), "+f"(d[89]), "+f"(d[90]), "+f"(d[91]), "+f"(d[92]), "+f"(d[93]), "+f"(d[94]), "+f"(d[95]), "+f"(d[96]), "+f"(d[97]), "+f"(d[98]), "+f"(d[99]), "+f"(d[100]), "+f"(d[101]), "+f"(d[102]), "+f"(d[103]), "+f"(d[104]), "+f"(d[105]), "+f"(d[106]), "+f"(d[107]), "+f"(d[108]), "+f"(d[109]), "+f"(d[110]), "+f"(d[111]), "+f"(d[112]), "+f"(d[113]), "+f"(d[114]), "+f"(d[115]), "+f"(d[116]), "+f"(d[117]), "+f"(d[118]), "+f"(d[119]), "+f"(d[120]), "+f"(d[121]), "+f"(d[122]), "+f"(d[123]), "+f"(d[124]), "+f"(d[125]), "+f"(d[126]), "+f"(d[127])
        : "l"(da), "l"(db), "r"(sd));
}
__device__ __forceinline__ void wgmma_rs_n128(float (&d)[64], uint32_t a0, uint32_t a1, uint32_t a2, uint32_t a3, uint64_t db, int sd) {
    asm volatile("{\n.reg .pred p;\nsetp.ne.b32 p, %69, 0;\n"
        "wgmma.mma_async.sync.aligned.m64n128k16.f32.bf16.bf16 "
        "{%0, %1, %2, %3, %4, %5, %6, %7, %8, %9, %10, %11, %12, %13, %14, %15, %16, %17, %18, %19, %20, %21, %22, %23, %24, %25, %26, %27, %28, %29, %30, %31, %32, %33, %34, %35, %36, %37, %38, %39, %40, %41, %42, %43, %44, %45, %46, %47, %48, %49, %50, %51, %52, %53, %54, %55, %56, %57, %58, %59, %60, %61, %62, %63}, "
        "{%64, %65, %66, %67}, %68, p, 1, 1, 0;\n}\n"
        : "+f"(d[0]), "+f"(d[1]), "+f"(d[2]), "+f"(d[3]), "+f"(d[4]), "+f"(d[5]), "+f"(d[6]), "+f"(d[7]), "+f"(d[8]), "+f"(d[9]), "+f"(d[10]), "+f"(d[11]), "+f"(d[12]), "+f"(d[13]), "+f"(d[14]), "+f"(d[15]), "+f"(d[16]), "+f"(d[17]), "+f"(d[18]), "+f"(d[19]), "+f"(d[20]), "+f"(d[21]), "+f"(d[22]), "+f"(d[23]), "+f"(d[24]), "+f"(d[25]), "+f"(d[26]), "+f"(d[27]), "+f"(d[28]), "+f"(d[29]), "+f"(d[30]), "+f"(d[31]), "+f"(d[32]), "+f"(d[33]), "+f"(d[34]), "+f"(d[35]), "+f"(d[36]), "+f"(d[37]), "+f"(d[38]), "+f"(d[39]), "+f"(d[40]), "+f"(d[41]), "+f"(d[42]), "+f"(d[43]), "+f"(d[44]), "+f"(d[45]), "+f"(d[46]), "+f"(d[47]), "+f"(d[48]), "+f"(d[49]), "+f"(d[50]), "+f"(d[51]), "+f"(d[52]), "+f"(d[53]), "+f"(d[54]), "+f"(d[55]), "+f"(d[56]), "+f"(d[57]), "+f"(d[58]), "+f"(d[59]), "+f"(d[60]), "+f"(d[61]), "+f"(d[62]), "+f"(d[63])
        : "r"(a0), "r"(a1), "r"(a2), "r"(a3), "l"(db), "r"(sd));
}
__device__ __forceinline__ void wgmma_rs_n128_tb(float (&d)[64], uint32_t a0, uint32_t a1, uint32_t a2, uint32_t a3, uint64_t db, int sd) {
    asm volatile("{\n.reg .pred p;\nsetp.ne.b32 p, %69, 0;\n"
        "wgmma.mma_async.sync.aligned.m64n128k16.f32.bf16.bf16 "
        "{%0, %1, %2, %3, %4, %5, %6, %7, %8, %9, %10, %11, %12, %13, %14, %15, %16, %17, %18, %19, %20, %21, %22, %23, %24, %25, %26, %27, %28, %29, %30, %31, %32, %33, %34, %35, %36, %37, %38, %39, %40, %41, %42, %43, %44, %45, %46, %47, %48, %49, %50, %51, %52, %53, %54, %55, %56, %57, %58, %59, %60, %61, %62, %63}, "
        "{%64, %65, %66, %67}, %68, p, 1, 1, 1;\n}\n"
        : "+f"(d[0]), "+f"(d[1]), "+f"(d[2]), "+f"(d[3]), "+f"(d[4]), "+f"(d[5]), "+f"(d[6]), "+f"(d[7]), "+f"(d[8]), "+f"(d[9]), "+f"(d[10]), "+f"(d[11]), "+f"(d[12]), "+f"(d[13]), "+f"(d[14]), "+f"(d[15]), "+f"(d[16]), "+f"(d[17]), "+f"(d[18]), "+f"(d[19]), "+f"(d[20]), "+f"(d[21]), "+f"(d[22]), "+f"(d[23]), "+f"(d[24]), "+f"(d[25]), "+f"(d[26]), "+f"(d[27]), "+f"(d[28]), "+f"(d[29]), "+f"(d[30]), "+f"(d[31]), "+f"(d[32]), "+f"(d[33]), "+f"(d[34]), "+f"(d[35]), "+f"(d[36]), "+f"(d[37]), "+f"(d[38]), "+f"(d[39]), "+f"(d[40]), "+f"(d[41]), "+f"(d[42]), "+f"(d[43]), "+f"(d[44]), "+f"(d[45]), "+f"(d[46]), "+f"(d[47]), "+f"(d[48]), "+f"(d[49]), "+f"(d[50]), "+f"(d[51]), "+f"(d[52]), "+f"(d[53]), "+f"(d[54]), "+f"(d[55]), "+f"(d[56]), "+f"(d[57]), "+f"(d[58]), "+f"(d[59]), "+f"(d[60]), "+f"(d[61]), "+f"(d[62]), "+f"(d[63])
        : "r"(a0), "r"(a1), "r"(a2), "r"(a3), "l"(db), "r"(sd));
}
__device__ __forceinline__ void wgmma_rs_n64_tb(float (&d)[32], uint32_t a0, uint32_t a1, uint32_t a2, uint32_t a3, uint64_t db, int sd) {
    asm volatile("{\n.reg .pred p;\nsetp.ne.b32 p, %37, 0;\n"
        "wgmma.mma_async.sync.aligned.m64n64k16.f32.bf16.bf16 "
        "{%0, %1, %2, %3, %4, %5, %6, %7, %8, %9, %10, %11, %12, %13, %14, %15, %16, %17, %18, %19, %20, %21, %22, %23, %24, %25, %26, %27, %28, %29, %30, %31}, "
        "{%32, %33, %34, %35}, %36, p, 1, 1, 1;\n}\n"
        : "+f"(d[0]), "+f"(d[1]), "+f"(d[2]), "+f"(d[3]), "+f"(d[4]), "+f"(d[5]), "+f"(d[6]), "+f"(d[7]), "+f"(d[8]), "+f"(d[9]), "+f"(d[10]), "+f"(d[11]), "+f"(d[12]), "+f"(d[13]), "+f"(d[14]), "+f"(d[15]), "+f"(d[16]), "+f"(d[17]), "+f"(d[18]), "+f"(d[19]), "+f"(d[20]), "+f"(d[21]), "+f"(d[22]), "+f"(d[23]), "+f"(d[24]), "+f"(d[25]), "+f"(d[26]), "+f"(d[27]), "+f"(d[28]), "+f"(d[29]), "+f"(d[30]), "+f"(d[31])
        : "r"(a0), "r"(a1), "r"(a2), "r"(a3), "l"(db), "r"(sd));
}

__global__ void __launch_bounds__(384, 1) fused_gqa_kernel(const __grid_constant__ Params P) {
    extern __shared__ uint8_t smem_raw[];
    const uint32_t base = (smem_u32(smem_raw) + 1023u) & ~1023u;
    const uint32_t smR = base;
    const uint32_t smS = base + R_BYTES;
    const uint32_t bars = smS + NSTAGE * STAGE_BYTES;
    const uint32_t prog = bars + 8 * (2 * NSTAGE + 10);
    const int tid = threadIdx.x;
    const int wid = __shfl_sync(0xffffffffu, tid >> 5, 0);
    const int lane = tid & 31;

    const int cta = blockIdx.x;
    const int blk = cta >> 6;
    const int hp = (cta >> 3) & 7;
    const int b = cta & 7;
    const int grp = blk * 8 + b;

    if (tid == 0) {
        TS(0);
        for (int i = 0; i < NSTAGE; i++) {
            mbar_init(bars + 8 * i, 1);
            mbar_init(bars + 8 * (NSTAGE + i), 8);
        }
        for (int i = 0; i < 10; i++) mbar_init(bars + 8 * (2 * NSTAGE + i), 4);
        asm volatile("st.volatile.shared.u32 [%0], %1;" ::"r"(prog), "r"(0) : "memory");
        asm volatile("fence.mbarrier_init.release.cluster;" ::: "memory");
        asm volatile("fence.proxy.async.shared::cta;" ::: "memory");
    }
    __syncthreads();

    if (wid >= 8) {
        asm volatile("setmaxnreg.dec.sync.aligned.u32 40;");
        if (wid == 8) {
            if (lane == 0) {
                int slot = 0, ph = 1;
                for (int s = 0; s < N_WQ; s++) {
                    const uint32_t fb = bars + 8 * slot;
                    mbar_wait(bars + 8 * (NSTAGE + slot), ph);
                    const uint32_t dst = smS + slot * STAGE_BYTES;
                    mbar_expect_tx(fb, (s & 1) ? STAGE_BYTES : STAGE_BYTES + 8192);
                    if (!(s & 1)) tma_2d(smR + ((s >> 1) & 7) * 8192, &P.x[blk], (s >> 1) * 64, b * 64, fb);
#pragma unroll
                    for (int p = 0; p < 4; p++) {
                        const int w = p >> 1, j = p & 1;
                        tma_3d(dst + p * 8192, &P.wq[blk], 0, s * 32, hp * 8 + j * 4 + w * 2, fb);
                    }
                    if (++slot == NSTAGE) { slot = 0; ph ^= 1; }
                }
                for (int i = 0; i < 34; i++) {
                    const uint32_t fb = bars + 8 * slot;
                    mbar_wait(bars + 8 * (NSTAGE + slot), ph);
                    const uint32_t dst = smS + slot * STAGE_BYTES;
                    mbar_expect_tx(fb, STAGE_BYTES);
                    if (i < 16) {
                        const int row = (b * kHkv + hp * 2) * kSk + (i >> 1) * 128;
                        const CUtensorMap* tm = (i & 1) ? &P.v[blk] : &P.k[blk];
                        tma_3d(dst, tm, 0, row, 0, fb);
                    } else {
                        const int q = i - 16;
                        if (q < 16) {
                            const int g0 = (q >> 3) * 4, r0 = hp * 512 + (q & 7) * 64, r1 = hp * 512 + ((q & 7) ^ 2) * 64;
                            tma_3d(dst, &P.wo[blk], 0, r0, g0, fb);
                            tma_3d(dst + 16384, &P.wo[blk], 0, r1, g0 + 2, fb);
                        } else {
                            const int r0 = hp * 512 + (q - 16) * 256;
                            tma_2d(dst, &P.wo8[blk], 512, r0, fb);
                            tma_2d(dst + 16384, &P.wo8[blk], 512, r0 + 128, fb);
                        }
                    }
                    asm volatile("st.volatile.shared.u32 [%0], %1;" ::"r"(prog), "r"(i + 1) : "memory");
                    if (++slot == NSTAGE) { slot = 0; ph ^= 1; }
                }
            }
        } else if (wid == 11) {
            if (PF_DIST > 0) {
                uint32_t sink = 0;
                mbar_wait(bars, 0);
                if (PF_WQ) {
                    const char* wqs = (const char*)(P.wqp[blk] + hp * 512) + (size_t)(160 + b * 52) * 8192;
#pragma unroll
                    for (int h = 0; h < 2; h++) {
#pragma unroll
                        for (int j = 0; j < 4; j++) {
                            const int e = (h * 4 + j) * 32 + lane;
                            if (e < 208) sink |= l2_touch(wqs + (size_t)(e >> 2) * 8192 + (e & 3) * 256);
                        }
                        if (sink == 0x9E3779B9u) asm volatile("st.volatile.shared.u32 [%0], %1;" ::"r"(prog + 4), "r"(sink) : "memory");
                    }
                }
                const char* kbase = (const char*)(P.kp[blk] + (size_t)(b * kHkv + hp * 2) * kSk * kDh);
                const char* vbase = (const char*)(P.vp[blk] + (size_t)(b * kHkv + hp * 2) * kSk * kDh);
                const char* wos = (const char*)(P.wop[blk] + (size_t)hp * 512 * kD) + (size_t)b * 73728;
                for (int i = 0; i < 19; i++) {
                    if (i >= PF_DIST) {
                        uint32_t pr, n = 0;
                        while (true) {
                            asm volatile("ld.volatile.shared.u32 %0, [%1];" : "=r"(pr) : "r"(prog) : "memory");
                            if ((int)pr + PF_DIST >= i) break;
                            if (++n > (1u << 22)) break;
                            __nanosleep(100);
                        }
                    }
                    if (i < 16) {
                        const char* p = ((i & 1) ? vbase : kbase) + (size_t)(i >> 1) * 32768 + lane * 256;
#pragma unroll
                        for (int j = 0; j < 4; j++) sink |= l2_touch(p + j * 8192);
                    } else {
                        const char* p = wos + (size_t)(i - 16) * 24576 + lane * 256;
#pragma unroll
                        for (int j = 0; j < 3; j++) sink |= l2_touch(p + j * 8192);
                    }
                    if (sink == 0x9E3779B9u) asm volatile("st.volatile.shared.u32 [%0], %1;" ::"r"(prog + 4), "r"(sink) : "memory");
                }
            }
        } else {
            const int hw = wid - 9;
            for (int k = 0; k < 3; k++) {
                mbar_wait(bars + 8 * (2 * NSTAGE + hw * 5 + k), 0);
                const int c = (k < 2) ? (2 * k + hw) : 4;
                asm volatile("fence.acq_rel.gpu;" ::: "memory");
                asm volatile("red.relaxed.gpu.global.add.u32 [%0], 1;" ::"l"(&g_cnt[(grp * 9 + c) * 32 + lane]) : "memory");
            }
        }
    } else {
        asm volatile("setmaxnreg.inc.sync.aligned.u32 232;");
        const int w = wid >> 2;
        const int t = tid & 127;
        int slot = 0, ph = 0;
        uint32_t qf[8][4];
        const uint32_t stash = smR + (1 + w) * 16384 + t * 16;
        {
            float acc[128];
            int pslot = 0;
            for (int s = 0; s < N_WQ; s++) {
                mbar_wait(bars + 8 * slot, ph);
                if (tid == 0 && s == 0) TS(20);
                if (tid == 0 && s == 5) TS(21);
                if (tid == 0 && s == 10) TS(22);
                const uint64_t da = mk_desc(smR + ((s >> 1) & 7) * 8192 + (s & 1) * 64, 16, 1024);
                const uint64_t db = mk_desc(smS + slot * STAGE_BYTES + w * 16384, 4096, 1024);
                wg_fence();
                wgmma_ss_n256_tb(acc, da, db, s != 0);
                wgmma_ss_n256_tb(acc, da + 2, db + 128, 1);
                wg_commit();
                if (s > 0) {
                    wg_wait<1>();
                    if (lane == 0) mbar_arrive(bars + 8 * (NSTAGE + pslot));
                }
                pslot = slot;
                if (++slot == NSTAGE) { slot = 0; ph ^= 1; }
            }
            wg_wait<0>();
            if (lane == 0) mbar_arrive(bars + 8 * (NSTAGE + pslot));
            fence_regs(acc);
            if (tid == 0) TS(1);
#pragma unroll
            for (int kk = 0; kk < 8; kk++) {
#pragma unroll
                for (int i = 0; i < 4; i++) qf[kk][i] = pack_bf16(acc[8 * kk + 2 * i], acc[8 * kk + 2 * i + 1]);
                sts128(stash + kk * 2048,
                       pack_bf16(acc[64 + 8 * kk + 0], acc[64 + 8 * kk + 1]), pack_bf16(acc[64 + 8 * kk + 2], acc[64 + 8 * kk + 3]),
                       pack_bf16(acc[64 + 8 * kk + 4], acc[64 + 8 * kk + 5]), pack_bf16(acc[64 + 8 * kk + 6], acc[64 + 8 * kk + 7]));
            }
        }
        if (w == 1) bar_arrive<5, 256>();
        const float sc = 0.08838834764831845f * 1.4426950408889634f;
        uint32_t af[32][4];
#pragma unroll
        for (int u = 0; u < 2; u++) {
            {
                if (u == 1) {
#pragma unroll
                    for (int kk = 0; kk < 8; kk++) lds128(stash + kk * 2048, qf[kk]);
                }
                float o[64], s[64];
                float m0 = -INFINITY, m1 = -INFINITY, l0 = 0.f, l1 = 0.f;
                uint32_t pf[8][4];
#pragma unroll
                for (int i = 0; i < 64; i++) { o[i] = 0.f; s[i] = 0.f; }
#pragma unroll
                for (int i = 0; i < 32; i++) pf[i >> 2][i & 3] = 0u;
#pragma unroll 1
                for (int tt = 0; tt <= 4; tt++) {
                    int vslot = slot;
                    if (tt > 0) {
                        mbar_wait(bars + 8 * slot, ph);
                        if (++slot == NSTAGE) { slot = 0; ph ^= 1; }
                    }
                    if (tt < 4) mbar_wait(bars + 8 * slot, ph);
                    if (tid == 0) TS(32 + u * 20 + tt * 4);
                    if (w == 0) bar_sync<5, 256>(); else bar_sync<6, 256>();
                    wg_fence();
                    if (tt > 0) {
                        const uint64_t db = mk_desc(smS + vslot * STAGE_BYTES, 16384, 1024);
#pragma unroll
                        for (int kk = 0; kk < 8; kk++)
                            wgmma_rs_n128_tb(o, pf[kk][0], pf[kk][1], pf[kk][2], pf[kk][3], db + kk * 128, (tt > 1) || (kk != 0));
                        wg_commit();
                    }
                    if (tt < 4) {
                        const uint64_t db = mk_desc(smS + slot * STAGE_BYTES, 16, 1024);
#pragma unroll
                        for (int kk = 0; kk < 8; kk++)
                            wgmma_rs_n128(s, qf[kk][0], qf[kk][1], qf[kk][2], qf[kk][3], db + (kk >> 2) * 1024 + (kk & 3) * 2, kk != 0);
                        wg_commit();
                    }
                    if (w == 0) bar_arrive<6, 256>(); else if (!(u == 1 && tt == 4)) bar_arrive<5, 256>();
                    if (tid == 0) TS(32 + u * 20 + tt * 4 + 1);
                    wg_wait<0>();
                    fence_regs(o);
                    fence_regs(s);
                    if (tid == 0) TS(32 + u * 20 + tt * 4 + 2);
                    if (tt > 0 && lane == 0) mbar_arrive(bars + 8 * (NSTAGE + vslot));
                    if (tt == 4) break;
                    if (lane == 0) mbar_arrive(bars + 8 * (NSTAGE + slot));
                    if (++slot == NSTAGE) { slot = 0; ph ^= 1; }
                    float mx0 = s[0], mx1 = s[2];
#pragma unroll
                    for (int j = 0; j < 16; j++) {
                        mx0 = fmaxf(mx0, fmaxf(s[4 * j], s[4 * j + 1]));
                        mx1 = fmaxf(mx1, fmaxf(s[4 * j + 2], s[4 * j + 3]));
                    }
                    mx0 = fmaxf(mx0, __shfl_xor_sync(0xffffffffu, mx0, 1));
                    mx1 = fmaxf(mx1, __shfl_xor_sync(0xffffffffu, mx1, 1));
                    mx0 = fmaxf(mx0, __shfl_xor_sync(0xffffffffu, mx0, 2));
                    mx1 = fmaxf(mx1, __shfl_xor_sync(0xffffffffu, mx1, 2));
                    const float mn0 = fmaxf(m0, mx0), mn1 = fmaxf(m1, mx1);
                    const float al0 = ex2((m0 - mn0) * sc), al1 = ex2((m1 - mn1) * sc);
                    m0 = mn0; m1 = mn1;
                    const float ms0 = mn0 * sc, ms1 = mn1 * sc;
                    float rs0 = 0.f, rs1 = 0.f;
#pragma unroll
                    for (int j = 0; j < 16; j++) {
                        const float p0 = ex2(fmaf(s[4 * j], sc, -ms0)), p1 = ex2(fmaf(s[4 * j + 1], sc, -ms0));
                        const float p2 = ex2(fmaf(s[4 * j + 2], sc, -ms1)), p3 = ex2(fmaf(s[4 * j + 3], sc, -ms1));
                        rs0 += p0 + p1; rs1 += p2 + p3;
                        pf[j >> 1][(j & 1) * 2] = pack_bf16(p0, p1);
                        pf[j >> 1][(j & 1) * 2 + 1] = pack_bf16(p2, p3);
                    }
                    l0 = l0 * al0 + rs0; l1 = l1 * al1 + rs1;
                    if (tt > 0) {
#pragma unroll
                        for (int j = 0; j < 16; j++) { o[4 * j] *= al0; o[4 * j + 1] *= al0; o[4 * j + 2] *= al1; o[4 * j + 3] *= al1; }
                    }
                    if (tid == 0) TS(32 + u * 20 + tt * 4 + 3);
                }
                if (tid == 0) TS(2 + u);
                l0 += __shfl_xor_sync(0xffffffffu, l0, 1);
                l1 += __shfl_xor_sync(0xffffffffu, l1, 1);
                l0 += __shfl_xor_sync(0xffffffffu, l0, 2);
                l1 += __shfl_xor_sync(0xffffffffu, l1, 2);
                const float i0 = 1.f / l0, i1 = 1.f / l1;
                const uint32_t zown = smR + ((u == 0) ? (w ? 3 : 0) : (w ? 2 : 1)) * 16384 + t * 16;
#pragma unroll
                for (int kk = 0; kk < 8; kk++) {
                    af[16 + kk][0] = pack_bf16(o[8 * kk + 0] * i0, o[8 * kk + 1] * i0);
                    af[16 + kk][1] = pack_bf16(o[8 * kk + 2] * i1, o[8 * kk + 3] * i1);
                    af[16 + kk][2] = pack_bf16(o[8 * kk + 4] * i0, o[8 * kk + 5] * i0);
                    af[16 + kk][3] = pack_bf16(o[8 * kk + 6] * i1, o[8 * kk + 7] * i1);
                    sts128(zown + kk * 2048, af[16 + kk][0], af[16 + kk][1], af[16 + kk][2], af[16 + kk][3]);
                }
            }
        }
        if (w == 0) bar_arrive<7, 256>(); else bar_arrive<8, 256>();
        {
#pragma unroll
            for (int kk = 0; kk < 8; kk++) {
                lds128(smR + (w ? 3 : 0) * 16384 + kk * 2048 + t * 16, af[kk]);
                lds128(smR + (w ? 0 : 3) * 16384 + kk * 2048 + t * 16, af[8 + kk]);
            }
            uint2* dst0 = g_part + (size_t)(grp * 80 + 2 * w * 8 + hp) * 1024 + t;
            uint2* dst8 = g_part + (size_t)(grp * 80 + 64 + hp * 2 + w) * 1024 + t;
#pragma unroll
            for (int ps = 0; ps < 2; ps++) {
                float acc[64];
#pragma unroll
                for (int i = 0; i < 64; i++) acc[i] = 0.f;
                int pslot = 0;
#pragma unroll
                for (int st = 0; st < 8; st++) {
                    if (ps == 0 && st == 5) {
                        if (w == 0) bar_sync<8, 256>(); else bar_sync<7, 256>();
#pragma unroll
                        for (int kk = 0; kk < 8; kk++) lds128(smR + (w ? 1 : 2) * 16384 + kk * 2048 + t * 16, af[24 + kk]);
                    }
                    mbar_wait(bars + 8 * slot, ph);
                    const uint64_t db = mk_desc(smS + slot * STAGE_BYTES + w * 16384, 8192, 1024);
                    wg_fence();
#pragma unroll
                    for (int kk = 0; kk < 4; kk++)
                        wgmma_rs_n128_tb(acc, af[st * 4 + kk][0], af[st * 4 + kk][1], af[st * 4 + kk][2], af[st * 4 + kk][3], db + kk * 128, (st | kk) != 0);
                    wg_commit();
                    if (st > 0) {
                        wg_wait<1>();
                        if (lane == 0) mbar_arrive(bars + 8 * (NSTAGE + pslot));
                    }
                    pslot = slot;
                    if (++slot == NSTAGE) { slot = 0; ph ^= 1; }
                }
                wg_wait<0>();
                if (lane == 0) mbar_arrive(bars + 8 * (NSTAGE + pslot));
                fence_regs(acc);
                uint2* dst = dst0 + (size_t)ps * 32 * 1024;
#pragma unroll
                for (int j = 0; j < 16; j++)
                    __stcg(dst + (j >> 3) * 8192 + (j & 7) * 128, make_uint2(pack_bf16(acc[4 * j], acc[4 * j + 1]), pack_bf16(acc[4 * j + 2], acc[4 * j + 3])));
                __syncwarp();
                if (lane == 0) mbar_arrive(bars + 8 * (2 * NSTAGE + w * 5 + ps));
                if (tid == 0) TS(4 + ps);
            }
            {
                float acc[32];
#pragma unroll
                for (int i = 0; i < 32; i++) acc[i] = 0.f;
                int pslot = slot;
#pragma unroll
                for (int st = 0; st < 2; st++) {
                    mbar_wait(bars + 8 * slot, ph);
                    const uint64_t db = mk_desc(smS + slot * STAGE_BYTES + w * 16384, 8192, 1024);
                    wg_fence();
#pragma unroll
                    for (int kk = 0; kk < 8; kk++)
                        wgmma_rs_n64_tb(acc, af[st * 16 + kk][0], af[st * 16 + kk][1], af[st * 16 + kk][2], af[st * 16 + kk][3], db + kk * 128, (st | kk) != 0);
                    wg_commit();
                    if (++slot == NSTAGE) { slot = 0; ph ^= 1; }
                }
                wg_wait<0>();
                (void)pslot;
                fence_regs(acc);
#pragma unroll
                for (int j = 0; j < 8; j++)
                    __stcg(dst8 + j * 128, make_uint2(pack_bf16(acc[4 * j], acc[4 * j + 1]), pack_bf16(acc[4 * j + 2], acc[4 * j + 3])));
                __syncwarp();
                if (lane == 0) mbar_arrive(bars + 8 * (2 * NSTAGE + w * 5 + 2));
                if (tid == 0) TS(8);
            }
        }
        {
            const int nch = (w == 0) ? 3 : 2;
            if (lane < nch) {
                const int c = (lane < 2) ? (2 * lane + w) : 4;
                const unsigned need = (lane < 2) ? 8u : 16u;
                unsigned* cp = &g_cnt[(grp * 9 + c) * 32 + hp * 4 + (wid & 3)];
                unsigned v, n = 0;
                while (true) {
                    asm volatile("ld.acquire.gpu.global.u32 %0, [%1];" : "=r"(v) : "l"(cp) : "memory");
                    if (v >= need) break;
                    if (++n > (1u << 21)) break;
                }
                *cp = 0;
            }
            __syncwarp();
            if (tid == 0) TS(18);
            __nv_bfloat16* orow = P.out + (size_t)(b * 64 + (t >> 5) * 16 + (lane >> 2)) * (2 * kD) + blk * kD + hp * 8 + (lane & 3) * 2;
            const uint2* src = g_part + ((size_t)(grp * 80 + 2 * w * 8) * 8 + hp) * 128 + t;
            uint2 v[4][8];
#pragma unroll
            for (int k = 0; k < 4; k++)
#pragma unroll
                for (int i = 0; i < 8; i++) v[k][i] = __ldcg(src + (size_t)((k >> 1) * 32 + (k & 1) * 8 + i) * 1024);
            if (w == 0) {
                const uint2* src8 = g_part + ((size_t)(grp * 80 + 64) * 8 + hp) * 128 + t;
                uint2 u[16];
#pragma unroll
                for (int i = 0; i < 16; i++) u[i] = __ldcg(src8 + (size_t)i * 1024);
                float a0 = 0.f, a1 = 0.f, a2 = 0.f, a3 = 0.f;
#pragma unroll
                for (int i = 0; i < 16; i++) {
                    a0 += __uint_as_float(u[i].x << 16); a1 += __uint_as_float(u[i].x & 0xffff0000u);
                    a2 += __uint_as_float(u[i].y << 16); a3 += __uint_as_float(u[i].y & 0xffff0000u);
                }
                *(uint32_t*)(orow + 512) = pack_bf16(a0, a1);
                *(uint32_t*)(orow + 512 + 8 * 2 * kD) = pack_bf16(a2, a3);
            }
#pragma unroll
            for (int k = 0; k < 4; k++) {
                float a0 = 0.f, a1 = 0.f, a2 = 0.f, a3 = 0.f;
#pragma unroll
                for (int i = 0; i < 8; i++) {
                    a0 += __uint_as_float(v[k][i].x << 16); a1 += __uint_as_float(v[k][i].x & 0xffff0000u);
                    a2 += __uint_as_float(v[k][i].y << 16); a3 += __uint_as_float(v[k][i].y & 0xffff0000u);
                }
                *(uint32_t*)(orow + ((k >> 1) * 4 + 2 * w + (k & 1)) * 64) = pack_bf16(a0, a1);
                *(uint32_t*)(orow + ((k >> 1) * 4 + 2 * w + (k & 1)) * 64 + 8 * 2 * kD) = pack_bf16(a2, a3);
            }
            if (tid == 0) TS(19);
        }
    }
}

typedef CUresult (*EncodeFn)(CUtensorMap*, CUtensorMapDataType, cuuint32_t, void*, const cuuint64_t*, const cuuint64_t*,
                             const cuuint32_t*, const cuuint32_t*, CUtensorMapInterleave, CUtensorMapSwizzle,
                             CUtensorMapL2promotion, CUtensorMapFloatOOBfill);

void make_map(EncodeFn fn, CUtensorMap* m, const void* ptr, uint64_t cols, uint64_t rows, uint32_t box_rows) {
    cuuint64_t dims[2] = {cols, rows};
    cuuint64_t strides[1] = {cols * 2};
    cuuint32_t box[2] = {64, box_rows};
    cuuint32_t es[2] = {1, 1};
    fn(m, CU_TENSOR_MAP_DATA_TYPE_BFLOAT16, 2, const_cast<void*>(ptr), dims, strides, box, es, CU_TENSOR_MAP_INTERLEAVE_NONE,
       CU_TENSOR_MAP_SWIZZLE_128B, CU_TENSOR_MAP_L2_PROMOTION_L2_256B, CU_TENSOR_MAP_FLOAT_OOB_FILL_NONE);
}

void make_map3(EncodeFn fn, CUtensorMap* m, const void* ptr, uint64_t cols, uint64_t rows, uint32_t box_rows, uint32_t box_groups) {
    cuuint64_t dims[3] = {64, rows, cols / 64};
    cuuint64_t strides[2] = {cols * 2, 128};
    cuuint32_t box[3] = {64, box_rows, box_groups};
    cuuint32_t es[3] = {1, 1, 1};
    fn(m, CU_TENSOR_MAP_DATA_TYPE_BFLOAT16, 3, const_cast<void*>(ptr), dims, strides, box, es, CU_TENSOR_MAP_INTERLEAVE_NONE,
       CU_TENSOR_MAP_SWIZZLE_128B, CU_TENSOR_MAP_L2_PROMOTION_L2_256B, CU_TENSOR_MAP_FLOAT_OOB_FILL_NONE);
}

}

extern "C" void kernel_launch(void* const* d_in, const int* in_sizes, int n_in, void* d_out, int out_size) {
    static EncodeFn enc = nullptr;
    if (!enc) {
        void* fn = nullptr;
        cudaDriverEntryPointQueryResult st;
        cudaGetDriverEntryPoint("cuTensorMapEncodeTiled", &fn, cudaEnableDefault, &st);
        enc = (EncodeFn)fn;
        cudaFuncSetAttribute(fused_gqa_kernel, cudaFuncAttributeMaxDynamicSharedMemorySize, SMEM_BYTES);
    }
    Params P;
    for (int blk = 0; blk < 2; blk++) {
        const void* x = d_in[blk * 5 + 0];
        const void* k = d_in[blk * 5 + 1];
        const void* v = d_in[blk * 5 + 2];
        const void* wq = d_in[blk * 5 + 3];
        const void* wo = d_in[blk * 5 + 4];
        make_map(enc, &P.x[blk], x, kD, kB * kSq, 64);
        make_map3(enc, &P.wq[blk], wq, kHq * kDh, kD, 32, 2);
        make_map3(enc, &P.k[blk], k, kDh, (uint64_t)kB * kHkv * kSk, 128, 2);
        make_map3(enc, &P.v[blk], v, kDh, (uint64_t)kB * kHkv * kSk, 128, 2);
        make_map3(enc, &P.wo[blk], wo, kD, kHq * kDh, 64, 2);
        make_map(enc, &P.wo8[blk], wo, kD, kHq * kDh, 128);
        P.wqp[blk] = (const __nv_bfloat16*)wq;
        P.kp[blk] = (const __nv_bfloat16*)k;
        P.vp[blk] = (const __nv_bfloat16*)v;
        P.wop[blk] = (const __nv_bfloat16*)wo;
    }
    P.out = (__nv_bfloat16*)d_out;
    fused_gqa_kernel<<<128, 384, SMEM_BYTES>>>(P);
}
```

```cpp
#include <cuda_runtime.h>
#include <cuda_bf16.h>
#include <cuda.h>
#include <stdint.h>

namespace {

constexpr int kB = 8, kSq = 64, kD = 576, kHq = 32, kHkv = 16, kSk = 512, kDh = 128;
constexpr int NSTAGE = 5;
constexpr int STAGE_BYTES = 32768;
constexpr int R_BYTES = 65536;
constexpr int SMEM_BYTES = R_BYTES + NSTAGE * STAGE_BYTES + 1024   + 256  ;
constexpr int N_WQ = 18;
#define PF_DIST_V 6
#define OP_WAIT0 1
#define QP_WAIT0 1
#define PF_WQ 0
#define PF_SLEEP 1000
constexpr int PF_DIST = PF_DIST_V;

struct __align__(64) Params {
    CUtensorMap x[2], wq[2], k[2], v[2], wo[2], wo8[2];
    const __nv_bfloat16* wqp[2];
    const __nv_bfloat16* kp[2];
    const __nv_bfloat16* vp[2];
    const __nv_bfloat16* wop[2];
    __nv_bfloat16* out;
};

__device__ uint2 g_part[16 * 80 * 8 * 128];
__device__ unsigned int g_cnt[16 * 9 * 32];
#define TS(k) do {} while (0)

__device__ __forceinline__ uint32_t smem_u32(const void* p) { return (uint32_t)__cvta_generic_to_shared(p); }
__device__ __forceinline__ void mbar_init(uint32_t bar, int cnt) {
    asm volatile("mbarrier.init.shared::cta.b64 [%0], %1;" ::"r"(bar), "r"(cnt));
}
__device__ __forceinline__ void mbar_expect_tx(uint32_t bar, uint32_t bytes) {
    asm volatile("mbarrier.arrive.expect_tx.shared::cta.b64 _, [%0], %1;" ::"r"(bar), "r"(bytes) : "memory");
}
__device__ __forceinline__ void mbar_arrive(uint32_t bar) {
    asm volatile("mbarrier.arrive.shared::cta.b64 _, [%0];" ::"r"(bar) : "memory");
}
__device__ __forceinline__ bool mbar_try(uint32_t bar, uint32_t parity) {
    uint32_t ok;
    asm volatile("{\n.reg .pred p;\nmbarrier.try_wait.parity.shared::cta.b64 p, [%1], %2;\nselp.u32 %0, 1, 0, p;\n}\n"
                 : "=r"(ok) : "r"(bar), "r"(parity) : "memory");
    return ok != 0;
}
__device__ __forceinline__ void mbar_wait(uint32_t bar, uint32_t parity) {
    if (mbar_try(bar, parity)) return;
    uint32_t n = 0;
    while (!mbar_try(bar, parity)) {
        if (++n > (1u << 20)) break;
    }
}
__device__ __forceinline__ void tma_2d(uint32_t dst, const CUtensorMap* tm, int c0, int c1, uint32_t bar) {
    asm volatile("cp.async.bulk.tensor.2d.shared::cluster.global.mbarrier::complete_tx::bytes [%0], [%1, {%3, %4}], [%2];"
                 ::"r"(dst), "l"(tm), "r"(bar), "r"(c0), "r"(c1) : "memory");
}
__device__ __forceinline__ void tma_3d(uint32_t dst, const CUtensorMap* tm, int c0, int c1, int c2, uint32_t bar) {
    asm volatile("cp.async.bulk.tensor.3d.shared::cluster.global.mbarrier::complete_tx::bytes [%0], [%1, {%3, %4, %5}], [%2];"
                 ::"r"(dst), "l"(tm), "r"(bar), "r"(c0), "r"(c1), "r"(c2) : "memory");
}
__device__ __forceinline__ void tma_3d_mc(uint32_t dst, const CUtensorMap* tm, int c0, int c1, int c2, uint32_t bar) {
    asm volatile("cp.async.bulk.tensor.3d.shared::cluster.global.mbarrier::complete_tx::bytes.multicast::cluster [%0], [%1, {%3, %4, %5}], [%2], %6;"
                 ::"r"(dst), "l"(tm), "r"(bar), "r"(c0), "r"(c1), "r"(c2), "h"((uint16_t)3) : "memory");
}
__device__ __forceinline__ void tma_2d_mc(uint32_t dst, const CUtensorMap* tm, int c0, int c1, uint32_t bar) {
    asm volatile("cp.async.bulk.tensor.2d.shared::cluster.global.mbarrier::complete_tx::bytes.multicast::cluster [%0], [%1, {%3, %4}], [%2], %5;"
                 ::"r"(dst), "l"(tm), "r"(bar), "r"(c0), "r"(c1), "h"((uint16_t)3) : "memory");
}
__device__ __forceinline__ void mbar_arrive_cluster(uint32_t cluster_addr) {
    asm volatile("mbarrier.arrive.release.cluster.shared::cluster.b64 _, [%0];" ::"r"(cluster_addr) : "memory");
}
__device__ __forceinline__ void cluster_sync_all() {
    asm volatile("barrier.cluster.arrive.release;\nbarrier.cluster.wait.acquire;" ::: "memory");
}
__device__ __forceinline__ void l2_prefetch(const void* p, uint32_t bytes) {
    asm volatile("cp.async.bulk.prefetch.L2.global [%0], %1;" ::"l"(p), "r"(bytes) : "memory");
}
__device__ __forceinline__ uint32_t l2_touch(const void* p) {
    uint32_t v;
    asm volatile("ld.global.L2::256B.b32 %0, [%1];" : "=r"(v) : "l"(p) : "memory");
    return v;
}
__device__ __forceinline__ void wg_fence() { asm volatile("wgmma.fence.sync.aligned;" ::: "memory"); }
__device__ __forceinline__ void wg_commit() { asm volatile("wgmma.commit_group.sync.aligned;" ::: "memory"); }
template <int N> __device__ __forceinline__ void wg_wait() { asm volatile("wgmma.wait_group.sync.aligned %0;" ::"n"(N) : "memory"); }
template <int N> __device__ __forceinline__ void fence_regs(float (&d)[N]) {
#pragma unroll
    for (int i = 0; i < N; i++) asm volatile("" : "+f"(d[i])::"memory");
}
__device__ __forceinline__ uint64_t mk_desc(uint32_t addr, uint32_t lbo, uint32_t sbo) {
    return (uint64_t)((addr & 0x3FFFF) >> 4) | ((uint64_t)(lbo >> 4) << 16) | ((uint64_t)(sbo >> 4) << 32) | (1ull << 62);
}
__device__ __forceinline__ uint32_t pack_bf16(float a, float b) {
    uint32_t r;
    asm("cvt.rn.bf16x2.f32 %0, %1, %2;" : "=r"(r) : "f"(b), "f"(a));
    return r;
}
__device__ __forceinline__ float ex2(float x) {
    float y;
    asm("ex2.approx.ftz.f32 %0, %1;" : "=f"(y) : "f"(x));
    return y;
}
template <int ID, int N> __device__ __forceinline__ void bar_sync() { asm volatile("bar.sync %0, %1;" ::"n"(ID), "n"(N) : "memory"); }
template <int ID, int N> __device__ __forceinline__ void bar_arrive() { asm volatile("bar.arrive %0, %1;" ::"n"(ID), "n"(N) : "memory"); }
__device__ __forceinline__ void sts128(uint32_t addr, uint32_t a, uint32_t b, uint32_t c, uint32_t d) {
    asm volatile("st.shared.v4.b32 [%0], {%1,%2,%3,%4};" ::"r"(addr), "r"(a), "r"(b), "r"(c), "r"(d) : "memory");
}
__device__ __forceinline__ void lds128(uint32_t addr, uint32_t (&r)[4]) {
    asm volatile("ld.shared.v4.b32 {%0,%1,%2,%3}, [%4];" : "=r"(r[0]), "=r"(r[1]), "=r"(r[2]), "=r"(r[3]) : "r"(addr) : "memory");
}

__device__ __forceinline__ void wgmma_ss_n256_tb(float (&d)[128], uint64_t da, uint64_t db, int sd) {
    asm volatile("{\n.reg .pred p;\nsetp.ne.b32 p, %130, 0;\n"
        "wgmma.mma_async.sync.aligned.m64n256k16.f32.bf16.bf16 "
        "{%0, %1, %2, %3, %4, %5, %6, %7, %8, %9, %10, %11, %12, %13, %14, %15, %16, %17, %18, %19, %20, %21, %22, %23, %24, %25, %26, %27, %28, %29, %30, %31, %32, %33, %34, %35, %36, %37, %38, %39, %40, %41, %42, %43, %44, %45, %46, %47, %48, %49, %50, %51, %52, %53, %54, %55, %56, %57, %58, %59, %60, %61, %62, %63, %64, %65, %66, %67, %68, %69, %70, %71, %72, %73, %74, %75, %76, %77, %78, %79, %80, %81, %82, %83, %84, %85, %86, %87, %88, %89, %90, %91, %92, %93, %94, %95, %96, %97, %98, %99, %100, %101, %102, %103, %104, %105, %106, %107, %108, %109, %110, %111, %112, %113, %114, %115, %116, %117, %118, %119, %120, %121, %122, %123, %124, %125, %126, %127}, "
        "%128, %129, p, 1, 1, 0, 1;\n}\n"
        : "+f"(d[0]), "+f"(d[1]), "+f"(d[2]), "+f"(d[3]), "+f"(d[4]), "+f"(d[5]), "+f"(d[6]), "+f"(d[7]), "+f"(d[8]), "+f"(d[9]), "+f"(d[10]), "+f"(d[11]), "+f"(d[12]), "+f"(d[13]), "+f"(d[14]), "+f"(d[15]), "+f"(d[16]), "+f"(d[17]), "+f"(d[18]), "+f"(d[19]), "+f"(d[20]), "+f"(d[21]), "+f"(d[22]), "+f"(d[23]), "+f"(d[24]), "+f"(d[25]), "+f"(d[26]), "+f"(d[27]), "+f"(d[28]), "+f"(d[29]), "+f"(d[30]), "+f"(d[31]), "+f"(d[32]), "+f"(d[33]), "+f"(d[34]), "+f"(d[35]), "+f"(d[36]), "+f"(d[37]), "+f"(d[38]), "+f"(d[39]), "+f"(d[40]), "+f"(d[41]), "+f"(d[42]), "+f"(d[43]), "+f"(d[44]), "+f"(d[45]), "+f"(d[46]), "+f"(d[47]), "+f"(d[48]), "+f"(d[49]), "+f"(d[50]), "+f"(d[51]), "+f"(d[52]), "+f"(d[53]), "+f"(d[54]), "+f"(d[55]), "+f"(d[56]), "+f"(d[57]), "+f"(d[58]), "+f"(d[59]), "+f"(d[60]), "+f"(d[61]), "+f"(d[62]), "+f"(d[63]), "+f"(d[64]), "+f"(d[65]), "+f"(d[66]), "+f"(d[67]), "+f"(d[68]), "+f"(d[69]), "+f"(d[70]), "+f"(d[71]), "+f"(d[72]), "+f"(d[73]), "+f"(d[74]), "+f"(d[75]), "+f"(d[76]), "+f"(d[77]), "+f"(d[78]), "+f"(d[79]), "+f"(d[80]), "+f"(d[81]), "+f"(d[82]), "+f"(d[83]), "+f"(d[84]), "+f"(d[85]), "+f"(d[86]), "+f"(d[87]), "+f"(d[88]), "+f"(d[89]), "+f"(d[90]), "+f"(d[91]), "+f"(d[92]), "+f"(d[93]), "+f"(d[94]), "+f"(d[95]), "+f"(d[96]), "+f"(d[97]), "+f"(d[98]), "+f"(d[99]), "+f"(d[100]), "+f"(d[101]), "+f"(d[102]), "+f"(d[103]), "+f"(d[104]), "+f"(d[105]), "+f"(d[106]), "+f"(d[107]), "+f"(d[108]), "+f"(d[109]), "+f"(d[110]), "+f"(d[111]), "+f"(d[112]), "+f"(d[113]), "+f"(d[114]), "+f"(d[115]), "+f"(d[116]), "+f"(d[117]), "+f"(d[118]), "+f"(d[119]), "+f"(d[120]), "+f"(d[121]), "+f"(d[122]), "+f"(d[123]), "+f"(d[124]), "+f"(d[125]), "+f"(d[126]), "+f"(d[127])
        : "l"(da), "l"(db), "r"(sd));
}
__device__ __forceinline__ void wgmma_rs_n128(float (&d)[64], uint32_t a0, uint32_t a1, uint32_t a2, uint32_t a3, uint64_t db, int sd) {
    asm volatile("{\n.reg .pred p;\nsetp.ne.b32 p, %69, 0;\n"
        "wgmma.mma_async.sync.aligned.m64n128k16.f32.bf16.bf16 "
        "{%0, %1, %2, %3, %4, %5, %6, %7, %8, %9, %10, %11, %12, %13, %14, %15, %16, %17, %18, %19, %20, %21, %22, %23, %24, %25, %26, %27, %28, %29, %30, %31, %32, %33, %34, %35, %36, %37, %38, %39, %40, %41, %42, %43, %44, %45, %46, %47, %48, %49, %50, %51, %52, %53, %54, %55, %56, %57, %58, %59, %60, %61, %62, %63}, "
        "{%64, %65, %66, %67}, %68, p, 1, 1, 0;\n}\n"
        : "+f"(d[0]), "+f"(d[1]), "+f"(d[2]), "+f"(d[3]), "+f"(d[4]), "+f"(d[5]), "+f"(d[6]), "+f"(d[7]), "+f"(d[8]), "+f"(d[9]), "+f"(d[10]), "+f"(d[11]), "+f"(d[12]), "+f"(d[13]), "+f"(d[14]), "+f"(d[15]), "+f"(d[16]), "+f"(d[17]), "+f"(d[18]), "+f"(d[19]), "+f"(d[20]), "+f"(d[21]), "+f"(d[22]), "+f"(d[23]), "+f"(d[24]), "+f"(d[25]), "+f"(d[26]), "+f"(d[27]), "+f"(d[28]), "+f"(d[29]), "+f"(d[30]), "+f"(d[31]), "+f"(d[32]), "+f"(d[33]), "+f"(d[34]), "+f"(d[35]), "+f"(d[36]), "+f"(d[37]), "+f"(d[38]), "+f"(d[39]), "+f"(d[40]), "+f"(d[41]), "+f"(d[42]), "+f"(d[43]), "+f"(d[44]), "+f"(d[45]), "+f"(d[46]), "+f"(d[47]), "+f"(d[48]), "+f"(d[49]), "+f"(d[50]), "+f"(d[51]), "+f"(d[52]), "+f"(d[53]), "+f"(d[54]), "+f"(d[55]), "+f"(d[56]), "+f"(d[57]), "+f"(d[58]), "+f"(d[59]), "+f"(d[60]), "+f"(d[61]), "+f"(d[62]), "+f"(d[63])
        : "r"(a0), "r"(a1), "r"(a2), "r"(a3), "l"(db), "r"(sd));
}
__device__ __forceinline__ void wgmma_rs_n128_tb(float (&d)[64], uint32_t a0, uint32_t a1, uint32_t a2, uint32_t a3, uint64_t db, int sd) {
    asm volatile("{\n.reg .pred p;\nsetp.ne.b32 p, %69, 0;\n"
        "wgmma.mma_async.sync.aligned.m64n128k16.f32.bf16.bf16 "
        "{%0, %1, %2, %3, %4, %5, %6, %7, %8, %9, %10, %11, %12, %13, %14, %15, %16, %17, %18, %19, %20, %21, %22, %23, %24, %25, %26, %27, %28, %29, %30, %31, %32, %33, %34, %35, %36, %37, %38, %39, %40, %41, %42, %43, %44, %45, %46, %47, %48, %49, %50, %51, %52, %53, %54, %55, %56, %57, %58, %59, %60, %61, %62, %63}, "
        "{%64, %65, %66, %67}, %68, p, 1, 1, 1;\n}\n"
        : "+f"(d[0]), "+f"(d[1]), "+f"(d[2]), "+f"(d[3]), "+f"(d[4]), "+f"(d[5]), "+f"(d[6]), "+f"(d[7]), "+f"(d[8]), "+f"(d[9]), "+f"(d[10]), "+f"(d[11]), "+f"(d[12]), "+f"(d[13]), "+f"(d[14]), "+f"(d[15]), "+f"(d[16]), "+f"(d[17]), "+f"(d[18]), "+f"(d[19]), "+f"(d[20]), "+f"(d[21]), "+f"(d[22]), "+f"(d[23]), "+f"(d[24]), "+f"(d[25]), "+f"(d[26]), "+f"(d[27]), "+f"(d[28]), "+f"(d[29]), "+f"(d[30]), "+f"(d[31]), "+f"(d[32]), "+f"(d[33]), "+f"(d[34]), "+f"(d[35]), "+f"(d[36]), "+f"(d[37]), "+f"(d[38]), "+f"(d[39]), "+f"(d[40]), "+f"(d[41]), "+f"(d[42]), "+f"(d[43]), "+f"(d[44]), "+f"(d[45]), "+f"(d[46]), "+f"(d[47]), "+f"(d[48]), "+f"(d[49]), "+f"(d[50]), "+f"(d[51]), "+f"(d[52]), "+f"(d[53]), "+f"(d[54]), "+f"(d[55]), "+f"(d[56]), "+f"(d[57]), "+f"(d[58]), "+f"(d[59]), "+f"(d[60]), "+f"(d[61]), "+f"(d[62]), "+f"(d[63])
        : "r"(a0), "r"(a1), "r"(a2), "r"(a3), "l"(db), "r"(sd));
}
__device__ __forceinline__ void wgmma_rs_n64_tb(float (&d)[32], uint32_t a0, uint32_t a1, uint32_t a2, uint32_t a3, uint64_t db, int sd) {
    asm volatile("{\n.reg .pred p;\nsetp.ne.b32 p, %37, 0;\n"
        "wgmma.mma_async.sync.aligned.m64n64k16.f32.bf16.bf16 "
        "{%0, %1, %2, %3, %4, %5, %6, %7, %8, %9, %10, %11, %12, %13, %14, %15, %16, %17, %18, %19, %20, %21, %22, %23, %24, %25, %26, %27, %28, %29, %30, %31}, "
        "{%32, %33, %34, %35}, %36, p, 1, 1, 1;\n}\n"
        : "+f"(d[0]), "+f"(d[1]), "+f"(d[2]), "+f"(d[3]), "+f"(d[4]), "+f"(d[5]), "+f"(d[6]), "+f"(d[7]), "+f"(d[8]), "+f"(d[9]), "+f"(d[10]), "+f"(d[11]), "+f"(d[12]), "+f"(d[13]), "+f"(d[14]), "+f"(d[15]), "+f"(d[16]), "+f"(d[17]), "+f"(d[18]), "+f"(d[19]), "+f"(d[20]), "+f"(d[21]), "+f"(d[22]), "+f"(d[23]), "+f"(d[24]), "+f"(d[25]), "+f"(d[26]), "+f"(d[27]), "+f"(d[28]), "+f"(d[29]), "+f"(d[30]), "+f"(d[31])
        : "r"(a0), "r"(a1), "r"(a2), "r"(a3), "l"(db), "r"(sd));
}

__global__ void __cluster_dims__(2, 1, 1) __launch_bounds__(384, 1) fused_gqa_kernel(const __grid_constant__ Params P) {
    extern __shared__ uint8_t smem_raw[];
    const uint32_t base = (smem_u32(smem_raw) + 1023u) & ~1023u;
    const uint32_t smR = base;
    const uint32_t smS = base + R_BYTES;
    const uint32_t bars = smS + NSTAGE * STAGE_BYTES;
    const uint32_t prog = bars + 8 * (2 * NSTAGE + 10);
    const uint32_t barW = prog + 16;
    const int tid = threadIdx.x;
    const int wid = __shfl_sync(0xffffffffu, tid >> 5, 0);
    const int lane = tid & 31;

    const int cta = blockIdx.x;
    const int blk = cta >> 6;
    const int hp = (cta >> 3) & 7;
    const int b = cta & 7;
    const int grp = blk * 8 + b;

    if (tid == 0) {
        TS(0);
        for (int i = 0; i < NSTAGE; i++) {
            mbar_init(bars + 8 * i, 1);
            mbar_init(bars + 8 * (NSTAGE + i), 8);
            mbar_init(barW + 8 * i, 16);
        }
        for (int i = 0; i < 10; i++) mbar_init(bars + 8 * (2 * NSTAGE + i), 4);
        asm volatile("st.volatile.shared.u32 [%0], %1;" ::"r"(prog), "r"(0) : "memory");
        asm volatile("fence.mbarrier_init.release.cluster;" ::: "memory");
        asm volatile("fence.proxy.async.shared::cta;" ::: "memory");
    }
    __syncthreads();
    cluster_sync_all();
    const int rank = cta & 1;

    if (wid >= 8) {
        asm volatile("setmaxnreg.dec.sync.aligned.u32 40;");
        if (wid == 8) {
            if (lane == 0) {
                int slot = 0;
                uint32_t phW = 0, phL = 0;
                for (int s = 0; s < N_WQ; s++) {
                    const uint32_t fb = bars + 8 * slot;
                    if (s >= NSTAGE) { mbar_wait(barW + 8 * slot, (phW >> slot) & 1); phW ^= 1u << slot; }
                    const uint32_t dst = smS + slot * STAGE_BYTES;
                    mbar_expect_tx(fb, (s & 1) ? STAGE_BYTES : STAGE_BYTES + 8192);
                    if (!(s & 1)) tma_2d(smR + ((s >> 1) & 7) * 8192, &P.x[blk], (s >> 1) * 64, b * 64, fb);
#pragma unroll
                    for (int j = 0; j < 2; j++) {
                        tma_3d_mc(dst + (rank * 2 + j) * 8192, &P.wq[blk], 0, s * 32, hp * 8 + j * 4 + rank * 2, fb);
                    }
                    if (++slot == NSTAGE) slot = 0;
                }
                for (int i = 0; i < 34; i++) {
                    const uint32_t fb = bars + 8 * slot;
                    if (i < 16) { mbar_wait(bars + 8 * (NSTAGE + slot), (phL >> slot) & 1); phL ^= 1u << slot; }
                    else { mbar_wait(barW + 8 * slot, (phW >> slot) & 1); phW ^= 1u << slot; }
                    const uint32_t dst = smS + slot * STAGE_BYTES;
                    mbar_expect_tx(fb, STAGE_BYTES);
                    if (i < 16) {
                        const int row = (b * kHkv + hp * 2) * kSk + (i >> 1) * 128;
                        const CUtensorMap* tm = (i & 1) ? &P.v[blk] : &P.k[blk];
                        tma_3d(dst, tm, 0, row, 0, fb);
                    } else {
                        const int q = i - 16;
                        if (q < 16) {
                            tma_3d_mc(dst + rank * 16384, &P.wo[blk], 0, hp * 512 + ((q & 7) ^ (rank * 2)) * 64, (q >> 3) * 4 + rank * 2, fb);
                        } else {
                            tma_2d_mc(dst + rank * 16384, &P.wo8[blk], 512, hp * 512 + (q - 16) * 256 + rank * 128, fb);
                        }
                    }
                    asm volatile("st.volatile.shared.u32 [%0], %1;" ::"r"(prog), "r"(i + 1) : "memory");
                    if (++slot == NSTAGE) slot = 0;
                }
            }
        } else if (wid == 11) {
            if (PF_DIST > 0) {
                uint32_t sink = 0;
                mbar_wait(bars, 0);
                if (PF_WQ) {
                    const char* wqs = (const char*)(P.wqp[blk] + hp * 512) + (size_t)(160 + b * 52) * 8192;
#pragma unroll
                    for (int h = 0; h < 2; h++) {
#pragma unroll
                        for (int j = 0; j < 4; j++) {
                            const int e = (h * 4 + j) * 32 + lane;
                            if (e < 208) sink |= l2_touch(wqs + (size_t)(e >> 2) * 8192 + (e & 3) * 256);
                        }
                        if (sink == 0x9E3779B9u) asm volatile("st.volatile.shared.u32 [%0], %1;" ::"r"(prog + 4), "r"(sink) : "memory");
                    }
                }
                const char* kbase = (const char*)(P.kp[blk] + (size_t)(b * kHkv + hp * 2) * kSk * kDh);
                const char* vbase = (const char*)(P.vp[blk] + (size_t)(b * kHkv + hp * 2) * kSk * kDh);
                const char* wos = (const char*)(P.wop[blk] + (size_t)hp * 512 * kD) + (size_t)b * 73728;
#define WO_POS 16
#define WO_FULL 0
                for (int ii = 0; ii < 17; ii++) {
                    const bool is_wo = (ii == WO_POS);
                    const int i = (ii > WO_POS) ? ii - 1 : ii;
                    if (i >= PF_DIST) {
                        uint32_t pr, n = 0;
                        while (true) {
                            asm volatile("ld.volatile.shared.u32 %0, [%1];" : "=r"(pr) : "r"(prog) : "memory");
                            if ((int)pr + PF_DIST >= i) break;
                            if (++n > (1u << 22)) break;
                            __nanosleep(100);
                        }
                    }
                    if (!is_wo) {
                        const char* p = ((i & 1) ? vbase : kbase) + (size_t)(i >> 1) * 32768 + lane * 256;
#pragma unroll
                        for (int j = 0; j < 4; j++) sink |= l2_touch(p + j * 8192);
                        if (sink == 0x9E3779B9u) asm volatile("st.volatile.shared.u32 [%0], %1;" ::"r"(prog + 4), "r"(sink) : "memory");
                    } else {
                        for (int h = 0; h < (WO_FULL ? 24 : 3); h++) {
                            const char* p = (WO_FULL ? (wos - (size_t)b * 73728 + (size_t)((h + 3 * b) % 24) * 24576) : (wos + (size_t)h * 24576)) + lane * 256;
#pragma unroll
                            for (int j = 0; j < 3; j++) sink |= l2_touch(p + j * 8192);
                            if (sink == 0x9E3779B9u) asm volatile("st.volatile.shared.u32 [%0], %1;" ::"r"(prog + 4), "r"(sink) : "memory");
                        }
                    }
                }
            }
        } else {
            const int hw = wid - 9;
            for (int k = 0; k < 3; k++) {
                mbar_wait(bars + 8 * (2 * NSTAGE + hw * 5 + k), 0);
                const int c = (k < 2) ? (2 * k + hw) : 4;
                asm volatile("fence.acq_rel.gpu;" ::: "memory");
                asm volatile("red.relaxed.gpu.global.add.u32 [%0], 1;" ::"l"(&g_cnt[(grp * 9 + c) * 32 + lane]) : "memory");
            }
        }
        cluster_sync_all();
    } else {
        asm volatile("setmaxnreg.inc.sync.aligned.u32 232;");
        const int w = wid >> 2;
        const int t = tid & 127;
        int slot = 0, ph = 0;
        uint32_t qf[8][4];
        const uint32_t stash = smR + (1 + w) * 16384 + t * 16;
        uint32_t relW;
        asm volatile("mapa.shared::cluster.u32 %0, %1, %2;" : "=r"(relW) : "r"(barW), "r"(rank ^ (lane & 1)));
        auto release = [&](int sl, bool pair) {
            if (pair) { if (lane < 2) mbar_arrive_cluster(relW + 8 * sl); }
            else if (lane == 0) mbar_arrive(bars + 8 * (NSTAGE + sl));
        };
        {
            float acc[128];
            for (int s = 0; s < N_WQ; s++) {
                mbar_wait(bars + 8 * slot, ph);
                if (tid == 0 && s == 0) TS(20);
                if (tid == 0 && s == 5) TS(21);
                if (tid == 0 && s == 10) TS(22);
                const uint64_t da = mk_desc(smR + ((s >> 1) & 7) * 8192 + (s & 1) * 64, 16, 1024);
                const uint64_t db = mk_desc(smS + slot * STAGE_BYTES + w * 16384, 4096, 1024);
                wg_fence();
                wgmma_ss_n256_tb(acc, da, db, s != 0);
                wgmma_ss_n256_tb(acc, da + 2, db + 128, 1);
                wg_commit();
                wg_wait<0>();
                release(slot, s < 13);
                if (++slot == NSTAGE) { slot = 0; ph ^= 1; }
            }
            fence_regs(acc);
            if (tid == 0) TS(1);
#pragma unroll
            for (int kk = 0; kk < 8; kk++) {
#pragma unroll
                for (int i = 0; i < 4; i++) qf[kk][i] = pack_bf16(acc[8 * kk + 2 * i], acc[8 * kk + 2 * i + 1]);
                sts128(stash + kk * 2048,
                       pack_bf16(acc[64 + 8 * kk + 0], acc[64 + 8 * kk + 1]), pack_bf16(acc[64 + 8 * kk + 2], acc[64 + 8 * kk + 3]),
                       pack_bf16(acc[64 + 8 * kk + 4], acc[64 + 8 * kk + 5]), pack_bf16(acc[64 + 8 * kk + 6], acc[64 + 8 * kk + 7]));
            }
        }
        if (w == 1) bar_arrive<5, 256>();
        const float sc = 0.08838834764831845f * 1.4426950408889634f;
        uint32_t af[32][4];
#pragma unroll
        for (int u = 0; u < 2; u++) {
            {
                if (u == 1) {
#pragma unroll
                    for (int kk = 0; kk < 8; kk++) lds128(stash + kk * 2048, qf[kk]);
                }
                float o[64], s[64];
                float m0 = -INFINITY, m1 = -INFINITY, l0 = 0.f, l1 = 0.f;
                uint32_t pf[8][4];
#pragma unroll
                for (int i = 0; i < 64; i++) { o[i] = 0.f; s[i] = 0.f; }
#pragma unroll
                for (int i = 0; i < 32; i++) pf[i >> 2][i & 3] = 0u;
#pragma unroll 1
                for (int tt = 0; tt <= 4; tt++) {
                    int vslot = slot;
                    if (tt > 0) {
                        mbar_wait(bars + 8 * slot, ph);
                        if (++slot == NSTAGE) { slot = 0; ph ^= 1; }
                    }
                    if (tt < 4) mbar_wait(bars + 8 * slot, ph);
                    if (tid == 0) TS(32 + u * 20 + tt * 4);
                    if (w == 0) bar_sync<5, 256>(); else bar_sync<6, 256>();
                    wg_fence();
                    if (tt > 0) {
                        const uint64_t db = mk_desc(smS + vslot * STAGE_BYTES, 16384, 1024);
#pragma unroll
                        for (int kk = 0; kk < 8; kk++)
                            wgmma_rs_n128_tb(o, pf[kk][0], pf[kk][1], pf[kk][2], pf[kk][3], db + kk * 128, (tt > 1) || (kk != 0));
                        wg_commit();
                    }
                    if (tt < 4) {
                        const uint64_t db = mk_desc(smS + slot * STAGE_BYTES, 16, 1024);
#pragma unroll
                        for (int kk = 0; kk < 8; kk++)
                            wgmma_rs_n128(s, qf[kk][0], qf[kk][1], qf[kk][2], qf[kk][3], db + (kk >> 2) * 1024 + (kk & 3) * 2, kk != 0);
                        wg_commit();
                    }
                    if (w == 0) bar_arrive<6, 256>(); else if (!(u == 1 && tt == 4)) bar_arrive<5, 256>();
                    if (tid == 0) TS(32 + u * 20 + tt * 4 + 1);
                    wg_wait<0>();
                    fence_regs(o);
                    fence_regs(s);
                    if (tid == 0) TS(32 + u * 20 + tt * 4 + 2);
                    if (tt > 0) release(vslot, u * 8 + 2 * tt - 1 >= 11);
                    if (tt == 4) break;
                    release(slot, u * 8 + 2 * tt >= 11);
                    if (++slot == NSTAGE) { slot = 0; ph ^= 1; }
                    float mx0 = s[0], mx1 = s[2];
#pragma unroll
                    for (int j = 0; j < 16; j++) {
                        mx0 = fmaxf(mx0, fmaxf(s[4 * j], s[4 * j + 1]));
                        mx1 = fmaxf(mx1, fmaxf(s[4 * j + 2], s[4 * j + 3]));
                    }
                    mx0 = fmaxf(mx0, __shfl_xor_sync(0xffffffffu, mx0, 1));
                    mx1 = fmaxf(mx1, __shfl_xor_sync(0xffffffffu, mx1, 1));
                    mx0 = fmaxf(mx0, __shfl_xor_sync(0xffffffffu, mx0, 2));
                    mx1 = fmaxf(mx1, __shfl_xor_sync(0xffffffffu, mx1, 2));
                    const float mn0 = fmaxf(m0, mx0), mn1 = fmaxf(m1, mx1);
                    const float al0 = ex2((m0 - mn0) * sc), al1 = ex2((m1 - mn1) * sc);
                    m0 = mn0; m1 = mn1;
                    const float ms0 = mn0 * sc, ms1 = mn1 * sc;
                    float rs0 = 0.f, rs1 = 0.f;
#pragma unroll
                    for (int j = 0; j < 16; j++) {
                        const float p0 = ex2(fmaf(s[4 * j], sc, -ms0)), p1 = ex2(fmaf(s[4 * j + 1], sc, -ms0));
                        const float p2 = ex2(fmaf(s[4 * j + 2], sc, -ms1)), p3 = ex2(fmaf(s[4 * j + 3], sc, -ms1));
                        rs0 += p0 + p1; rs1 += p2 + p3;
                        pf[j >> 1][(j & 1) * 2] = pack_bf16(p0, p1);
                        pf[j >> 1][(j & 1) * 2 + 1] = pack_bf16(p2, p3);
                    }
                    l0 = l0 * al0 + rs0; l1 = l1 * al1 + rs1;
                    if (tt > 0) {
#pragma unroll
                        for (int j = 0; j < 16; j++) { o[4 * j] *= al0; o[4 * j + 1] *= al0; o[4 * j + 2] *= al1; o[4 * j + 3] *= al1; }
                    }
                    if (tid == 0) TS(32 + u * 20 + tt * 4 + 3);
                }
                if (tid == 0) TS(2 + u);
                l0 += __shfl_xor_sync(0xffffffffu, l0, 1);
                l1 += __shfl_xor_sync(0xffffffffu, l1, 1);
                l0 += __shfl_xor_sync(0xffffffffu, l0, 2);
                l1 += __shfl_xor_sync(0xffffffffu, l1, 2);
                const float i0 = 1.f / l0, i1 = 1.f / l1;
                const uint32_t zown = smR + ((u == 0) ? (w ? 3 : 0) : (w ? 2 : 1)) * 16384 + t * 16;
#pragma unroll
                for (int kk = 0; kk < 8; kk++) {
                    af[16 + kk][0] = pack_bf16(o[8 * kk + 0] * i0, o[8 * kk + 1] * i0);
                    af[16 + kk][1] = pack_bf16(o[8 * kk + 2] * i1, o[8 * kk + 3] * i1);
                    af[16 + kk][2] = pack_bf16(o[8 * kk + 4] * i0, o[8 * kk + 5] * i0);
                    af[16 + kk][3] = pack_bf16(o[8 * kk + 6] * i1, o[8 * kk + 7] * i1);
                    sts128(zown + kk * 2048, af[16 + kk][0], af[16 + kk][1], af[16 + kk][2], af[16 + kk][3]);
                }
            }
        }
        if (w == 0) bar_arrive<7, 256>(); else bar_arrive<8, 256>();
        {
#pragma unroll
            for (int kk = 0; kk < 8; kk++) {
                lds128(smR + (w ? 3 : 0) * 16384 + kk * 2048 + t * 16, af[kk]);
                lds128(smR + (w ? 0 : 3) * 16384 + kk * 2048 + t * 16, af[8 + kk]);
            }
            uint2* dst0 = g_part + (size_t)(grp * 80 + 2 * w * 8 + hp) * 1024 + t;
            uint2* dst8 = g_part + (size_t)(grp * 80 + 64 + hp * 2 + w) * 1024 + t;
#pragma unroll
            for (int ps = 0; ps < 2; ps++) {
                float acc[64];
#pragma unroll
                for (int i = 0; i < 64; i++) acc[i] = 0.f;
#pragma unroll
                for (int st = 0; st < 8; st++) {
                    if (ps == 0 && st == 5) {
                        if (w == 0) bar_sync<8, 256>(); else bar_sync<7, 256>();
#pragma unroll
                        for (int kk = 0; kk < 8; kk++) lds128(smR + (w ? 1 : 2) * 16384 + kk * 2048 + t * 16, af[24 + kk]);
                    }
                    mbar_wait(bars + 8 * slot, ph);
                    if (tid == 0) TS(80 + ps * 16 + 2 * st);
                    const uint64_t db = mk_desc(smS + slot * STAGE_BYTES + w * 16384, 8192, 1024);
                    wg_fence();
#pragma unroll
                    for (int kk = 0; kk < 4; kk++)
                        wgmma_rs_n128_tb(acc, af[st * 4 + kk][0], af[st * 4 + kk][1], af[st * 4 + kk][2], af[st * 4 + kk][3], db + kk * 128, (st | kk) != 0);
                    wg_commit();
                    wg_wait<0>();
                    if (ps * 8 + st <= 12) release(slot, true);
                    if (tid == 0) TS(80 + ps * 16 + 2 * st + 1);
                    if (++slot == NSTAGE) { slot = 0; ph ^= 1; }
                }
                fence_regs(acc);
                uint2* dst = dst0 + (size_t)ps * 32 * 1024;
#pragma unroll
                for (int j = 0; j < 16; j++)
                    __stcg(dst + (j >> 3) * 8192 + (j & 7) * 128, make_uint2(pack_bf16(acc[4 * j], acc[4 * j + 1]), pack_bf16(acc[4 * j + 2], acc[4 * j + 3])));
                __syncwarp();
                if (lane == 0) mbar_arrive(bars + 8 * (2 * NSTAGE + w * 5 + ps));
                if (tid == 0) TS(4 + ps);
            }
            {
                float acc[32];
#pragma unroll
                for (int i = 0; i < 32; i++) acc[i] = 0.f;
                int pslot = slot;
#pragma unroll
                for (int st = 0; st < 2; st++) {
                    mbar_wait(bars + 8 * slot, ph);
                    const uint64_t db = mk_desc(smS + slot * STAGE_BYTES + w * 16384, 8192, 1024);
                    wg_fence();
#pragma unroll
                    for (int kk = 0; kk < 8; kk++)
                        wgmma_rs_n64_tb(acc, af[st * 16 + kk][0], af[st * 16 + kk][1], af[st * 16 + kk][2], af[st * 16 + kk][3], db + kk * 128, (st | kk) != 0);
                    wg_commit();
                    if (++slot == NSTAGE) { slot = 0; ph ^= 1; }
                }
                wg_wait<0>();
                (void)pslot;
                fence_regs(acc);
#pragma unroll
                for (int j = 0; j < 8; j++)
                    __stcg(dst8 + j * 128, make_uint2(pack_bf16(acc[4 * j], acc[4 * j + 1]), pack_bf16(acc[4 * j + 2], acc[4 * j + 3])));
                __syncwarp();
                if (lane == 0) mbar_arrive(bars + 8 * (2 * NSTAGE + w * 5 + 2));
                if (tid == 0) TS(8);
            }
        }
        {
            const int nch = (w == 0) ? 3 : 2;
            if (lane < nch) {
                const int c = (lane < 2) ? (2 * lane + w) : 4;
                const unsigned need = (lane < 2) ? 8u : 16u;
                unsigned* cp = &g_cnt[(grp * 9 + c) * 32 + hp * 4 + (wid & 3)];
                unsigned v, n = 0;
                while (true) {
                    asm volatile("ld.acquire.gpu.global.u32 %0, [%1];" : "=r"(v) : "l"(cp) : "memory");
                    if (v >= need) break;
                    if (++n > (1u << 21)) break;
                }
                *cp = 0;
            }
            __syncwarp();
            if (tid == 0) TS(18);
            __nv_bfloat16* orow = P.out + (size_t)(b * 64 + (t >> 5) * 16 + (lane >> 2)) * (2 * kD) + blk * kD + hp * 8 + (lane & 3) * 2;
            const uint2* src = g_part + ((size_t)(grp * 80 + 2 * w * 8) * 8 + hp) * 128 + t;
            uint2 v[4][8];
#pragma unroll
            for (int k = 0; k < 4; k++)
#pragma unroll
                for (int i = 0; i < 8; i++) v[k][i] = __ldcg(src + (size_t)((k >> 1) * 32 + (k & 1) * 8 + i) * 1024);
            if (w == 0) {
                const uint2* src8 = g_part + ((size_t)(grp * 80 + 64) * 8 + hp) * 128 + t;
                uint2 u[16];
#pragma unroll
                for (int i = 0; i < 16; i++) u[i] = __ldcg(src8 + (size_t)i * 1024);
                float a0 = 0.f, a1 = 0.f, a2 = 0.f, a3 = 0.f;
#pragma unroll
                for (int i = 0; i < 16; i++) {
                    a0 += __uint_as_float(u[i].x << 16); a1 += __uint_as_float(u[i].x & 0xffff0000u);
                    a2 += __uint_as_float(u[i].y << 16); a3 += __uint_as_float(u[i].y & 0xffff0000u);
                }
                *(uint32_t*)(orow + 512) = pack_bf16(a0, a1);
                *(uint32_t*)(orow + 512 + 8 * 2 * kD) = pack_bf16(a2, a3);
            }
#pragma unroll
            for (int k = 0; k < 4; k++) {
                float a0 = 0.f, a1 = 0.f, a2 = 0.f, a3 = 0.f;
#pragma unroll
                for (int i = 0; i < 8; i++) {
                    a0 += __uint_as_float(v[k][i].x << 16); a1 += __uint_as_float(v[k][i].x & 0xffff0000u);
                    a2 += __uint_as_float(v[k][i].y << 16); a3 += __uint_as_float(v[k][i].y & 0xffff0000u);
                }
                *(uint32_t*)(orow + ((k >> 1) * 4 + 2 * w + (k & 1)) * 64) = pack_bf16(a0, a1);
                *(uint32_t*)(orow + ((k >> 1) * 4 + 2 * w + (k & 1)) * 64 + 8 * 2 * kD) = pack_bf16(a2, a3);
            }
            if (tid == 0) TS(19);
        }
        cluster_sync_all();
    }
}

typedef CUresult (*EncodeFn)(CUtensorMap*, CUtensorMapDataType, cuuint32_t, void*, const cuuint64_t*, const cuuint64_t*,
                             const cuuint32_t*, const cuuint32_t*, CUtensorMapInterleave, CUtensorMapSwizzle,
                             CUtensorMapL2promotion, CUtensorMapFloatOOBfill);

void make_map(EncodeFn fn, CUtensorMap* m, const void* ptr, uint64_t cols, uint64_t rows, uint32_t box_rows) {
    cuuint64_t dims[2] = {cols, rows};
    cuuint64_t strides[1] = {cols * 2};
    cuuint32_t box[2] = {64, box_rows};
    cuuint32_t es[2] = {1, 1};
    fn(m, CU_TENSOR_MAP_DATA_TYPE_BFLOAT16, 2, const_cast<void*>(ptr), dims, strides, box, es, CU_TENSOR_MAP_INTERLEAVE_NONE,
       CU_TENSOR_MAP_SWIZZLE_128B, CU_TENSOR_MAP_L2_PROMOTION_L2_256B, CU_TENSOR_MAP_FLOAT_OOB_FILL_NONE);
}

void make_map3(EncodeFn fn, CUtensorMap* m, const void* ptr, uint64_t cols, uint64_t rows, uint32_t box_rows, uint32_t box_groups) {
    cuuint64_t dims[3] = {64, rows, cols / 64};
    cuuint64_t strides[2] = {cols * 2, 128};
    cuuint32_t box[3] = {64, box_rows, box_groups};
    cuuint32_t es[3] = {1, 1, 1};
    fn(m, CU_TENSOR_MAP_DATA_TYPE_BFLOAT16, 3, const_cast<void*>(ptr), dims, strides, box, es, CU_TENSOR_MAP_INTERLEAVE_NONE,
       CU_TENSOR_MAP_SWIZZLE_128B, CU_TENSOR_MAP_L2_PROMOTION_L2_256B, CU_TENSOR_MAP_FLOAT_OOB_FILL_NONE);
}

}

extern "C" void kernel_launch(void* const* d_in, const int* in_sizes, int n_in, void* d_out, int out_size) {
    static EncodeFn enc = nullptr;
    if (!enc) {
        void* fn = nullptr;
        cudaDriverEntryPointQueryResult st;
        cudaGetDriverEntryPoint("cuTensorMapEncodeTiled", &fn, cudaEnableDefault, &st);
        enc = (EncodeFn)fn;
        cudaFuncSetAttribute(fused_gqa_kernel, cudaFuncAttributeMaxDynamicSharedMemorySize, SMEM_BYTES);
    }
    Params P;
    for (int blk = 0; blk < 2; blk++) {
        const void* x = d_in[blk * 5 + 0];
        const void* k = d_in[blk * 5 + 1];
        const void* v = d_in[blk * 5 + 2];
        const void* wq = d_in[blk * 5 + 3];
        const void* wo = d_in[blk * 5 + 4];
        make_map(enc, &P.x[blk], x, kD, kB * kSq, 64);
        make_map3(enc, &P.wq[blk], wq, kHq * kDh, kD, 32, 2);
        make_map3(enc, &P.k[blk], k, kDh, (uint64_t)kB * kHkv * kSk, 128, 2);
        make_map3(enc, &P.v[blk], v, kDh, (uint64_t)kB * kHkv * kSk, 128, 2);
        make_map3(enc, &P.wo[blk], wo, kD, kHq * kDh, 64, 2);
        make_map(enc, &P.wo8[blk], wo, kD, kHq * kDh, 128);
        P.wqp[blk] = (const __nv_bfloat16*)wq;
        P.kp[blk] = (const __nv_bfloat16*)k;
        P.vp[blk] = (const __nv_bfloat16*)v;
        P.wop[blk] = (const __nv_bfloat16*)wo;
    }
    P.out = (__nv_bfloat16*)d_out;
    fused_gqa_kernel<<<128, 384, SMEM_BYTES>>>(P);
}
```

```cpp
#include <cuda_runtime.h>
#include <cuda_bf16.h>
#include <cuda.h>
#include <stdint.h>

namespace {

constexpr int kB = 8, kSq = 64, kD = 576, kHq = 32, kHkv = 16, kSk = 512, kDh = 128;
constexpr int NSTAGE = 5;
constexpr int STAGE_BYTES = 32768;
constexpr int R_BYTES = 65536;
constexpr int SMEM_BYTES = R_BYTES + NSTAGE * STAGE_BYTES + 1024   + 512  ;
constexpr int N_WQ = 18;
#define PF_DIST_V 6
#define OP_WAIT0 1
#define QP_WAIT0 1
#define PF_WQ 0
#define PF_SLEEP 1000
constexpr int PF_DIST = PF_DIST_V;

struct __align__(64) Params {
    CUtensorMap x[2], wq[2], k[2], v[2], wo[2], wo8[2];
    const __nv_bfloat16* wqp[2];
    const __nv_bfloat16* kp[2];
    const __nv_bfloat16* vp[2];
    const __nv_bfloat16* wop[2];
    __nv_bfloat16* out;
};

__device__ uint2 g_part[16 * 80 * 8 * 128];
__device__ unsigned int g_cnt[16 * 9 * 32];
#define TS(k) do {} while (0)

__device__ __forceinline__ uint32_t smem_u32(const void* p) { return (uint32_t)__cvta_generic_to_shared(p); }
__device__ __forceinline__ void mbar_init(uint32_t bar, int cnt) {
    asm volatile("mbarrier.init.shared::cta.b64 [%0], %1;" ::"r"(bar), "r"(cnt));
}
__device__ __forceinline__ void mbar_expect_tx(uint32_t bar, uint32_t bytes) {
    asm volatile("mbarrier.arrive.expect_tx.shared::cta.b64 _, [%0], %1;" ::"r"(bar), "r"(bytes) : "memory");
}
__device__ __forceinline__ void mbar_arrive(uint32_t bar) {
    asm volatile("mbarrier.arrive.shared::cta.b64 _, [%0];" ::"r"(bar) : "memory");
}
__device__ __forceinline__ bool mbar_try(uint32_t bar, uint32_t parity) {
    uint32_t ok;
    asm volatile("{\n.reg .pred p;\nmbarrier.try_wait.parity.shared::cta.b64 p, [%1], %2;\nselp.u32 %0, 1, 0, p;\n}\n"
                 : "=r"(ok) : "r"(bar), "r"(parity) : "memory");
    return ok != 0;
}
__device__ __forceinline__ void mbar_wait(uint32_t bar, uint32_t parity) {
    if (mbar_try(bar, parity)) return;
    uint32_t n = 0;
    while (!mbar_try(bar, parity)) {
        if (++n > (1u << 20)) break;
    }
}
__device__ __forceinline__ void tma_2d(uint32_t dst, const CUtensorMap* tm, int c0, int c1, uint32_t bar) {
    asm volatile("cp.async.bulk.tensor.2d.shared::cluster.global.mbarrier::complete_tx::bytes [%0], [%1, {%3, %4}], [%2];"
                 ::"r"(dst), "l"(tm), "r"(bar), "r"(c0), "r"(c1) : "memory");
}
__device__ __forceinline__ void tma_3d(uint32_t dst, const CUtensorMap* tm, int c0, int c1, int c2, uint32_t bar) {
    asm volatile("cp.async.bulk.tensor.3d.shared::cluster.global.mbarrier::complete_tx::bytes [%0], [%1, {%3, %4, %5}], [%2];"
                 ::"r"(dst), "l"(tm), "r"(bar), "r"(c0), "r"(c1), "r"(c2) : "memory");
}
__device__ __forceinline__ void l2_prefetch(const void* p, uint32_t bytes) {
    asm volatile("cp.async.bulk.prefetch.L2.global [%0], %1;" ::"l"(p), "r"(bytes) : "memory");
}
__device__ __forceinline__ uint32_t l2_touch(const void* p) {
    uint32_t v;
    asm volatile("ld.global.L2::256B.b32 %0, [%1];" : "=r"(v) : "l"(p) : "memory");
    return v;
}
__device__ __forceinline__ void wg_fence() { asm volatile("wgmma.fence.sync.aligned;" ::: "memory"); }
__device__ __forceinline__ void wg_commit() { asm volatile("wgmma.commit_group.sync.aligned;" ::: "memory"); }
template <int N> __device__ __forceinline__ void wg_wait() { asm volatile("wgmma.wait_group.sync.aligned %0;" ::"n"(N) : "memory"); }
template <int N> __device__ __forceinline__ void fence_regs(float (&d)[N]) {
#pragma unroll
    for (int i = 0; i < N; i++) asm volatile("" : "+f"(d[i])::"memory");
}
__device__ __forceinline__ uint64_t mk_desc(uint32_t addr, uint32_t lbo, uint32_t sbo) {
    return (uint64_t)((addr & 0x3FFFF) >> 4) | ((uint64_t)(lbo >> 4) << 16) | ((uint64_t)(sbo >> 4) << 32) | (1ull << 62);
}
__device__ __forceinline__ uint32_t pack_bf16(float a, float b) {
    uint32_t r;
    asm("cvt.rn.bf16x2.f32 %0, %1, %2;" : "=r"(r) : "f"(b), "f"(a));
    return r;
}
__device__ __forceinline__ float ex2(float x) {
    float y;
    asm("ex2.approx.ftz.f32 %0, %1;" : "=f"(y) : "f"(x));
    return y;
}
template <int ID, int N> __device__ __forceinline__ void bar_sync() { asm volatile("bar.sync %0, %1;" ::"n"(ID), "n"(N) : "memory"); }
template <int ID, int N> __device__ __forceinline__ void bar_arrive() { asm volatile("bar.arrive %0, %1;" ::"n"(ID), "n"(N) : "memory"); }
__device__ __forceinline__ void sts128(uint32_t addr, uint32_t a, uint32_t b, uint32_t c, uint32_t d) {
    asm volatile("st.shared.v4.b32 [%0], {%1,%2,%3,%4};" ::"r"(addr), "r"(a), "r"(b), "r"(c), "r"(d) : "memory");
}
__device__ __forceinline__ void lds128(uint32_t addr, uint32_t (&r)[4]) {
    asm volatile("ld.shared.v4.b32 {%0,%1,%2,%3}, [%4];" : "=r"(r[0]), "=r"(r[1]), "=r"(r[2]), "=r"(r[3]) : "r"(addr) : "memory");
}

__device__ __forceinline__ void wgmma_ss_n256_tb(float (&d)[128], uint64_t da, uint64_t db, int sd) {
    asm volatile("{\n.reg .pred p;\nsetp.ne.b32 p, %130, 0;\n"
        "wgmma.mma_async.sync.aligned.m64n256k16.f32.bf16.bf16 "
        "{%0, %1, %2, %3, %4, %5, %6, %7, %8, %9, %10, %11, %12, %13, %14, %15, %16, %17, %18, %19, %20, %21, %22, %23, %24, %25, %26, %27, %28, %29, %30, %31, %32, %33, %34, %35, %36, %37, %38, %39, %40, %41, %42, %43, %44, %45, %46, %47, %48, %49, %50, %51, %52, %53, %54, %55, %56, %57, %58, %59, %60, %61, %62, %63, %64, %65, %66, %67, %68, %69, %70, %71, %72, %73, %74, %75, %76, %77, %78, %79, %80, %81, %82, %83, %84, %85, %86, %87, %88, %89, %90, %91, %92, %93, %94, %95, %96, %97, %98, %99, %100, %101, %102, %103, %104, %105, %106, %107, %108, %109, %110, %111, %112, %113, %114, %115, %116, %117, %118, %119, %120, %121, %122, %123, %124, %125, %126, %127}, "
        "%128, %129, p, 1, 1, 0, 1;\n}\n"
        : "+f"(d[0]), "+f"(d[1]), "+f"(d[2]), "+f"(d[3]), "+f"(d[4]), "+f"(d[5]), "+f"(d[6]), "+f"(d[7]), "+f"(d[8]), "+f"(d[9]), "+f"(d[10]), "+f"(d[11]), "+f"(d[12]), "+f"(d[13]), "+f"(d[14]), "+f"(d[15]), "+f"(d[16]), "+f"(d[17]), "+f"(d[18]), "+f"(d[19]), "+f"(d[20]), "+f"(d[21]), "+f"(d[22]), "+f"(d[23]), "+f"(d[24]), "+f"(d[25]), "+f"(d[26]), "+f"(d[27]), "+f"(d[28]), "+f"(d[29]), "+f"(d[30]), "+f"(d[31]), "+f"(d[32]), "+f"(d[33]), "+f"(d[34]), "+f"(d[35]), "+f"(d[36]), "+f"(d[37]), "+f"(d[38]), "+f"(d[39]), "+f"(d[40]), "+f"(d[41]), "+f"(d[42]), "+f"(d[43]), "+f"(d[44]), "+f"(d[45]), "+f"(d[46]), "+f"(d[47]), "+f"(d[48]), "+f"(d[49]), "+f"(d[50]), "+f"(d[51]), "+f"(d[52]), "+f"(d[53]), "+f"(d[54]), "+f"(d[55]), "+f"(d[56]), "+f"(d[57]), "+f"(d[58]), "+f"(d[59]), "+f"(d[60]), "+f"(d[61]), "+f"(d[62]), "+f"(d[63]), "+f"(d[64]), "+f"(d[65]), "+f"(d[66]), "+f"(d[67]), "+f"(d[68]), "+f"(d[69]), "+f"(d[70]), "+f"(d[71]), "+f"(d[72]), "+f"(d[73]), "+f"(d[74]), "+f"(d[75]), "+f"(d[76]), "+f"(d[77]), "+f"(d[78]), "+f"(d[79]), "+f"(d[80]), "+f"(d[81]), "+f"(d[82]), "+f"(d[83]), "+f"(d[84]), "+f"(d[85]), "+f"(d[86]), "+f"(d[87]), "+f"(d[88]), "+f"(d[89]), "+f"(d[90]), "+f"(d[91]), "+f"(d[92]), "+f"(d[93]), "+f"(d[94]), "+f"(d[95]), "+f"(d[96]), "+f"(d[97]), "+f"(d[98]), "+f"(d[99]), "+f"(d[100]), "+f"(d[101]), "+f"(d[102]), "+f"(d[103]), "+f"(d[104]), "+f"(d[105]), "+f"(d[106]), "+f"(d[107]), "+f"(d[108]), "+f"(d[109]), "+f"(d[110]), "+f"(d[111]), "+f"(d[112]), "+f"(d[113]), "+f"(d[114]), "+f"(d[115]), "+f"(d[116]), "+f"(d[117]), "+f"(d[118]), "+f"(d[119]), "+f"(d[120]), "+f"(d[121]), "+f"(d[122]), "+f"(d[123]), "+f"(d[124]), "+f"(d[125]), "+f"(d[126]), "+f"(d[127])
        : "l"(da), "l"(db), "r"(sd));
}
__device__ __forceinline__ void wgmma_rs_n128(float (&d)[64], uint32_t a0, uint32_t a1, uint32_t a2, uint32_t a3, uint64_t db, int sd) {
    asm volatile("{\n.reg .pred p;\nsetp.ne.b32 p, %69, 0;\n"
        "wgmma.mma_async.sync.aligned.m64n128k16.f32.bf16.bf16 "
        "{%0, %1, %2, %3, %4, %5, %6, %7, %8, %9, %10, %11, %12, %13, %14, %15, %16, %17, %18, %19, %20, %21, %22, %23, %24, %25, %26, %27, %28, %29, %30, %31, %32, %33, %34, %35, %36, %37, %38, %39, %40, %41, %42, %43, %44, %45, %46, %47, %48, %49, %50, %51, %52, %53, %54, %55, %56, %57, %58, %59, %60, %61, %62, %63}, "
        "{%64, %65, %66, %67}, %68, p, 1, 1, 0;\n}\n"
        : "+f"(d[0]), "+f"(d[1]), "+f"(d[2]), "+f"(d[3]), "+f"(d[4]), "+f"(d[5]), "+f"(d[6]), "+f"(d[7]), "+f"(d[8]), "+f"(d[9]), "+f"(d[10]), "+f"(d[11]), "+f"(d[12]), "+f"(d[13]), "+f"(d[14]), "+f"(d[15]), "+f"(d[16]), "+f"(d[17]), "+f"(d[18]), "+f"(d[19]), "+f"(d[20]), "+f"(d[21]), "+f"(d[22]), "+f"(d[23]), "+f"(d[24]), "+f"(d[25]), "+f"(d[26]), "+f"(d[27]), "+f"(d[28]), "+f"(d[29]), "+f"(d[30]), "+f"(d[31]), "+f"(d[32]), "+f"(d[33]), "+f"(d[34]), "+f"(d[35]), "+f"(d[36]), "+f"(d[37]), "+f"(d[38]), "+f"(d[39]), "+f"(d[40]), "+f"(d[41]), "+f"(d[42]), "+f"(d[43]), "+f"(d[44]), "+f"(d[45]), "+f"(d[46]), "+f"(d[47]), "+f"(d[48]), "+f"(d[49]), "+f"(d[50]), "+f"(d[51]), "+f"(d[52]), "+f"(d[53]), "+f"(d[54]), "+f"(d[55]), "+f"(d[56]), "+f"(d[57]), "+f"(d[58]), "+f"(d[59]), "+f"(d[60]), "+f"(d[61]), "+f"(d[62]), "+f"(d[63])
        : "r"(a0), "r"(a1), "r"(a2), "r"(a3), "l"(db), "r"(sd));
}
__device__ __forceinline__ void wgmma_rs_n128_tb(float (&d)[64], uint32_t a0, uint32_t a1, uint32_t a2, uint32_t a3, uint64_t db, int sd) {
    asm volatile("{\n.reg .pred p;\nsetp.ne.b32 p, %69, 0;\n"
        "wgmma.mma_async.sync.aligned.m64n128k16.f32.bf16.bf16 "
        "{%0, %1, %2, %3, %4, %5, %6, %7, %8, %9, %10, %11, %12, %13, %14, %15, %16, %17, %18, %19, %20, %21, %22, %23, %24, %25, %26, %27, %28, %29, %30, %31, %32, %33, %34, %35, %36, %37, %38, %39, %40, %41, %42, %43, %44, %45, %46, %47, %48, %49, %50, %51, %52, %53, %54, %55, %56, %57, %58, %59, %60, %61, %62, %63}, "
        "{%64, %65, %66, %67}, %68, p, 1, 1, 1;\n}\n"
        : "+f"(d[0]), "+f"(d[1]), "+f"(d[2]), "+f"(d[3]), "+f"(d[4]), "+f"(d[5]), "+f"(d[6]), "+f"(d[7]), "+f"(d[8]), "+f"(d[9]), "+f"(d[10]), "+f"(d[11]), "+f"(d[12]), "+f"(d[13]), "+f"(d[14]), "+f"(d[15]), "+f"(d[16]), "+f"(d[17]), "+f"(d[18]), "+f"(d[19]), "+f"(d[20]), "+f"(d[21]), "+f"(d[22]), "+f"(d[23]), "+f"(d[24]), "+f"(d[25]), "+f"(d[26]), "+f"(d[27]), "+f"(d[28]), "+f"(d[29]), "+f"(d[30]), "+f"(d[31]), "+f"(d[32]), "+f"(d[33]), "+f"(d[34]), "+f"(d[35]), "+f"(d[36]), "+f"(d[37]), "+f"(d[38]), "+f"(d[39]), "+f"(d[40]), "+f"(d[41]), "+f"(d[42]), "+f"(d[43]), "+f"(d[44]), "+f"(d[45]), "+f"(d[46]), "+f"(d[47]), "+f"(d[48]), "+f"(d[49]), "+f"(d[50]), "+f"(d[51]), "+f"(d[52]), "+f"(d[53]), "+f"(d[54]), "+f"(d[55]), "+f"(d[56]), "+f"(d[57]), "+f"(d[58]), "+f"(d[59]), "+f"(d[60]), "+f"(d[61]), "+f"(d[62]), "+f"(d[63])
        : "r"(a0), "r"(a1), "r"(a2), "r"(a3), "l"(db), "r"(sd));
}
__device__ __forceinline__ void wgmma_rs_n64_tb(float (&d)[32], uint32_t a0, uint32_t a1, uint32_t a2, uint32_t a3, uint64_t db, int sd) {
    asm volatile("{\n.reg .pred p;\nsetp.ne.b32 p, %37, 0;\n"
        "wgmma.mma_async.sync.aligned.m64n64k16.f32.bf16.bf16 "
        "{%0, %1, %2, %3, %4, %5, %6, %7, %8, %9, %10, %11, %12, %13, %14, %15, %16, %17, %18, %19, %20, %21, %22, %23, %24, %25, %26, %27, %28, %29, %30, %31}, "
        "{%32, %33, %34, %35}, %36, p, 1, 1, 1;\n}\n"
        : "+f"(d[0]), "+f"(d[1]), "+f"(d[2]), "+f"(d[3]), "+f"(d[4]), "+f"(d[5]), "+f"(d[6]), "+f"(d[7]), "+f"(d[8]), "+f"(d[9]), "+f"(d[10]), "+f"(d[11]), "+f"(d[12]), "+f"(d[13]), "+f"(d[14]), "+f"(d[15]), "+f"(d[16]), "+f"(d[17]), "+f"(d[18]), "+f"(d[19]), "+f"(d[20]), "+f"(d[21]), "+f"(d[22]), "+f"(d[23]), "+f"(d[24]), "+f"(d[25]), "+f"(d[26]), "+f"(d[27]), "+f"(d[28]), "+f"(d[29]), "+f"(d[30]), "+f"(d[31])
        : "r"(a0), "r"(a1), "r"(a2), "r"(a3), "l"(db), "r"(sd));
}

__global__ void __launch_bounds__(384, 1) fused_gqa_kernel(const __grid_constant__ Params P) {
    extern __shared__ uint8_t smem_raw[];
    const uint32_t base = (smem_u32(smem_raw) + 1023u) & ~1023u;
    const uint32_t smR = base;
    const uint32_t smS = base + R_BYTES;
    const uint32_t bars = smS + NSTAGE * STAGE_BYTES;
    const uint32_t prog = bars + 8 * (2 * NSTAGE + 10);
    const uint32_t barP = prog + 16;
    const int tid = threadIdx.x;
    const int wid = __shfl_sync(0xffffffffu, tid >> 5, 0);
    const int lane = tid & 31;

    const int cta = blockIdx.x;
    const int blk = cta >> 6;
    const int hp = (cta >> 3) & 7;
    const int b = cta & 7;
    const int grp = blk * 8 + b;

    if (tid == 0) {
        TS(0);
        for (int i = 0; i < NSTAGE; i++) {
            mbar_init(bars + 8 * i, 1);
            mbar_init(bars + 8 * (NSTAGE + i), 8);
        }
        for (int i = 0; i < 10; i++) { mbar_init(bars + 8 * (2 * NSTAGE + i), 4); mbar_init(barP + 8 * i, 1); mbar_init(barP + 80 + 8 * i, 4); }
        asm volatile("st.volatile.shared.u32 [%0], %1;" ::"r"(prog), "r"(0) : "memory");
        asm volatile("fence.mbarrier_init.release.cluster;" ::: "memory");
        asm volatile("fence.proxy.async.shared::cta;" ::: "memory");
    }
    __syncthreads();

    if (wid >= 8) {
        asm volatile("setmaxnreg.dec.sync.aligned.u32 40;");
        auto wo_stream = [&](int w) {
            int slot = 4;
            for (int q = 0; q < 18; q++) {
                if (q < NSTAGE) mbar_wait(bars + 8 * (NSTAGE + slot), q == 0);
                else mbar_wait(barP + 80 + 8 * (w * 5 + slot), ((q >= 10) && (q < 15)) ? 1 : 0);
                const uint32_t fb = barP + 8 * (w * 5 + slot);
                const uint32_t dst = smS + slot * STAGE_BYTES + w * 16384;
                mbar_expect_tx(fb, 16384);
                if (q < 16) tma_3d(dst, &P.wo[blk], 0, hp * 512 + ((q & 7) ^ (w * 2)) * 64, (q >> 3) * 4 + w * 2, fb);
                else tma_2d(dst, &P.wo8[blk], 512, hp * 512 + (q - 16) * 256 + w * 128, fb);
                if (++slot == NSTAGE) slot = 0;
            }
        };
        if (wid == 8) {
            if (lane == 0) {
                int slot = 0, ph = 1;
                for (int s = 0; s < N_WQ; s++) {
                    const uint32_t fb = bars + 8 * slot;
                    mbar_wait(bars + 8 * (NSTAGE + slot), ph);
                    const uint32_t dst = smS + slot * STAGE_BYTES;
                    mbar_expect_tx(fb, (s & 1) ? STAGE_BYTES : STAGE_BYTES + 8192);
                    if (!(s & 1)) tma_2d(smR + ((s >> 1) & 7) * 8192, &P.x[blk], (s >> 1) * 64, b * 64, fb);
#pragma unroll
                    for (int p = 0; p < 4; p++) {
                        const int w = p >> 1, j = p & 1;
                        tma_3d(dst + p * 8192, &P.wq[blk], 0, s * 32, hp * 8 + j * 4 + w * 2, fb);
                    }
                    if (++slot == NSTAGE) { slot = 0; ph ^= 1; }
                }
                for (int i = 0; i < 16; i++) {
                    const uint32_t fb = bars + 8 * slot;
                    mbar_wait(bars + 8 * (NSTAGE + slot), ph);
                    const uint32_t dst = smS + slot * STAGE_BYTES;
                    mbar_expect_tx(fb, STAGE_BYTES);
                    const int row = (b * kHkv + hp * 2) * kSk + (i >> 1) * 128;
                    tma_3d(dst, (i & 1) ? &P.v[blk] : &P.k[blk], 0, row, 0, fb);
                    asm volatile("st.volatile.shared.u32 [%0], %1;" ::"r"(prog), "r"(i + 1) : "memory");
                    if (++slot == NSTAGE) { slot = 0; ph ^= 1; }
                }
                wo_stream(0);
            }
        } else if (wid == 11) {
            if (PF_DIST > 0) {
                uint32_t sink = 0;
                mbar_wait(bars, 0);
                if (PF_WQ) {
                    const char* wqs = (const char*)(P.wqp[blk] + hp * 512) + (size_t)(160 + b * 52) * 8192;
#pragma unroll
                    for (int h = 0; h < 2; h++) {
#pragma unroll
                        for (int j = 0; j < 4; j++) {
                            const int e = (h * 4 + j) * 32 + lane;
                            if (e < 208) sink |= l2_touch(wqs + (size_t)(e >> 2) * 8192 + (e & 3) * 256);
                        }
                        if (sink == 0x9E3779B9u) asm volatile("st.volatile.shared.u32 [%0], %1;" ::"r"(prog + 4), "r"(sink) : "memory");
                    }
                }
                const char* kbase = (const char*)(P.kp[blk] + (size_t)(b * kHkv + hp * 2) * kSk * kDh);
                const char* vbase = (const char*)(P.vp[blk] + (size_t)(b * kHkv + hp * 2) * kSk * kDh);
                const char* wos = (const char*)(P.wop[blk] + (size_t)hp * 512 * kD) + (size_t)b * 73728;
#define WO_POS 16
#define WO_FULL 0
                for (int ii = 0; ii < 17; ii++) {
                    const bool is_wo = (ii == WO_POS);
                    const int i = (ii > WO_POS) ? ii - 1 : ii;
                    if (i >= PF_DIST) {
                        uint32_t pr, n = 0;
                        while (true) {
                            asm volatile("ld.volatile.shared.u32 %0, [%1];" : "=r"(pr) : "r"(prog) : "memory");
                            if ((int)pr + PF_DIST >= i) break;
                            if (++n > (1u << 22)) break;
                            __nanosleep(100);
                        }
                    }
                    if (!is_wo) {
                        const char* p = ((i & 1) ? vbase : kbase) + (size_t)(i >> 1) * 32768 + lane * 256;
#pragma unroll
                        for (int j = 0; j < 4; j++) sink |= l2_touch(p + j * 8192);
                        if (sink == 0x9E3779B9u) asm volatile("st.volatile.shared.u32 [%0], %1;" ::"r"(prog + 4), "r"(sink) : "memory");
                    } else {
                        for (int h = 0; h < (WO_FULL ? 24 : 3); h++) {
                            const char* p = (WO_FULL ? (wos - (size_t)b * 73728 + (size_t)((h + 3 * b) % 24) * 24576) : (wos + (size_t)h * 24576)) + lane * 256;
#pragma unroll
                            for (int j = 0; j < 3; j++) sink |= l2_touch(p + j * 8192);
                            if (sink == 0x9E3779B9u) asm volatile("st.volatile.shared.u32 [%0], %1;" ::"r"(prog + 4), "r"(sink) : "memory");
                        }
                    }
                }
            }
            if (lane == 0) wo_stream(1);
        } else {
            const int hw = wid - 9;
            for (int k = 0; k < 3; k++) {
                mbar_wait(bars + 8 * (2 * NSTAGE + hw * 5 + k), 0);
                const int c = (k < 2) ? (2 * k + hw) : 4;
                asm volatile("fence.acq_rel.gpu;" ::: "memory");
                asm volatile("red.relaxed.gpu.global.add.u32 [%0], 1;" ::"l"(&g_cnt[(grp * 9 + c) * 32 + lane]) : "memory");
            }
        }
    } else {
        asm volatile("setmaxnreg.inc.sync.aligned.u32 232;");
        const int w = wid >> 2;
        const int t = tid & 127;
        int slot = 0, ph = 0;
        uint32_t qf[8][4];
        const uint32_t stash = smR + (1 + w) * 16384 + t * 16;
        {
            float acc[128];
            int pslot = 0;
            for (int s = 0; s < N_WQ; s++) {
                mbar_wait(bars + 8 * slot, ph);
                if (tid == 0 && s == 0) TS(20);
                if (tid == 0 && s == 5) TS(21);
                if (tid == 0 && s == 10) TS(22);
                const uint64_t da = mk_desc(smR + ((s >> 1) & 7) * 8192 + (s & 1) * 64, 16, 1024);
                const uint64_t db = mk_desc(smS + slot * STAGE_BYTES + w * 16384, 4096, 1024);
                wg_fence();
                wgmma_ss_n256_tb(acc, da, db, s != 0);
                wgmma_ss_n256_tb(acc, da + 2, db + 128, 1);
                wg_commit();
                wg_wait<0>();
                if (lane == 0) mbar_arrive(bars + 8 * (NSTAGE + slot));
                pslot = slot;
                if (++slot == NSTAGE) { slot = 0; ph ^= 1; }
            }
            fence_regs(acc);
            if (tid == 0) TS(1);
#pragma unroll
            for (int kk = 0; kk < 8; kk++) {
#pragma unroll
                for (int i = 0; i < 4; i++) qf[kk][i] = pack_bf16(acc[8 * kk + 2 * i], acc[8 * kk + 2 * i + 1]);
                sts128(stash + kk * 2048,
                       pack_bf16(acc[64 + 8 * kk + 0], acc[64 + 8 * kk + 1]), pack_bf16(acc[64 + 8 * kk + 2], acc[64 + 8 * kk + 3]),
                       pack_bf16(acc[64 + 8 * kk + 4], acc[64 + 8 * kk + 5]), pack_bf16(acc[64 + 8 * kk + 6], acc[64 + 8 * kk + 7]));
            }
        }
        if (w == 1) bar_arrive<5, 256>();
        const float sc = 0.08838834764831845f * 1.4426950408889634f;
        uint32_t af[32][4];
#pragma unroll
        for (int u = 0; u < 2; u++) {
            {
                if (u == 1) {
#pragma unroll
                    for (int kk = 0; kk < 8; kk++) lds128(stash + kk * 2048, qf[kk]);
                }
                float o[64], s[64];
                float m0 = -INFINITY, m1 = -INFINITY, l0 = 0.f, l1 = 0.f;
                uint32_t pf[8][4];
#pragma unroll
                for (int i = 0; i < 64; i++) { o[i] = 0.f; s[i] = 0.f; }
#pragma unroll
                for (int i = 0; i < 32; i++) pf[i >> 2][i & 3] = 0u;
#pragma unroll 1
                for (int tt = 0; tt <= 4; tt++) {
                    int vslot = slot;
                    if (tt > 0) {
                        mbar_wait(bars + 8 * slot, ph);
                        if (++slot == NSTAGE) { slot = 0; ph ^= 1; }
                    }
                    if (tt < 4) mbar_wait(bars + 8 * slot, ph);
                    if (tid == 0) TS(32 + u * 20 + tt * 4);
                    if (w == 0) bar_sync<5, 256>(); else bar_sync<6, 256>();
                    wg_fence();
                    if (tt > 0) {
                        const uint64_t db = mk_desc(smS + vslot * STAGE_BYTES, 16384, 1024);
#pragma unroll
                        for (int kk = 0; kk < 8; kk++)
                            wgmma_rs_n128_tb(o, pf[kk][0], pf[kk][1], pf[kk][2], pf[kk][3], db + kk * 128, (tt > 1) || (kk != 0));
                        wg_commit();
                    }
                    if (tt < 4) {
                        const uint64_t db = mk_desc(smS + slot * STAGE_BYTES, 16, 1024);
#pragma unroll
                        for (int kk = 0; kk < 8; kk++)
                            wgmma_rs_n128(s, qf[kk][0], qf[kk][1], qf[kk][2], qf[kk][3], db + (kk >> 2) * 1024 + (kk & 3) * 2, kk != 0);
                        wg_commit();
                    }
                    if (w == 0) bar_arrive<6, 256>(); else if (!(u == 1 && tt == 4)) bar_arrive<5, 256>();
                    if (tid == 0) TS(32 + u * 20 + tt * 4 + 1);
                    wg_wait<0>();
                    fence_regs(o);
                    fence_regs(s);
                    if (tid == 0) TS(32 + u * 20 + tt * 4 + 2);
                    if (tt > 0 && lane == 0) mbar_arrive(bars + 8 * (NSTAGE + vslot));
                    if (tt == 4) break;
                    if (lane == 0) mbar_arrive(bars + 8 * (NSTAGE + slot));
                    if (++slot == NSTAGE) { slot = 0; ph ^= 1; }
                    float mx0 = s[0], mx1 = s[2];
#pragma unroll
                    for (int j = 0; j < 16; j++) {
                        mx0 = fmaxf(mx0, fmaxf(s[4 * j], s[4 * j + 1]));
                        mx1 = fmaxf(mx1, fmaxf(s[4 * j + 2], s[4 * j + 3]));
                    }
                    mx0 = fmaxf(mx0, __shfl_xor_sync(0xffffffffu, mx0, 1));
                    mx1 = fmaxf(mx1, __shfl_xor_sync(0xffffffffu, mx1, 1));
                    mx0 = fmaxf(mx0, __shfl_xor_sync(0xffffffffu, mx0, 2));
                    mx1 = fmaxf(mx1, __shfl_xor_sync(0xffffffffu, mx1, 2));
                    const float mn0 = fmaxf(m0, mx0), mn1 = fmaxf(m1, mx1);
                    const float al0 = ex2((m0 - mn0) * sc), al1 = ex2((m1 - mn1) * sc);
                    m0 = mn0; m1 = mn1;
                    const float ms0 = mn0 * sc, ms1 = mn1 * sc;
                    float rs0 = 0.f, rs1 = 0.f;
#pragma unroll
                    for (int j = 0; j < 16; j++) {
                        const float p0 = ex2(fmaf(s[4 * j], sc, -ms0)), p1 = ex2(fmaf(s[4 * j + 1], sc, -ms0));
                        const float p2 = ex2(fmaf(s[4 * j + 2], sc, -ms1)), p3 = ex2(fmaf(s[4 * j + 3], sc, -ms1));
                        rs0 += p0 + p1; rs1 += p2 + p3;
                        pf[j >> 1][(j & 1) * 2] = pack_bf16(p0, p1);
                        pf[j >> 1][(j & 1) * 2 + 1] = pack_bf16(p2, p3);
                    }
                    l0 = l0 * al0 + rs0; l1 = l1 * al1 + rs1;
                    if (tt > 0) {
#pragma unroll
                        for (int j = 0; j < 16; j++) { o[4 * j] *= al0; o[4 * j + 1] *= al0; o[4 * j + 2] *= al1; o[4 * j + 3] *= al1; }
                    }
                    if (tid == 0) TS(32 + u * 20 + tt * 4 + 3);
                }
                if (tid == 0) TS(2 + u);
                l0 += __shfl_xor_sync(0xffffffffu, l0, 1);
                l1 += __shfl_xor_sync(0xffffffffu, l1, 1);
                l0 += __shfl_xor_sync(0xffffffffu, l0, 2);
                l1 += __shfl_xor_sync(0xffffffffu, l1, 2);
                const float i0 = 1.f / l0, i1 = 1.f / l1;
                const uint32_t zown = smR + ((u == 0) ? (w ? 3 : 0) : (w ? 2 : 1)) * 16384 + t * 16;
#pragma unroll
                for (int kk = 0; kk < 8; kk++) {
                    af[16 + kk][0] = pack_bf16(o[8 * kk + 0] * i0, o[8 * kk + 1] * i0);
                    af[16 + kk][1] = pack_bf16(o[8 * kk + 2] * i1, o[8 * kk + 3] * i1);
                    af[16 + kk][2] = pack_bf16(o[8 * kk + 4] * i0, o[8 * kk + 5] * i0);
                    af[16 + kk][3] = pack_bf16(o[8 * kk + 6] * i1, o[8 * kk + 7] * i1);
                    sts128(zown + kk * 2048, af[16 + kk][0], af[16 + kk][1], af[16 + kk][2], af[16 + kk][3]);
                }
            }
        }
        if (w == 0) bar_arrive<7, 256>(); else bar_arrive<8, 256>();
        {
#pragma unroll
            for (int kk = 0; kk < 8; kk++) {
                lds128(smR + (w ? 3 : 0) * 16384 + kk * 2048 + t * 16, af[kk]);
                lds128(smR + (w ? 0 : 3) * 16384 + kk * 2048 + t * 16, af[8 + kk]);
            }
            uint2* dst0 = g_part + (size_t)(grp * 80 + 2 * w * 8 + hp) * 1024 + t;
            uint2* dst8 = g_part + (size_t)(grp * 80 + 64 + hp * 2 + w) * 1024 + t;
#pragma unroll
            for (int ps = 0; ps < 2; ps++) {
                float acc[64];
#pragma unroll
                for (int i = 0; i < 64; i++) acc[i] = 0.f;
#pragma unroll
                for (int st = 0; st < 8; st++) {
                    if (ps == 0 && st == 5) {
                        if (w == 0) bar_sync<8, 256>(); else bar_sync<7, 256>();
#pragma unroll
                        for (int kk = 0; kk < 8; kk++) lds128(smR + (w ? 1 : 2) * 16384 + kk * 2048 + t * 16, af[24 + kk]);
                    }
                    mbar_wait(barP + 8 * (w * 5 + slot), ((ps * 8 + st) / 5) & 1);
                    if (tid == 0) TS(80 + ps * 16 + 2 * st);
                    const uint64_t db = mk_desc(smS + slot * STAGE_BYTES + w * 16384, 8192, 1024);
                    wg_fence();
#pragma unroll
                    for (int kk = 0; kk < 4; kk++)
                        wgmma_rs_n128_tb(acc, af[st * 4 + kk][0], af[st * 4 + kk][1], af[st * 4 + kk][2], af[st * 4 + kk][3], db + kk * 128, (st | kk) != 0);
                    wg_commit();
                    wg_wait<0>();
                    if (lane == 0) mbar_arrive(barP + 80 + 8 * (w * 5 + slot));
                    if (tid == 0) TS(80 + ps * 16 + 2 * st + 1);
                    if (++slot == NSTAGE) slot = 0;
                }
                fence_regs(acc);
                uint2* dst = dst0 + (size_t)ps * 32 * 1024;
#pragma unroll
                for (int j = 0; j < 16; j++)
                    __stcg(dst + (j >> 3) * 8192 + (j & 7) * 128, make_uint2(pack_bf16(acc[4 * j], acc[4 * j + 1]), pack_bf16(acc[4 * j + 2], acc[4 * j + 3])));
                __syncwarp();
                if (lane == 0) mbar_arrive(bars + 8 * (2 * NSTAGE + w * 5 + ps));
                if (tid == 0) TS(4 + ps);
            }
            {
                float acc[32];
#pragma unroll
                for (int i = 0; i < 32; i++) acc[i] = 0.f;
#pragma unroll
                for (int st = 0; st < 2; st++) {
                    mbar_wait(barP + 8 * (w * 5 + slot), 1);
                    const uint64_t db = mk_desc(smS + slot * STAGE_BYTES + w * 16384, 8192, 1024);
                    wg_fence();
#pragma unroll
                    for (int kk = 0; kk < 8; kk++)
                        wgmma_rs_n64_tb(acc, af[st * 16 + kk][0], af[st * 16 + kk][1], af[st * 16 + kk][2], af[st * 16 + kk][3], db + kk * 128, (st | kk) != 0);
                    wg_commit();
                    if (++slot == NSTAGE) slot = 0;
                }
                wg_wait<0>();
                fence_regs(acc);
#pragma unroll
                for (int j = 0; j < 8; j++)
                    __stcg(dst8 + j * 128, make_uint2(pack_bf16(acc[4 * j], acc[4 * j + 1]), pack_bf16(acc[4 * j + 2], acc[4 * j + 3])));
                __syncwarp();
                if (lane == 0) mbar_arrive(bars + 8 * (2 * NSTAGE + w * 5 + 2));
                if (tid == 0) TS(8);
            }
        }
        {
            const int nch = (w == 0) ? 3 : 2;
            if (lane < nch) {
                const int c = (lane < 2) ? (2 * lane + w) : 4;
                const unsigned need = (lane < 2) ? 8u : 16u;
                unsigned* cp = &g_cnt[(grp * 9 + c) * 32 + hp * 4 + (wid & 3)];
                unsigned v, n = 0;
                while (true) {
                    asm volatile("ld.acquire.gpu.global.u32 %0, [%1];" : "=r"(v) : "l"(cp) : "memory");
                    if (v >= need) break;
                    if (++n > (1u << 21)) break;
                }
                *cp = 0;
            }
            __syncwarp();
            if (tid == 0) TS(18);
            __nv_bfloat16* orow = P.out + (size_t)(b * 64 + (t >> 5) * 16 + (lane >> 2)) * (2 * kD) + blk * kD + hp * 8 + (lane & 3) * 2;
            const uint2* src = g_part + ((size_t)(grp * 80 + 2 * w * 8) * 8 + hp) * 128 + t;
            uint2 v[4][8];
#pragma unroll
            for (int k = 0; k < 4; k++)
#pragma unroll
                for (int i = 0; i < 8; i++) v[k][i] = __ldcg(src + (size_t)((k >> 1) * 32 + (k & 1) * 8 + i) * 1024);
            if (w == 0) {
                const uint2* src8 = g_part + ((size_t)(grp * 80 + 64) * 8 + hp) * 128 + t;
                uint2 u[16];
#pragma unroll
                for (int i = 0; i < 16; i++) u[i] = __ldcg(src8 + (size_t)i * 1024);
                float a0 = 0.f, a1 = 0.f, a2 = 0.f, a3 = 0.f;
#pragma unroll
                for (int i = 0; i < 16; i++) {
                    a0 += __uint_as_float(u[i].x << 16); a1 += __uint_as_float(u[i].x & 0xffff0000u);
                    a2 += __uint_as_float(u[i].y << 16); a3 += __uint_as_float(u[i].y & 0xffff0000u);
                }
                *(uint32_t*)(orow + 512) = pack_bf16(a0, a1);
                *(uint32_t*)(orow + 512 + 8 * 2 * kD) = pack_bf16(a2, a3);
            }
#pragma unroll
            for (int k = 0; k < 4; k++) {
                float a0 = 0.f, a1 = 0.f, a2 = 0.f, a3 = 0.f;
#pragma unroll
                for (int i = 0; i < 8; i++) {
                    a0 += __uint_as_float(v[k][i].x << 16); a1 += __uint_as_float(v[k][i].x & 0xffff0000u);
                    a2 += __uint_as_float(v[k][i].y << 16); a3 += __uint_as_float(v[k][i].y & 0xffff0000u);
                }
                *(uint32_t*)(orow + ((k >> 1) * 4 + 2 * w + (k & 1)) * 64) = pack_bf16(a0, a1);
                *(uint32_t*)(orow + ((k >> 1) * 4 + 2 * w + (k & 1)) * 64 + 8 * 2 * kD) = pack_bf16(a2, a3);
            }
            if (tid == 0) TS(19);
        }
    }
}

typedef CUresult (*EncodeFn)(CUtensorMap*, CUtensorMapDataType, cuuint32_t, void*, const cuuint64_t*, const cuuint64_t*,
                             const cuuint32_t*, const cuuint32_t*, CUtensorMapInterleave, CUtensorMapSwizzle,
                             CUtensorMapL2promotion, CUtensorMapFloatOOBfill);

void make_map(EncodeFn fn, CUtensorMap* m, const void* ptr, uint64_t cols, uint64_t rows, uint32_t box_rows) {
    cuuint64_t dims[2] = {cols, rows};
    cuuint64_t strides[1] = {cols * 2};
    cuuint32_t box[2] = {64, box_rows};
    cuuint32_t es[2] = {1, 1};
    fn(m, CU_TENSOR_MAP_DATA_TYPE_BFLOAT16, 2, const_cast<void*>(ptr), dims, strides, box, es, CU_TENSOR_MAP_INTERLEAVE_NONE,
       CU_TENSOR_MAP_SWIZZLE_128B, CU_TENSOR_MAP_L2_PROMOTION_L2_256B, CU_TENSOR_MAP_FLOAT_OOB_FILL_NONE);
}

void make_map3(EncodeFn fn, CUtensorMap* m, const void* ptr, uint64_t cols, uint64_t rows, uint32_t box_rows, uint32_t box_groups) {
    cuuint64_t dims[3] = {64, rows, cols / 64};
    cuuint64_t strides[2] = {cols * 2, 128};
    cuuint32_t box[3] = {64, box_rows, box_groups};
    cuuint32_t es[3] = {1, 1, 1};
    fn(m, CU_TENSOR_MAP_DATA_TYPE_BFLOAT16, 3, const_cast<void*>(ptr), dims, strides, box, es, CU_TENSOR_MAP_INTERLEAVE_NONE,
       CU_TENSOR_MAP_SWIZZLE_128B, CU_TENSOR_MAP_L2_PROMOTION_L2_256B, CU_TENSOR_MAP_FLOAT_OOB_FILL_NONE);
}

}

extern "C" void kernel_launch(void* const* d_in, const int* in_sizes, int n_in, void* d_out, int out_size) {
    static EncodeFn enc = nullptr;
    if (!enc) {
        void* fn = nullptr;
        cudaDriverEntryPointQueryResult st;
        cudaGetDriverEntryPoint("cuTensorMapEncodeTiled", &fn, cudaEnableDefault, &st);
        enc = (EncodeFn)fn;
        cudaFuncSetAttribute(fused_gqa_kernel, cudaFuncAttributeMaxDynamicSharedMemorySize, SMEM_BYTES);
    }
    Params P;
    for (int blk = 0; blk < 2; blk++) {
        const void* x = d_in[blk * 5 + 0];
        const void* k = d_in[blk * 5 + 1];
        const void* v = d_in[blk * 5 + 2];
        const void* wq = d_in[blk * 5 + 3];
        const void* wo = d_in[blk * 5 + 4];
        make_map(enc, &P.x[blk], x, kD, kB * kSq, 64);
        make_map3(enc, &P.wq[blk], wq, kHq * kDh, kD, 32, 2);
        make_map3(enc, &P.k[blk], k, kDh, (uint64_t)kB * kHkv * kSk, 128, 2);
        make_map3(enc, &P.v[blk], v, kDh, (uint64_t)kB * kHkv * kSk, 128, 2);
        make_map3(enc, &P.wo[blk], wo, kD, kHq * kDh, 64, 2);
        make_map(enc, &P.wo8[blk], wo, kD, kHq * kDh, 128);
        P.wqp[blk] = (const __nv_bfloat16*)wq;
        P.kp[blk] = (const __nv_bfloat16*)k;
        P.vp[blk] = (const __nv_bfloat16*)v;
        P.wop[blk] = (const __nv_bfloat16*)wo;
    }
    P.out = (__nv_bfloat16*)d_out;
    fused_gqa_kernel<<<128, 384, SMEM_BYTES>>>(P);
}
```

```cpp
#include <cuda_runtime.h>
#include <cuda_bf16.h>
#include <cuda.h>
#include <stdint.h>

namespace {

constexpr int kB = 8, kSq = 64, kD = 576, kHq = 32, kHkv = 16, kSk = 512, kDh = 128;
constexpr int NSTAGE = 5;
constexpr int STAGE_BYTES = 32768;
constexpr int R_BYTES = 65536;
constexpr int SMEM_BYTES = R_BYTES + NSTAGE * STAGE_BYTES + 1024   + 512  ;
constexpr int N_WQ = 18;
#define PF_DIST_V 6
#define OP_WAIT0 1
#define QP_WAIT0 1
#define PF_WQ 0
#define PF_SLEEP 1000
constexpr int PF_DIST = PF_DIST_V;

struct __align__(64) Params {
    CUtensorMap x[2], wq[2], k[2], v[2], wo[2], wo8[2];
    const __nv_bfloat16* wqp[2];
    const __nv_bfloat16* kp[2];
    const __nv_bfloat16* vp[2];
    const __nv_bfloat16* wop[2];
    __nv_bfloat16* out;
};

__device__ uint2 g_part[16 * 80 * 8 * 128];
__device__ unsigned int g_cnt[16 * 9 * 32];
#define TS(k) do {} while (0)

__device__ __forceinline__ uint32_t smem_u32(const void* p) { return (uint32_t)__cvta_generic_to_shared(p); }
__device__ __forceinline__ void mbar_init(uint32_t bar, int cnt) {
    asm volatile("mbarrier.init.shared::cta.b64 [%0], %1;" ::"r"(bar), "r"(cnt));
}
__device__ __forceinline__ void mbar_expect_tx(uint32_t bar, uint32_t bytes) {
    asm volatile("mbarrier.arrive.expect_tx.shared::cta.b64 _, [%0], %1;" ::"r"(bar), "r"(bytes) : "memory");
}
__device__ __forceinline__ void mbar_arrive(uint32_t bar) {
    asm volatile("mbarrier.arrive.shared::cta.b64 _, [%0];" ::"r"(bar) : "memory");
}
__device__ __forceinline__ bool mbar_try(uint32_t bar, uint32_t parity) {
    uint32_t ok;
    asm volatile("{\n.reg .pred p;\nmbarrier.try_wait.parity.shared::cta.b64 p, [%1], %2;\nselp.u32 %0, 1, 0, p;\n}\n"
                 : "=r"(ok) : "r"(bar), "r"(parity) : "memory");
    return ok != 0;
}
__device__ __forceinline__ bool mbar_test(uint32_t bar, uint32_t parity) {
    uint32_t ok;
    asm volatile("{\n.reg .pred p;\nmbarrier.test_wait.parity.shared::cta.b64 p, [%1], %2;\nselp.u32 %0, 1, 0, p;\n}\n"
                 : "=r"(ok) : "r"(bar), "r"(parity) : "memory");
    return ok != 0;
}
__device__ __forceinline__ void mbar_wait(uint32_t bar, uint32_t parity) {
    if (mbar_try(bar, parity)) return;
    uint32_t n = 0;
    while (!mbar_try(bar, parity)) {
        if (++n > (1u << 20)) break;
    }
}
__device__ __forceinline__ void tma_2d(uint32_t dst, const CUtensorMap* tm, int c0, int c1, uint32_t bar) {
    asm volatile("cp.async.bulk.tensor.2d.shared::cluster.global.mbarrier::complete_tx::bytes [%0], [%1, {%3, %4}], [%2];"
                 ::"r"(dst), "l"(tm), "r"(bar), "r"(c0), "r"(c1) : "memory");
}
__device__ __forceinline__ void tma_3d(uint32_t dst, const CUtensorMap* tm, int c0, int c1, int c2, uint32_t bar) {
    asm volatile("cp.async.bulk.tensor.3d.shared::cluster.global.mbarrier::complete_tx::bytes [%0], [%1, {%3, %4, %5}], [%2];"
                 ::"r"(dst), "l"(tm), "r"(bar), "r"(c0), "r"(c1), "r"(c2) : "memory");
}
__device__ __forceinline__ void l2_prefetch(const void* p, uint32_t bytes) {
    asm volatile("cp.async.bulk.prefetch.L2.global [%0], %1;" ::"l"(p), "r"(bytes) : "memory");
}
__device__ __forceinline__ uint32_t l2_touch(const void* p) {
    uint32_t v;
    asm volatile("ld.global.L2::256B.b32 %0, [%1];" : "=r"(v) : "l"(p) : "memory");
    return v;
}
__device__ __forceinline__ void wg_fence() { asm volatile("wgmma.fence.sync.aligned;" ::: "memory"); }
__device__ __forceinline__ void wg_commit() { asm volatile("wgmma.commit_group.sync.aligned;" ::: "memory"); }
template <int N> __device__ __forceinline__ void wg_wait() { asm volatile("wgmma.wait_group.sync.aligned %0;" ::"n"(N) : "memory"); }
template <int N> __device__ __forceinline__ void fence_regs(float (&d)[N]) {
#pragma unroll
    for (int i = 0; i < N; i++) asm volatile("" : "+f"(d[i])::"memory");
}
__device__ __forceinline__ uint64_t mk_desc(uint32_t addr, uint32_t lbo, uint32_t sbo) {
    return (uint64_t)((addr & 0x3FFFF) >> 4) | ((uint64_t)(lbo >> 4) << 16) | ((uint64_t)(sbo >> 4) << 32) | (1ull << 62);
}
__device__ __forceinline__ uint32_t pack_bf16(float a, float b) {
    uint32_t r;
    asm("cvt.rn.bf16x2.f32 %0, %1, %2;" : "=r"(r) : "f"(b), "f"(a));
    return r;
}
__device__ __forceinline__ float ex2(float x) {
    float y;
    asm("ex2.approx.ftz.f32 %0, %1;" : "=f"(y) : "f"(x));
    return y;
}
template <int ID, int N> __device__ __forceinline__ void bar_sync() { asm volatile("bar.sync %0, %1;" ::"n"(ID), "n"(N) : "memory"); }
template <int ID, int N> __device__ __forceinline__ void bar_arrive() { asm volatile("bar.arrive %0, %1;" ::"n"(ID), "n"(N) : "memory"); }
__device__ __forceinline__ void sts128(uint32_t addr, uint32_t a, uint32_t b, uint32_t c, uint32_t d) {
    asm volatile("st.shared.v4.b32 [%0], {%1,%2,%3,%4};" ::"r"(addr), "r"(a), "r"(b), "r"(c), "r"(d) : "memory");
}
__device__ __forceinline__ void lds128(uint32_t addr, uint32_t (&r)[4]) {
    asm volatile("ld.shared.v4.b32 {%0,%1,%2,%3}, [%4];" : "=r"(r[0]), "=r"(r[1]), "=r"(r[2]), "=r"(r[3]) : "r"(addr) : "memory");
}

__device__ __forceinline__ void wgmma_ss_n256_tb(float (&d)[128], uint64_t da, uint64_t db, int sd) {
    asm volatile("{\n.reg .pred p;\nsetp.ne.b32 p, %130, 0;\n"
        "wgmma.mma_async.sync.aligned.m64n256k16.f32.bf16.bf16 "
        "{%0, %1, %2, %3, %4, %5, %6, %7, %8, %9, %10, %11, %12, %13, %14, %15, %16, %17, %18, %19, %20, %21, %22, %23, %24, %25, %26, %27, %28, %29, %30, %31, %32, %33, %34, %35, %36, %37, %38, %39, %40, %41, %42, %43, %44, %45, %46, %47, %48, %49, %50, %51, %52, %53, %54, %55, %56, %57, %58, %59, %60, %61, %62, %63, %64, %65, %66, %67, %68, %69, %70, %71, %72, %73, %74, %75, %76, %77, %78, %79, %80, %81, %82, %83, %84, %85, %86, %87, %88, %89, %90, %91, %92, %93, %94, %95, %96, %97, %98, %99, %100, %101, %102, %103, %104, %105, %106, %107, %108, %109, %110, %111, %112, %113, %114, %115, %116, %117, %118, %119, %120, %121, %122, %123, %124, %125, %126, %127}, "
        "%128, %129, p, 1, 1, 0, 1;\n}\n"
        : "+f"(d[0]), "+f"(d[1]), "+f"(d[2]), "+f"(d[3]), "+f"(d[4]), "+f"(d[5]), "+f"(d[6]), "+f"(d[7]), "+f"(d[8]), "+f"(d[9]), "+f"(d[10]), "+f"(d[11]), "+f"(d[12]), "+f"(d[13]), "+f"(d[14]), "+f"(d[15]), "+f"(d[16]), "+f"(d[17]), "+f"(d[18]), "+f"(d[19]), "+f"(d[20]), "+f"(d[21]), "+f"(d[22]), "+f"(d[23]), "+f"(d[24]), "+f"(d[25]), "+f"(d[26]), "+f"(d[27]), "+f"(d[28]), "+f"(d[29]), "+f"(d[30]), "+f"(d[31]), "+f"(d[32]), "+f"(d[33]), "+f"(d[34]), "+f"(d[35]), "+f"(d[36]), "+f"(d[37]), "+f"(d[38]), "+f"(d[39]), "+f"(d[40]), "+f"(d[41]), "+f"(d[42]), "+f"(d[43]), "+f"(d[44]), "+f"(d[45]), "+f"(d[46]), "+f"(d[47]), "+f"(d[48]), "+f"(d[49]), "+f"(d[50]), "+f"(d[51]), "+f"(d[52]), "+f"(d[53]), "+f"(d[54]), "+f"(d[55]), "+f"(d[56]), "+f"(d[57]), "+f"(d[58]), "+f"(d[59]), "+f"(d[60]), "+f"(d[61]), "+f"(d[62]), "+f"(d[63]), "+f"(d[64]), "+f"(d[65]), "+f"(d[66]), "+f"(d[67]), "+f"(d[68]), "+f"(d[69]), "+f"(d[70]), "+f"(d[71]), "+f"(d[72]), "+f"(d[73]), "+f"(d[74]), "+f"(d[75]), "+f"(d[76]), "+f"(d[77]), "+f"(d[78]), "+f"(d[79]), "+f"(d[80]), "+f"(d[81]), "+f"(d[82]), "+f"(d[83]), "+f"(d[84]), "+f"(d[85]), "+f"(d[86]), "+f"(d[87]), "+f"(d[88]), "+f"(d[89]), "+f"(d[90]), "+f"(d[91]), "+f"(d[92]), "+f"(d[93]), "+f"(d[94]), "+f"(d[95]), "+f"(d[96]), "+f"(d[97]), "+f"(d[98]), "+f"(d[99]), "+f"(d[100]), "+f"(d[101]), "+f"(d[102]), "+f"(d[103]), "+f"(d[104]), "+f"(d[105]), "+f"(d[106]), "+f"(d[107]), "+f"(d[108]), "+f"(d[109]), "+f"(d[110]), "+f"(d[111]), "+f"(d[112]), "+f"(d[113]), "+f"(d[114]), "+f"(d[115]), "+f"(d[116]), "+f"(d[117]), "+f"(d[118]), "+f"(d[119]), "+f"(d[120]), "+f"(d[121]), "+f"(d[122]), "+f"(d[123]), "+f"(d[124]), "+f"(d[125]), "+f"(d[126]), "+f"(d[127])
        : "l"(da), "l"(db), "r"(sd));
}
__device__ __forceinline__ void wgmma_rs_n128(float (&d)[64], uint32_t a0, uint32_t a1, uint32_t a2, uint32_t a3, uint64_t db, int sd) {
    asm volatile("{\n.reg .pred p;\nsetp.ne.b32 p, %69, 0;\n"
        "wgmma.mma_async.sync.aligned.m64n128k16.f32.bf16.bf16 "
        "{%0, %1, %2, %3, %4, %5, %6, %7, %8, %9, %10, %11, %12, %13, %14, %15, %16, %17, %18, %19, %20, %21, %22, %23, %24, %25, %26, %27, %28, %29, %30, %31, %32, %33, %34, %35, %36, %37, %38, %39, %40, %41, %42, %43, %44, %45, %46, %47, %48, %49, %50, %51, %52, %53, %54, %55, %56, %57, %58, %59, %60, %61, %62, %63}, "
        "{%64, %65, %66, %67}, %68, p, 1, 1, 0;\n}\n"
        : "+f"(d[0]), "+f"(d[1]), "+f"(d[2]), "+f"(d[3]), "+f"(d[4]), "+f"(d[5]), "+f"(d[6]), "+f"(d[7]), "+f"(d[8]), "+f"(d[9]), "+f"(d[10]), "+f"(d[11]), "+f"(d[12]), "+f"(d[13]), "+f"(d[14]), "+f"(d[15]), "+f"(d[16]), "+f"(d[17]), "+f"(d[18]), "+f"(d[19]), "+f"(d[20]), "+f"(d[21]), "+f"(d[22]), "+f"(d[23]), "+f"(d[24]), "+f"(d[25]), "+f"(d[26]), "+f"(d[27]), "+f"(d[28]), "+f"(d[29]), "+f"(d[30]), "+f"(d[31]), "+f"(d[32]), "+f"(d[33]), "+f"(d[34]), "+f"(d[35]), "+f"(d[36]), "+f"(d[37]), "+f"(d[38]), "+f"(d[39]), "+f"(d[40]), "+f"(d[41]), "+f"(d[42]), "+f"(d[43]), "+f"(d[44]), "+f"(d[45]), "+f"(d[46]), "+f"(d[47]), "+f"(d[48]), "+f"(d[49]), "+f"(d[50]), "+f"(d[51]), "+f"(d[52]), "+f"(d[53]), "+f"(d[54]), "+f"(d[55]), "+f"(d[56]), "+f"(d[57]), "+f"(d[58]), "+f"(d[59]), "+f"(d[60]), "+f"(d[61]), "+f"(d[62]), "+f"(d[63])
        : "r"(a0), "r"(a1), "r"(a2), "r"(a3), "l"(db), "r"(sd));
}
__device__ __forceinline__ void wgmma_rs_n128_tb(float (&d)[64], uint32_t a0, uint32_t a1, uint32_t a2, uint32_t a3, uint64_t db, int sd) {
    asm volatile("{\n.reg .pred p;\nsetp.ne.b32 p, %69, 0;\n"
        "wgmma.mma_async.sync.aligned.m64n128k16.f32.bf16.bf16 "
        "{%0, %1, %2, %3, %4, %5, %6, %7, %8, %9, %10, %11, %12, %13, %14, %15, %16, %17, %18, %19, %20, %21, %22, %23, %24, %25, %26, %27, %28, %29, %30, %31, %32, %33, %34, %35, %36, %37, %38, %39, %40, %41, %42, %43, %44, %45, %46, %47, %48, %49, %50, %51, %52, %53, %54, %55, %56, %57, %58, %59, %60, %61, %62, %63}, "
        "{%64, %65, %66, %67}, %68, p, 1, 1, 1;\n}\n"
        : "+f"(d[0]), "+f"(d[1]), "+f"(d[2]), "+f"(d[3]), "+f"(d[4]), "+f"(d[5]), "+f"(d[6]), "+f"(d[7]), "+f"(d[8]), "+f"(d[9]), "+f"(d[10]), "+f"(d[11]), "+f"(d[12]), "+f"(d[13]), "+f"(d[14]), "+f"(d[15]), "+f"(d[16]), "+f"(d[17]), "+f"(d[18]), "+f"(d[19]), "+f"(d[20]), "+f"(d[21]), "+f"(d[22]), "+f"(d[23]), "+f"(d[24]), "+f"(d[25]), "+f"(d[26]), "+f"(d[27]), "+f"(d[28]), "+f"(d[29]), "+f"(d[30]), "+f"(d[31]), "+f"(d[32]), "+f"(d[33]), "+f"(d[34]), "+f"(d[35]), "+f"(d[36]), "+f"(d[37]), "+f"(d[38]), "+f"(d[39]), "+f"(d[40]), "+f"(d[41]), "+f"(d[42]), "+f"(d[43]), "+f"(d[44]), "+f"(d[45]), "+f"(d[46]), "+f"(d[47]), "+f"(d[48]), "+f"(d[49]), "+f"(d[50]), "+f"(d[51]), "+f"(d[52]), "+f"(d[53]), "+f"(d[54]), "+f"(d[55]), "+f"(d[56]), "+f"(d[57]), "+f"(d[58]), "+f"(d[59]), "+f"(d[60]), "+f"(d[61]), "+f"(d[62]), "+f"(d[63])
        : "r"(a0), "r"(a1), "r"(a2), "r"(a3), "l"(db), "r"(sd));
}
__device__ __forceinline__ void wgmma_rs_n64_tb(float (&d)[32], uint32_t a0, uint32_t a1, uint32_t a2, uint32_t a3, uint64_t db, int sd) {
    asm volatile("{\n.reg .pred p;\nsetp.ne.b32 p, %37, 0;\n"
        "wgmma.mma_async.sync.aligned.m64n64k16.f32.bf16.bf16 "
        "{%0, %1, %2, %3, %4, %5, %6, %7, %8, %9, %10, %11, %12, %13, %14, %15, %16, %17, %18, %19, %20, %21, %22, %23, %24, %25, %26, %27, %28, %29, %30, %31}, "
        "{%32, %33, %34, %35}, %36, p, 1, 1, 1;\n}\n"
        : "+f"(d[0]), "+f"(d[1]), "+f"(d[2]), "+f"(d[3]), "+f"(d[4]), "+f"(d[5]), "+f"(d[6]), "+f"(d[7]), "+f"(d[8]), "+f"(d[9]), "+f"(d[10]), "+f"(d[11]), "+f"(d[12]), "+f"(d[13]), "+f"(d[14]), "+f"(d[15]), "+f"(d[16]), "+f"(d[17]), "+f"(d[18]), "+f"(d[19]), "+f"(d[20]), "+f"(d[21]), "+f"(d[22]), "+f"(d[23]), "+f"(d[24]), "+f"(d[25]), "+f"(d[26]), "+f"(d[27]), "+f"(d[28]), "+f"(d[29]), "+f"(d[30]), "+f"(d[31])
        : "r"(a0), "r"(a1), "r"(a2), "r"(a3), "l"(db), "r"(sd));
}

__global__ void __launch_bounds__(384, 1) fused_gqa_kernel(const __grid_constant__ Params P) {
    extern __shared__ uint8_t smem_raw[];
    const uint32_t base = (smem_u32(smem_raw) + 1023u) & ~1023u;
    const uint32_t smR = base;
    const uint32_t smS = base + R_BYTES;
    const uint32_t bars = smS + NSTAGE * STAGE_BYTES;
    const uint32_t prog = bars + 8 * (2 * NSTAGE + 10);
    const uint32_t barP = prog + 16;
    const int tid = threadIdx.x;
    const int wid = __shfl_sync(0xffffffffu, tid >> 5, 0);
    const int lane = tid & 31;

    const int cta = blockIdx.x;
    const int blk = cta >> 6;
    const int hp = (cta >> 3) & 7;
    const int b = cta & 7;
    const int grp = blk * 8 + b;

    if (tid == 0) {
        TS(0);
        for (int i = 0; i < NSTAGE; i++) {
            mbar_init(bars + 8 * i, 1);
            mbar_init(bars + 8 * (NSTAGE + i), 8);
        }
        for (int i = 0; i < 10; i++) { mbar_init(bars + 8 * (2 * NSTAGE + i), 4); mbar_init(barP + 8 * i, 1); mbar_init(barP + 80 + 8 * i, 4); }
        asm volatile("st.volatile.shared.u32 [%0], %1;" ::"r"(prog), "r"(0) : "memory");
        asm volatile("fence.mbarrier_init.release.cluster;" ::: "memory");
        asm volatile("fence.proxy.async.shared::cta;" ::: "memory");
    }
    __syncthreads();

    if (wid >= 8) {
        asm volatile("setmaxnreg.dec.sync.aligned.u32 40;");
        auto wo_stream = [&](int w) {
            int slot = 4;
            for (int q = 0; q < 18; q++) {
                if (q < NSTAGE) mbar_wait(bars + 8 * (NSTAGE + slot), q == 0);
                else mbar_wait(barP + 80 + 8 * (w * 5 + slot), ((q >= 10) && (q < 15)) ? 1 : 0);
                const uint32_t fb = barP + 8 * (w * 5 + slot);
                const uint32_t dst = smS + slot * STAGE_BYTES + w * 16384;
                mbar_expect_tx(fb, 16384);
                if (q < 16) tma_3d(dst, &P.wo[blk], 0, hp * 512 + ((q & 7) ^ (w * 2)) * 64, (q >> 3) * 4 + w * 2, fb);
                else tma_2d(dst, &P.wo8[blk], 512, hp * 512 + (q - 16) * 256 + w * 128, fb);
                if (++slot == NSTAGE) slot = 0;
            }
        };
        if (wid == 8) {
            if (lane == 0) {
                int slot = 0, ph = 1;
                for (int s = 0; s < N_WQ; s++) {
                    const uint32_t fb = bars + 8 * slot;
                    mbar_wait(bars + 8 * (NSTAGE + slot), ph);
                    const uint32_t dst = smS + slot * STAGE_BYTES;
                    mbar_expect_tx(fb, (s & 1) ? STAGE_BYTES : STAGE_BYTES + 8192);
                    if (!(s & 1)) tma_2d(smR + ((s >> 1) & 7) * 8192, &P.x[blk], (s >> 1) * 64, b * 64, fb);
#pragma unroll
                    for (int p = 0; p < 4; p++) {
                        const int w = p >> 1, j = p & 1;
                        tma_3d(dst + p * 8192, &P.wq[blk], 0, s * 32, hp * 8 + j * 4 + w * 2, fb);
                    }
                    if (++slot == NSTAGE) { slot = 0; ph ^= 1; }
                }
                for (int i = 0; i < 16; i++) {
                    const uint32_t fb = bars + 8 * slot;
                    mbar_wait(bars + 8 * (NSTAGE + slot), ph);
                    const uint32_t dst = smS + slot * STAGE_BYTES;
                    mbar_expect_tx(fb, STAGE_BYTES);
                    const int row = (b * kHkv + hp * 2) * kSk + (i >> 1) * 128;
                    tma_3d(dst, (i & 1) ? &P.v[blk] : &P.k[blk], 0, row, 0, fb);
                    asm volatile("st.volatile.shared.u32 [%0], %1;" ::"r"(prog), "r"(i + 1) : "memory");
                    if (++slot == NSTAGE) { slot = 0; ph ^= 1; }
                }
                wo_stream(0);
            }
        } else if (wid == 11) {
            if (PF_DIST > 0) {
                uint32_t sink = 0;
                mbar_wait(bars, 0);
                if (PF_WQ) {
                    const char* wqs = (const char*)(P.wqp[blk] + hp * 512) + (size_t)(160 + b * 52) * 8192;
#pragma unroll
                    for (int h = 0; h < 2; h++) {
#pragma unroll
                        for (int j = 0; j < 4; j++) {
                            const int e = (h * 4 + j) * 32 + lane;
                            if (e < 208) sink |= l2_touch(wqs + (size_t)(e >> 2) * 8192 + (e & 3) * 256);
                        }
                        if (sink == 0x9E3779B9u) asm volatile("st.volatile.shared.u32 [%0], %1;" ::"r"(prog + 4), "r"(sink) : "memory");
                    }
                }
                const char* kbase = (const char*)(P.kp[blk] + (size_t)(b * kHkv + hp * 2) * kSk * kDh);
                const char* vbase = (const char*)(P.vp[blk] + (size_t)(b * kHkv + hp * 2) * kSk * kDh);
                const char* wos = (const char*)(P.wop[blk] + (size_t)hp * 512 * kD) + (size_t)b * 73728;
#define WO_POS 16
#define WO_FULL 0
                for (int ii = 0; ii < 17; ii++) {
                    const bool is_wo = (ii == WO_POS);
                    const int i = (ii > WO_POS) ? ii - 1 : ii;
                    if (i >= PF_DIST) {
                        uint32_t pr, n = 0;
                        while (true) {
                            asm volatile("ld.volatile.shared.u32 %0, [%1];" : "=r"(pr) : "r"(prog) : "memory");
                            if ((int)pr + PF_DIST >= i) break;
                            if (++n > (1u << 22)) break;
                            __nanosleep(100);
                        }
                    }
                    if (!is_wo) {
                        const char* p = ((i & 1) ? vbase : kbase) + (size_t)(i >> 1) * 32768 + lane * 256;
#pragma unroll
                        for (int j = 0; j < 4; j++) sink |= l2_touch(p + j * 8192);
                        if (sink == 0x9E3779B9u) asm volatile("st.volatile.shared.u32 [%0], %1;" ::"r"(prog + 4), "r"(sink) : "memory");
                    } else {
                        for (int h = 0; h < (WO_FULL ? 24 : 3); h++) {
                            const char* p = (WO_FULL ? (wos - (size_t)b * 73728 + (size_t)((h + 3 * b) % 24) * 24576) : (wos + (size_t)h * 24576)) + lane * 256;
#pragma unroll
                            for (int j = 0; j < 3; j++) sink |= l2_touch(p + j * 8192);
                            if (sink == 0x9E3779B9u) asm volatile("st.volatile.shared.u32 [%0], %1;" ::"r"(prog + 4), "r"(sink) : "memory");
                        }
                    }
                }
            }
        } else if (wid == 10) {
            if (lane == 0) {
                uint32_t pr, n = 0;
                while (true) {
                    asm volatile("ld.volatile.shared.u32 %0, [%1];" : "=r"(pr) : "r"(prog) : "memory");
                    if (pr >= 16) break;
                    if (++n > (1u << 22)) break;
                    __nanosleep(200);
                }
                wo_stream(1);
            }
        } else {
            int k0 = 0, k1 = 0;
            uint32_t n = 0;
            while (k0 + k1 < 6) {
                const int hw = (k0 >= 3) ? 1 : (k1 >= 3) ? 0 : (int)(n & 1);
                const int k = hw ? k1 : k0;
                if (__all_sync(0xffffffffu, mbar_try(bars + 8 * (2 * NSTAGE + hw * 5 + k), 0))) {
                    const int c = (k < 2) ? (2 * k + hw) : 4;
                    asm volatile("fence.acq_rel.gpu;" ::: "memory");
                    asm volatile("red.relaxed.gpu.global.add.u32 [%0], 1;" ::"l"(&g_cnt[(grp * 9 + c) * 32 + lane]) : "memory");
                    if (hw) k1++; else k0++;
                }
                if (++n > (1u << 22)) break;
            }
        }
    } else {
        asm volatile("setmaxnreg.inc.sync.aligned.u32 232;");
        const int w = wid >> 2;
        const int t = tid & 127;
        int slot = 0, ph = 0;
        uint32_t qf[8][4];
        const uint32_t stash = smR + (1 + w) * 16384 + t * 16;
        {
            float acc[128];
            int pslot = 0;
            for (int s = 0; s < N_WQ; s++) {
                mbar_wait(bars + 8 * slot, ph);
                if (tid == 0 && s == 0) TS(20);
                if (tid == 0 && s == 5) TS(21);
                if (tid == 0 && s == 10) TS(22);
                const uint64_t da = mk_desc(smR + ((s >> 1) & 7) * 8192 + (s & 1) * 64, 16, 1024);
                const uint64_t db = mk_desc(smS + slot * STAGE_BYTES + w * 16384, 4096, 1024);
                wg_fence();
                wgmma_ss_n256_tb(acc, da, db, s != 0);
                wgmma_ss_n256_tb(acc, da + 2, db + 128, 1);
                wg_commit();
                wg_wait<0>();
                if (lane == 0) mbar_arrive(bars + 8 * (NSTAGE + slot));
                pslot = slot;
                if (++slot == NSTAGE) { slot = 0; ph ^= 1; }
            }
            fence_regs(acc);
            if (tid == 0) TS(1);
#pragma unroll
            for (int kk = 0; kk < 8; kk++) {
#pragma unroll
                for (int i = 0; i < 4; i++) qf[kk][i] = pack_bf16(acc[8 * kk + 2 * i], acc[8 * kk + 2 * i + 1]);
                sts128(stash + kk * 2048,
                       pack_bf16(acc[64 + 8 * kk + 0], acc[64 + 8 * kk + 1]), pack_bf16(acc[64 + 8 * kk + 2], acc[64 + 8 * kk + 3]),
                       pack_bf16(acc[64 + 8 * kk + 4], acc[64 + 8 * kk + 5]), pack_bf16(acc[64 + 8 * kk + 6], acc[64 + 8 * kk + 7]));
            }
        }
        if (w == 1) bar_arrive<5, 256>();
        const float sc = 0.08838834764831845f * 1.4426950408889634f;
        uint32_t af[32][4];
#pragma unroll
        for (int u = 0; u < 2; u++) {
            {
                if (u == 1) {
#pragma unroll
                    for (int kk = 0; kk < 8; kk++) lds128(stash + kk * 2048, qf[kk]);
                }
                float o[64], s[64];
                float m0 = -INFINITY, m1 = -INFINITY, l0 = 0.f, l1 = 0.f;
                uint32_t pf[8][4];
#pragma unroll
                for (int i = 0; i < 64; i++) { o[i] = 0.f; s[i] = 0.f; }
#pragma unroll
                for (int i = 0; i < 32; i++) pf[i >> 2][i & 3] = 0u;
#pragma unroll 1
                for (int tt = 0; tt <= 4; tt++) {
                    int vslot = slot;
                    if (tt > 0) {
                        mbar_wait(bars + 8 * slot, ph);
                        if (++slot == NSTAGE) { slot = 0; ph ^= 1; }
                    }
                    if (tt < 4) mbar_wait(bars + 8 * slot, ph);
                    if (tid == 0) TS(32 + u * 20 + tt * 4);
                    if (w == 0) bar_sync<5, 256>(); else bar_sync<6, 256>();
                    wg_fence();
                    if (tt > 0) {
                        const uint64_t db = mk_desc(smS + vslot * STAGE_BYTES, 16384, 1024);
#pragma unroll
                        for (int kk = 0; kk < 8; kk++)
                            wgmma_rs_n128_tb(o, pf[kk][0], pf[kk][1], pf[kk][2], pf[kk][3], db + kk * 128, (tt > 1) || (kk != 0));
                        wg_commit();
                    }
                    if (tt < 4) {
                        const uint64_t db = mk_desc(smS + slot * STAGE_BYTES, 16, 1024);
#pragma unroll
                        for (int kk = 0; kk < 8; kk++)
                            wgmma_rs_n128(s, qf[kk][0], qf[kk][1], qf[kk][2], qf[kk][3], db + (kk >> 2) * 1024 + (kk & 3) * 2, kk != 0);
                        wg_commit();
                    }
                    if (w == 0) bar_arrive<6, 256>(); else if (!(u == 1 && tt == 4)) bar_arrive<5, 256>();
                    if (tid == 0) TS(32 + u * 20 + tt * 4 + 1);
                    wg_wait<0>();
                    fence_regs(o);
                    fence_regs(s);
                    if (tid == 0) TS(32 + u * 20 + tt * 4 + 2);
                    if (tt > 0 && lane == 0) mbar_arrive(bars + 8 * (NSTAGE + vslot));
                    if (tt == 4) break;
                    if (lane == 0) mbar_arrive(bars + 8 * (NSTAGE + slot));
                    if (++slot == NSTAGE) { slot = 0; ph ^= 1; }
                    float mx0 = s[0], mx1 = s[2];
#pragma unroll
                    for (int j = 0; j < 16; j++) {
                        mx0 = fmaxf(mx0, fmaxf(s[4 * j], s[4 * j + 1]));
                        mx1 = fmaxf(mx1, fmaxf(s[4 * j + 2], s[4 * j + 3]));
                    }
                    mx0 = fmaxf(mx0, __shfl_xor_sync(0xffffffffu, mx0, 1));
                    mx1 = fmaxf(mx1, __shfl_xor_sync(0xffffffffu, mx1, 1));
                    mx0 = fmaxf(mx0, __shfl_xor_sync(0xffffffffu, mx0, 2));
                    mx1 = fmaxf(mx1, __shfl_xor_sync(0xffffffffu, mx1, 2));
                    const float mn0 = fmaxf(m0, mx0), mn1 = fmaxf(m1, mx1);
                    const float al0 = ex2((m0 - mn0) * sc), al1 = ex2((m1 - mn1) * sc);
                    m0 = mn0; m1 = mn1;
                    const float ms0 = mn0 * sc, ms1 = mn1 * sc;
                    float rs0 = 0.f, rs1 = 0.f;
#pragma unroll
                    for (int j = 0; j < 16; j++) {
                        const float p0 = ex2(fmaf(s[4 * j], sc, -ms0)), p1 = ex2(fmaf(s[4 * j + 1], sc, -ms0));
                        const float p2 = ex2(fmaf(s[4 * j + 2], sc, -ms1)), p3 = ex2(fmaf(s[4 * j + 3], sc, -ms1));
                        rs0 += p0 + p1; rs1 += p2 + p3;
                        pf[j >> 1][(j & 1) * 2] = pack_bf16(p0, p1);
                        pf[j >> 1][(j & 1) * 2 + 1] = pack_bf16(p2, p3);
                    }
                    l0 = l0 * al0 + rs0; l1 = l1 * al1 + rs1;
                    if (tt > 0) {
#pragma unroll
                        for (int j = 0; j < 16; j++) { o[4 * j] *= al0; o[4 * j + 1] *= al0; o[4 * j + 2] *= al1; o[4 * j + 3] *= al1; }
                    }
                    if (tid == 0) TS(32 + u * 20 + tt * 4 + 3);
                }
                if (tid == 0) TS(2 + u);
                l0 += __shfl_xor_sync(0xffffffffu, l0, 1);
                l1 += __shfl_xor_sync(0xffffffffu, l1, 1);
                l0 += __shfl_xor_sync(0xffffffffu, l0, 2);
                l1 += __shfl_xor_sync(0xffffffffu, l1, 2);
                const float i0 = 1.f / l0, i1 = 1.f / l1;
                const uint32_t zown = smR + ((u == 0) ? (w ? 3 : 0) : (w ? 2 : 1)) * 16384 + t * 16;
#pragma unroll
                for (int kk = 0; kk < 8; kk++) {
                    af[16 + kk][0] = pack_bf16(o[8 * kk + 0] * i0, o[8 * kk + 1] * i0);
                    af[16 + kk][1] = pack_bf16(o[8 * kk + 2] * i1, o[8 * kk + 3] * i1);
                    af[16 + kk][2] = pack_bf16(o[8 * kk + 4] * i0, o[8 * kk + 5] * i0);
                    af[16 + kk][3] = pack_bf16(o[8 * kk + 6] * i1, o[8 * kk + 7] * i1);
                    sts128(zown + kk * 2048, af[16 + kk][0], af[16 + kk][1], af[16 + kk][2], af[16 + kk][3]);
                }
            }
        }
        if (w == 0) bar_arrive<7, 256>(); else bar_arrive<8, 256>();
        {
#pragma unroll
            for (int kk = 0; kk < 8; kk++) {
                lds128(smR + (w ? 3 : 0) * 16384 + kk * 2048 + t * 16, af[kk]);
                lds128(smR + (w ? 0 : 3) * 16384 + kk * 2048 + t * 16, af[8 + kk]);
            }
            uint2* dst0 = g_part + (size_t)(grp * 80 + 2 * w * 8 + hp) * 1024 + t;
            uint2* dst8 = g_part + (size_t)(grp * 80 + 64 + hp * 2 + w) * 1024 + t;
#pragma unroll
            for (int ps = 0; ps < 2; ps++) {
                float acc[64];
#pragma unroll
                for (int i = 0; i < 64; i++) acc[i] = 0.f;
#pragma unroll
                for (int st = 0; st < 8; st++) {
                    if (ps == 0 && st == 5) {
                        if (w == 0) bar_sync<8, 256>(); else bar_sync<7, 256>();
#pragma unroll
                        for (int kk = 0; kk < 8; kk++) lds128(smR + (w ? 1 : 2) * 16384 + kk * 2048 + t * 16, af[24 + kk]);
                    }
                    mbar_wait(barP + 8 * (w * 5 + slot), ((ps * 8 + st) / 5) & 1);
                    if (tid == 0) TS(80 + ps * 16 + 2 * st);
                    const uint64_t db = mk_desc(smS + slot * STAGE_BYTES + w * 16384, 8192, 1024);
                    wg_fence();
#pragma unroll
                    for (int kk = 0; kk < 4; kk++)
                        wgmma_rs_n128_tb(acc, af[st * 4 + kk][0], af[st * 4 + kk][1], af[st * 4 + kk][2], af[st * 4 + kk][3], db + kk * 128, (st | kk) != 0);
                    wg_commit();
                    wg_wait<0>();
                    if (lane == 0) mbar_arrive(barP + 80 + 8 * (w * 5 + slot));
                    if (tid == 0) TS(80 + ps * 16 + 2 * st + 1);
                    if (++slot == NSTAGE) slot = 0;
                }
                fence_regs(acc);
                uint2* dst = dst0 + (size_t)ps * 32 * 1024;
#pragma unroll
                for (int j = 0; j < 16; j++)
                    __stcg(dst + (j >> 3) * 8192 + (j & 7) * 128, make_uint2(pack_bf16(acc[4 * j], acc[4 * j + 1]), pack_bf16(acc[4 * j + 2], acc[4 * j + 3])));
                __syncwarp();
                if (lane == 0) mbar_arrive(bars + 8 * (2 * NSTAGE + w * 5 + ps));
                if (tid == 0) TS(4 + ps);
            }
            {
                float acc[32];
#pragma unroll
                for (int i = 0; i < 32; i++) acc[i] = 0.f;
#pragma unroll
                for (int st = 0; st < 2; st++) {
                    mbar_wait(barP + 8 * (w * 5 + slot), 1);
                    const uint64_t db = mk_desc(smS + slot * STAGE_BYTES + w * 16384, 8192, 1024);
                    wg_fence();
#pragma unroll
                    for (int kk = 0; kk < 8; kk++)
                        wgmma_rs_n64_tb(acc, af[st * 16 + kk][0], af[st * 16 + kk][1], af[st * 16 + kk][2], af[st * 16 + kk][3], db + kk * 128, (st | kk) != 0);
                    wg_commit();
                    if (++slot == NSTAGE) slot = 0;
                }
                wg_wait<0>();
                fence_regs(acc);
#pragma unroll
                for (int j = 0; j < 8; j++)
                    __stcg(dst8 + j * 128, make_uint2(pack_bf16(acc[4 * j], acc[4 * j + 1]), pack_bf16(acc[4 * j + 2], acc[4 * j + 3])));
                __syncwarp();
                if (lane == 0) mbar_arrive(bars + 8 * (2 * NSTAGE + w * 5 + 2));
                if (tid == 0) TS(8);
            }
        }
        {
            const int nch = (w == 0) ? 3 : 2;
            if (lane < nch) {
                const int c = (lane < 2) ? (2 * lane + w) : 4;
                const unsigned need = (lane < 2) ? 8u : 16u;
                unsigned* cp = &g_cnt[(grp * 9 + c) * 32 + hp * 4 + (wid & 3)];
                unsigned v, n = 0;
                while (true) {
                    asm volatile("ld.acquire.gpu.global.u32 %0, [%1];" : "=r"(v) : "l"(cp) : "memory");
                    if (v >= need) break;
                    if (++n > (1u << 21)) break;
                }
                *cp = 0;
            }
            __syncwarp();
            if (tid == 0) TS(18);
            __nv_bfloat16* orow = P.out + (size_t)(b * 64 + (t >> 5) * 16 + (lane >> 2)) * (2 * kD) + blk * kD + hp * 8 + (lane & 3) * 2;
            const uint2* src = g_part + ((size_t)(grp * 80 + 2 * w * 8) * 8 + hp) * 128 + t;
            uint2 v[4][8];
#pragma unroll
            for (int k = 0; k < 4; k++)
#pragma unroll
                for (int i = 0; i < 8; i++) v[k][i] = __ldcg(src + (size_t)((k >> 1) * 32 + (k & 1) * 8 + i) * 1024);
            if (w == 0) {
                const uint2* src8 = g_part + ((size_t)(grp * 80 + 64) * 8 + hp) * 128 + t;
                uint2 u[16];
#pragma unroll
                for (int i = 0; i < 16; i++) u[i] = __ldcg(src8 + (size_t)i * 1024);
                float a0 = 0.f, a1 = 0.f, a2 = 0.f, a3 = 0.f;
#pragma unroll
                for (int i = 0; i < 16; i++) {
                    a0 += __uint_as_float(u[i].x << 16); a1 += __uint_as_float(u[i].x & 0xffff0000u);
                    a2 += __uint_as_float(u[i].y << 16); a3 += __uint_as_float(u[i].y & 0xffff0000u);
                }
                *(uint32_t*)(orow + 512) = pack_bf16(a0, a1);
                *(uint32_t*)(orow + 512 + 8 * 2 * kD) = pack_bf16(a2, a3);
            }
#pragma unroll
            for (int k = 0; k < 4; k++) {
                float a0 = 0.f, a1 = 0.f, a2 = 0.f, a3 = 0.f;
#pragma unroll
                for (int i = 0; i < 8; i++) {
                    a0 += __uint_as_float(v[k][i].x << 16); a1 += __uint_as_float(v[k][i].x & 0xffff0000u);
                    a2 += __uint_as_float(v[k][i].y << 16); a3 += __uint_as_float(v[k][i].y & 0xffff0000u);
                }
                *(uint32_t*)(orow + ((k >> 1) * 4 + 2 * w + (k & 1)) * 64) = pack_bf16(a0, a1);
                *(uint32_t*)(orow + ((k >> 1) * 4 + 2 * w + (k & 1)) * 64 + 8 * 2 * kD) = pack_bf16(a2, a3);
            }
            if (tid == 0) TS(19);
        }
    }
}

typedef CUresult (*EncodeFn)(CUtensorMap*, CUtensorMapDataType, cuuint32_t, void*, const cuuint64_t*, const cuuint64_t*,
                             const cuuint32_t*, const cuuint32_t*, CUtensorMapInterleave, CUtensorMapSwizzle,
                             CUtensorMapL2promotion, CUtensorMapFloatOOBfill);

void make_map(EncodeFn fn, CUtensorMap* m, const void* ptr, uint64_t cols, uint64_t rows, uint32_t box_rows) {
    cuuint64_t dims[2] = {cols, rows};
    cuuint64_t strides[1] = {cols * 2};
    cuuint32_t box[2] = {64, box_rows};
    cuuint32_t es[2] = {1, 1};
    fn(m, CU_TENSOR_MAP_DATA_TYPE_BFLOAT16, 2, const_cast<void*>(ptr), dims, strides, box, es, CU_TENSOR_MAP_INTERLEAVE_NONE,
       CU_TENSOR_MAP_SWIZZLE_128B, CU_TENSOR_MAP_L2_PROMOTION_L2_256B, CU_TENSOR_MAP_FLOAT_OOB_FILL_NONE);
}

void make_map3(EncodeFn fn, CUtensorMap* m, const void* ptr, uint64_t cols, uint64_t rows, uint32_t box_rows, uint32_t box_groups) {
    cuuint64_t dims[3] = {64, rows, cols / 64};
    cuuint64_t strides[2] = {cols * 2, 128};
    cuuint32_t box[3] = {64, box_rows, box_groups};
    cuuint32_t es[3] = {1, 1, 1};
    fn(m, CU_TENSOR_MAP_DATA_TYPE_BFLOAT16, 3, const_cast<void*>(ptr), dims, strides, box, es, CU_TENSOR_MAP_INTERLEAVE_NONE,
       CU_TENSOR_MAP_SWIZZLE_128B, CU_TENSOR_MAP_L2_PROMOTION_L2_256B, CU_TENSOR_MAP_FLOAT_OOB_FILL_NONE);
}

}

extern "C" void kernel_launch(void* const* d_in, const int* in_sizes, int n_in, void* d_out, int out_size) {
    static EncodeFn enc = nullptr;
    if (!enc) {
        void* fn = nullptr;
        cudaDriverEntryPointQueryResult st;
        cudaGetDriverEntryPoint("cuTensorMapEncodeTiled", &fn, cudaEnableDefault, &st);
        enc = (EncodeFn)fn;
        cudaFuncSetAttribute(fused_gqa_kernel, cudaFuncAttributeMaxDynamicSharedMemorySize, SMEM_BYTES);
    }
    Params P;
    for (int blk = 0; blk < 2; blk++) {
        const void* x = d_in[blk * 5 + 0];
        const void* k = d_in[blk * 5 + 1];
        const void* v = d_in[blk * 5 + 2];
        const void* wq = d_in[blk * 5 + 3];
        const void* wo = d_in[blk * 5 + 4];
        make_map(enc, &P.x[blk], x, kD, kB * kSq, 64);
        make_map3(enc, &P.wq[blk], wq, kHq * kDh, kD, 32, 2);
        make_map3(enc, &P.k[blk], k, kDh, (uint64_t)kB * kHkv * kSk, 128, 2);
        make_map3(enc, &P.v[blk], v, kDh, (uint64_t)kB * kHkv * kSk, 128, 2);
        make_map3(enc, &P.wo[blk], wo, kD, kHq * kDh, 64, 2);
        make_map(enc, &P.wo8[blk], wo, kD, kHq * kDh, 128);
        P.wqp[blk] = (const __nv_bfloat16*)wq;
        P.kp[blk] = (const __nv_bfloat16*)k;
        P.vp[blk] = (const __nv_bfloat16*)v;
        P.wop[blk] = (const __nv_bfloat16*)wo;
    }
    P.out = (__nv_bfloat16*)d_out;
    fused_gqa_kernel<<<128, 384, SMEM_BYTES>>>(P);
}
```

```cpp
#include <cuda_runtime.h>
#include <cuda_bf16.h>
#include <cuda.h>
#include <stdint.h>

namespace {

constexpr int kB = 8, kSq = 64, kD = 576, kHq = 32, kHkv = 16, kSk = 512, kDh = 128;
constexpr int NSTAGE = 5;
constexpr int STAGE_BYTES = 32768;
constexpr int R_BYTES = 65536;
constexpr int SMEM_BYTES = R_BYTES + NSTAGE * STAGE_BYTES + 1024   + 256  ;
constexpr int N_WQ = 18;
#define PF_DIST_V 6
#define OP_WAIT0 1
#define QP_WAIT0 1
#define PF_WQ 0
#define PF_SLEEP 1000
constexpr int PF_DIST = PF_DIST_V;

struct __align__(64) Params {
    CUtensorMap x[2], wq[2], k[2], v[2], wo[2], wo8[2];
    const __nv_bfloat16* wqp[2];
    const __nv_bfloat16* kp[2];
    const __nv_bfloat16* vp[2];
    const __nv_bfloat16* wop[2];
    __nv_bfloat16* out;
};

__device__ uint2 g_part[16 * 80 * 8 * 128];
__device__ unsigned int g_cnt[16 * 9 * 32];
#define TS(k) do {} while (0)

__device__ __forceinline__ uint32_t smem_u32(const void* p) { return (uint32_t)__cvta_generic_to_shared(p); }
__device__ __forceinline__ void mbar_init(uint32_t bar, int cnt) {
    asm volatile("mbarrier.init.shared::cta.b64 [%0], %1;" ::"r"(bar), "r"(cnt));
}
__device__ __forceinline__ void mbar_expect_tx(uint32_t bar, uint32_t bytes) {
    asm volatile("mbarrier.arrive.expect_tx.shared::cta.b64 _, [%0], %1;" ::"r"(bar), "r"(bytes) : "memory");
}
__device__ __forceinline__ void mbar_arrive(uint32_t bar) {
    asm volatile("mbarrier.arrive.shared::cta.b64 _, [%0];" ::"r"(bar) : "memory");
}
__device__ __forceinline__ bool mbar_try(uint32_t bar, uint32_t parity) {
    uint32_t ok;
    asm volatile("{\n.reg .pred p;\nmbarrier.try_wait.parity.shared::cta.b64 p, [%1], %2;\nselp.u32 %0, 1, 0, p;\n}\n"
                 : "=r"(ok) : "r"(bar), "r"(parity) : "memory");
    return ok != 0;
}
__device__ __forceinline__ void mbar_wait(uint32_t bar, uint32_t parity) {
    if (mbar_try(bar, parity)) return;
    uint32_t n = 0;
    while (!mbar_try(bar, parity)) {
        if (++n > (1u << 20)) break;
    }
}
__device__ __forceinline__ void tma_2d(uint32_t dst, const CUtensorMap* tm, int c0, int c1, uint32_t bar) {
    asm volatile("cp.async.bulk.tensor.2d.shared::cluster.global.mbarrier::complete_tx::bytes [%0], [%1, {%3, %4}], [%2];"
                 ::"r"(dst), "l"(tm), "r"(bar), "r"(c0), "r"(c1) : "memory");
}
__device__ __forceinline__ void tma_3d(uint32_t dst, const CUtensorMap* tm, int c0, int c1, int c2, uint32_t bar) {
    asm volatile("cp.async.bulk.tensor.3d.shared::cluster.global.mbarrier::complete_tx::bytes [%0], [%1, {%3, %4, %5}], [%2];"
                 ::"r"(dst), "l"(tm), "r"(bar), "r"(c0), "r"(c1), "r"(c2) : "memory");
}
__device__ __forceinline__ void l2_prefetch(const void* p, uint32_t bytes) {
    asm volatile("cp.async.bulk.prefetch.L2.global [%0], %1;" ::"l"(p), "r"(bytes) : "memory");
}
__device__ __forceinline__ uint32_t l2_touch(const void* p) {
    uint32_t v;
    asm volatile("ld.global.L2::256B.b32 %0, [%1];" : "=r"(v) : "l"(p) : "memory");
    return v;
}
__device__ __forceinline__ void wg_fence() { asm volatile("wgmma.fence.sync.aligned;" ::: "memory"); }
__device__ __forceinline__ void wg_commit() { asm volatile("wgmma.commit_group.sync.aligned;" ::: "memory"); }
template <int N> __device__ __forceinline__ void wg_wait() { asm volatile("wgmma.wait_group.sync.aligned %0;" ::"n"(N) : "memory"); }
template <int N> __device__ __forceinline__ void fence_regs(float (&d)[N]) {
#pragma unroll
    for (int i = 0; i < N; i++) asm volatile("" : "+f"(d[i])::"memory");
}
__device__ __forceinline__ uint64_t mk_desc(uint32_t addr, uint32_t lbo, uint32_t sbo) {
    return (uint64_t)((addr & 0x3FFFF) >> 4) | ((uint64_t)(lbo >> 4) << 16) | ((uint64_t)(sbo >> 4) << 32) | (1ull << 62);
}
__device__ __forceinline__ uint32_t pack_bf16(float a, float b) {
    uint32_t r;
    asm("cvt.rn.bf16x2.f32 %0, %1, %2;" : "=r"(r) : "f"(b), "f"(a));
    return r;
}
__device__ __forceinline__ float ex2(float x) {
    float y;
    asm("ex2.approx.ftz.f32 %0, %1;" : "=f"(y) : "f"(x));
    return y;
}
template <int ID, int N> __device__ __forceinline__ void bar_sync() { asm volatile("bar.sync %0, %1;" ::"n"(ID), "n"(N) : "memory"); }
template <int ID, int N> __device__ __forceinline__ void bar_arrive() { asm volatile("bar.arrive %0, %1;" ::"n"(ID), "n"(N) : "memory"); }
__device__ __forceinline__ void sts128(uint32_t addr, uint32_t a, uint32_t b, uint32_t c, uint32_t d) {
    asm volatile("st.shared.v4.b32 [%0], {%1,%2,%3,%4};" ::"r"(addr), "r"(a), "r"(b), "r"(c), "r"(d) : "memory");
}
__device__ __forceinline__ void lds128(uint32_t addr, uint32_t (&r)[4]) {
    asm volatile("ld.shared.v4.b32 {%0,%1,%2,%3}, [%4];" : "=r"(r[0]), "=r"(r[1]), "=r"(r[2]), "=r"(r[3]) : "r"(addr) : "memory");
}

__device__ __forceinline__ void wgmma_ss_n256_tb(float (&d)[128], uint64_t da, uint64_t db, int sd) {
    asm volatile("{\n.reg .pred p;\nsetp.ne.b32 p, %130, 0;\n"
        "wgmma.mma_async.sync.aligned.m64n256k16.f32.bf16.bf16 "
        "{%0, %1, %2, %3, %4, %5, %6, %7, %8, %9, %10, %11, %12, %13, %14, %15, %16, %17, %18, %19, %20, %21, %22, %23, %24, %25, %26, %27, %28, %29, %30, %31, %32, %33, %34, %35, %36, %37, %38, %39, %40, %41, %42, %43, %44, %45, %46, %47, %48, %49, %50, %51, %52, %53, %54, %55, %56, %57, %58, %59, %60, %61, %62, %63, %64, %65, %66, %67, %68, %69, %70, %71, %72, %73, %74, %75, %76, %77, %78, %79, %80, %81, %82, %83, %84, %85, %86, %87, %88, %89, %90, %91, %92, %93, %94, %95, %96, %97, %98, %99, %100, %101, %102, %103, %104, %105, %106, %107, %108, %109, %110, %111, %112, %113, %114, %115, %116, %117, %118, %119, %120, %121, %122, %123, %124, %125, %126, %127}, "
        "%128, %129, p, 1, 1, 0, 1;\n}\n"
        : "+f"(d[0]), "+f"(d[1]), "+f"(d[2]), "+f"(d[3]), "+f"(d[4]), "+f"(d[5]), "+f"(d[6]), "+f"(d[7]), "+f"(d[8]), "+f"(d[9]), "+f"(d[10]), "+f"(d[11]), "+f"(d[12]), "+f"(d[13]), "+f"(d[14]), "+f"(d[15]), "+f"(d[16]), "+f"(d[17]), "+f"(d[18]), "+f"(d[19]), "+f"(d[20]), "+f"(d[21]), "+f"(d[22]), "+f"(d[23]), "+f"(d[24]), "+f"(d[25]), "+f"(d[26]), "+f"(d[27]), "+f"(d[28]), "+f"(d[29]), "+f"(d[30]), "+f"(d[31]), "+f"(d[32]), "+f"(d[33]), "+f"(d[34]), "+f"(d[35]), "+f"(d[36]), "+f"(d[37]), "+f"(d[38]), "+f"(d[39]), "+f"(d[40]), "+f"(d[41]), "+f"(d[42]), "+f"(d[43]), "+f"(d[44]), "+f"(d[45]), "+f"(d[46]), "+f"(d[47]), "+f"(d[48]), "+f"(d[49]), "+f"(d[50]), "+f"(d[51]), "+f"(d[52]), "+f"(d[53]), "+f"(d[54]), "+f"(d[55]), "+f"(d[56]), "+f"(d[57]), "+f"(d[58]), "+f"(d[59]), "+f"(d[60]), "+f"(d[61]), "+f"(d[62]), "+f"(d[63]), "+f"(d[64]), "+f"(d[65]), "+f"(d[66]), "+f"(d[67]), "+f"(d[68]), "+f"(d[69]), "+f"(d[70]), "+f"(d[71]), "+f"(d[72]), "+f"(d[73]), "+f"(d[74]), "+f"(d[75]), "+f"(d[76]), "+f"(d[77]), "+f"(d[78]), "+f"(d[79]), "+f"(d[80]), "+f"(d[81]), "+f"(d[82]), "+f"(d[83]), "+f"(d[84]), "+f"(d[85]), "+f"(d[86]), "+f"(d[87]), "+f"(d[88]), "+f"(d[89]), "+f"(d[90]), "+f"(d[91]), "+f"(d[92]), "+f"(d[93]), "+f"(d[94]), "+f"(d[95]), "+f"(d[96]), "+f"(d[97]), "+f"(d[98]), "+f"(d[99]), "+f"(d[100]), "+f"(d[101]), "+f"(d[102]), "+f"(d[103]), "+f"(d[104]), "+f"(d[105]), "+f"(d[106]), "+f"(d[107]), "+f"(d[108]), "+f"(d[109]), "+f"(d[110]), "+f"(d[111]), "+f"(d[112]), "+f"(d[113]), "+f"(d[114]), "+f"(d[115]), "+f"(d[116]), "+f"(d[117]), "+f"(d[118]), "+f"(d[119]), "+f"(d[120]), "+f"(d[121]), "+f"(d[122]), "+f"(d[123]), "+f"(d[124]), "+f"(d[125]), "+f"(d[126]), "+f"(d[127])
        : "l"(da), "l"(db), "r"(sd));
}
__device__ __forceinline__ void wgmma_rs_n128(float (&d)[64], uint32_t a0, uint32_t a1, uint32_t a2, uint32_t a3, uint64_t db, int sd) {
    asm volatile("{\n.reg .pred p;\nsetp.ne.b32 p, %69, 0;\n"
        "wgmma.mma_async.sync.aligned.m64n128k16.f32.bf16.bf16 "
        "{%0, %1, %2, %3, %4, %5, %6, %7, %8, %9, %10, %11, %12, %13, %14, %15, %16, %17, %18, %19, %20, %21, %22, %23, %24, %25, %26, %27, %28, %29, %30, %31, %32, %33, %34, %35, %36, %37, %38, %39, %40, %41, %42, %43, %44, %45, %46, %47, %48, %49, %50, %51, %52, %53, %54, %55, %56, %57, %58, %59, %60, %61, %62, %63}, "
        "{%64, %65, %66, %67}, %68, p, 1, 1, 0;\n}\n"
        : "+f"(d[0]), "+f"(d[1]), "+f"(d[2]), "+f"(d[3]), "+f"(d[4]), "+f"(d[5]), "+f"(d[6]), "+f"(d[7]), "+f"(d[8]), "+f"(d[9]), "+f"(d[10]), "+f"(d[11]), "+f"(d[12]), "+f"(d[13]), "+f"(d[14]), "+f"(d[15]), "+f"(d[16]), "+f"(d[17]), "+f"(d[18]), "+f"(d[19]), "+f"(d[20]), "+f"(d[21]), "+f"(d[22]), "+f"(d[23]), "+f"(d[24]), "+f"(d[25]), "+f"(d[26]), "+f"(d[27]), "+f"(d[28]), "+f"(d[29]), "+f"(d[30]), "+f"(d[31]), "+f"(d[32]), "+f"(d[33]), "+f"(d[34]), "+f"(d[35]), "+f"(d[36]), "+f"(d[37]), "+f"(d[38]), "+f"(d[39]), "+f"(d[40]), "+f"(d[41]), "+f"(d[42]), "+f"(d[43]), "+f"(d[44]), "+f"(d[45]), "+f"(d[46]), "+f"(d[47]), "+f"(d[48]), "+f"(d[49]), "+f"(d[50]), "+f"(d[51]), "+f"(d[52]), "+f"(d[53]), "+f"(d[54]), "+f"(d[55]), "+f"(d[56]), "+f"(d[57]), "+f"(d[58]), "+f"(d[59]), "+f"(d[60]), "+f"(d[61]), "+f"(d[62]), "+f"(d[63])
        : "r"(a0), "r"(a1), "r"(a2), "r"(a3), "l"(db), "r"(sd));
}
__device__ __forceinline__ void wgmma_rs_n128_tb(float (&d)[64], uint32_t a0, uint32_t a1, uint32_t a2, uint32_t a3, uint64_t db, int sd) {
    asm volatile("{\n.reg .pred p;\nsetp.ne.b32 p, %69, 0;\n"
        "wgmma.mma_async.sync.aligned.m64n128k16.f32.bf16.bf16 "
        "{%0, %1, %2, %3, %4, %5, %6, %7, %8, %9, %10, %11, %12, %13, %14, %15, %16, %17, %18, %19, %20, %21, %22, %23, %24, %25, %26, %27, %28, %29, %30, %31, %32, %33, %34, %35, %36, %37, %38, %39, %40, %41, %42, %43, %44, %45, %46, %47, %48, %49, %50, %51, %52, %53, %54, %55, %56, %57, %58, %59, %60, %61, %62, %63}, "
        "{%64, %65, %66, %67}, %68, p, 1, 1, 1;\n}\n"
        : "+f"(d[0]), "+f"(d[1]), "+f"(d[2]), "+f"(d[3]), "+f"(d[4]), "+f"(d[5]), "+f"(d[6]), "+f"(d[7]), "+f"(d[8]), "+f"(d[9]), "+f"(d[10]), "+f"(d[11]), "+f"(d[12]), "+f"(d[13]), "+f"(d[14]), "+f"(d[15]), "+f"(d[16]), "+f"(d[17]), "+f"(d[18]), "+f"(d[19]), "+f"(d[20]), "+f"(d[21]), "+f"(d[22]), "+f"(d[23]), "+f"(d[24]), "+f"(d[25]), "+f"(d[26]), "+f"(d[27]), "+f"(d[28]), "+f"(d[29]), "+f"(d[30]), "+f"(d[31]), "+f"(d[32]), "+f"(d[33]), "+f"(d[34]), "+f"(d[35]), "+f"(d[36]), "+f"(d[37]), "+f"(d[38]), "+f"(d[39]), "+f"(d[40]), "+f"(d[41]), "+f"(d[42]), "+f"(d[43]), "+f"(d[44]), "+f"(d[45]), "+f"(d[46]), "+f"(d[47]), "+f"(d[48]), "+f"(d[49]), "+f"(d[50]), "+f"(d[51]), "+f"(d[52]), "+f"(d[53]), "+f"(d[54]), "+f"(d[55]), "+f"(d[56]), "+f"(d[57]), "+f"(d[58]), "+f"(d[59]), "+f"(d[60]), "+f"(d[61]), "+f"(d[62]), "+f"(d[63])
        : "r"(a0), "r"(a1), "r"(a2), "r"(a3), "l"(db), "r"(sd));
}
__device__ __forceinline__ void wgmma_rs_n64_tb(float (&d)[32], uint32_t a0, uint32_t a1, uint32_t a2, uint32_t a3, uint64_t db, int sd) {
    asm volatile("{\n.reg .pred p;\nsetp.ne.b32 p, %37, 0;\n"
        "wgmma.mma_async.sync.aligned.m64n64k16.f32.bf16.bf16 "
        "{%0, %1, %2, %3, %4, %5, %6, %7, %8, %9, %10, %11, %12, %13, %14, %15, %16, %17, %18, %19, %20, %21, %22, %23, %24, %25, %26, %27, %28, %29, %30, %31}, "
        "{%32, %33, %34, %35}, %36, p, 1, 1, 1;\n}\n"
        : "+f"(d[0]), "+f"(d[1]), "+f"(d[2]), "+f"(d[3]), "+f"(d[4]), "+f"(d[5]), "+f"(d[6]), "+f"(d[7]), "+f"(d[8]), "+f"(d[9]), "+f"(d[10]), "+f"(d[11]), "+f"(d[12]), "+f"(d[13]), "+f"(d[14]), "+f"(d[15]), "+f"(d[16]), "+f"(d[17]), "+f"(d[18]), "+f"(d[19]), "+f"(d[20]), "+f"(d[21]), "+f"(d[22]), "+f"(d[23]), "+f"(d[24]), "+f"(d[25]), "+f"(d[26]), "+f"(d[27]), "+f"(d[28]), "+f"(d[29]), "+f"(d[30]), "+f"(d[31])
        : "r"(a0), "r"(a1), "r"(a2), "r"(a3), "l"(db), "r"(sd));
}

__global__ void __launch_bounds__(384, 1) fused_gqa_kernel(const __grid_constant__ Params P) {
    extern __shared__ uint8_t smem_raw[];
    const uint32_t base = (smem_u32(smem_raw) + 1023u) & ~1023u;
    const uint32_t smR = base;
    const uint32_t smS = base + R_BYTES;
    const uint32_t bars = smS + NSTAGE * STAGE_BYTES;
    const uint32_t prog = bars + 8 * (2 * NSTAGE + 10);
    const int tid = threadIdx.x;
    const int wid = __shfl_sync(0xffffffffu, tid >> 5, 0);
    const int lane = tid & 31;

    const int cta = blockIdx.x;
    const int blk = cta >> 6;
    const int hp = (cta >> 3) & 7;
    const int b = cta & 7;
    const int grp = blk * 8 + b;

    if (tid == 0) {
        TS(0);
        for (int i = 0; i < NSTAGE; i++) {
            mbar_init(bars + 8 * i, 1);
            mbar_init(bars + 8 * (NSTAGE + i), 8);
        }
        for (int i = 0; i < 10; i++) mbar_init(bars + 8 * (2 * NSTAGE + i), 4);
        asm volatile("st.volatile.shared.u32 [%0], %1;" ::"r"(prog), "r"(0) : "memory");
        asm volatile("fence.mbarrier_init.release.cluster;" ::: "memory");
        asm volatile("fence.proxy.async.shared::cta;" ::: "memory");
    }
    __syncthreads();

    if (wid >= 8) {
        asm volatile("setmaxnreg.dec.sync.aligned.u32 40;");
        if (wid == 8) {
            if (lane == 0) {
                int slot = 0, ph = 1;
                for (int s = 0; s < N_WQ; s++) {
                    const uint32_t fb = bars + 8 * slot;
                    mbar_wait(bars + 8 * (NSTAGE + slot), ph);
                    const uint32_t dst = smS + slot * STAGE_BYTES;
                    mbar_expect_tx(fb, (s & 1) ? STAGE_BYTES : STAGE_BYTES + 8192);
                    if (!(s & 1)) tma_2d(smR + ((s >> 1) & 7) * 8192, &P.x[blk], (s >> 1) * 64, b * 64, fb);
#pragma unroll
                    for (int p = 0; p < 4; p++) {
                        const int w = p >> 1, j = p & 1;
                        tma_3d(dst + p * 8192, &P.wq[blk], 0, s * 32, hp * 8 + j * 4 + w * 2, fb);
                    }
                    if (++slot == NSTAGE) { slot = 0; ph ^= 1; }
                }
                for (int i = 0; i < 34; i++) {
                    const uint32_t fb = bars + 8 * slot;
                    mbar_wait(bars + 8 * (NSTAGE + slot), ph);
                    const uint32_t dst = smS + slot * STAGE_BYTES;
                    mbar_expect_tx(fb, STAGE_BYTES);
                    if (i < 16) {
                        const int row = (b * kHkv + hp * 2) * kSk + (i >> 1) * 128;
                        const CUtensorMap* tm = (i & 1) ? &P.v[blk] : &P.k[blk];
                        tma_3d(dst, tm, 0, row, 0, fb);
                    } else {
                        const int q = i - 18;
                        if (q >= 0) {
                            const int g0 = (q >> 3) * 4, r0 = hp * 512 + (q & 7) * 64, r1 = hp * 512 + ((q & 7) ^ 2) * 64;
                            tma_3d(dst, &P.wo[blk], 0, r0, g0, fb);
                            tma_3d(dst + 16384, &P.wo[blk], 0, r1, g0 + 2, fb);
                        } else {
                            const int r0 = hp * 512 + (17 - i) * 256;
                            tma_2d(dst, &P.wo8[blk], 512, r0, fb);
                            tma_2d(dst + 16384, &P.wo8[blk], 512, r0 + 128, fb);
                        }
                    }
                    asm volatile("st.volatile.shared.u32 [%0], %1;" ::"r"(prog), "r"(i + 1) : "memory");
                    if (++slot == NSTAGE) { slot = 0; ph ^= 1; }
                }
            }
        } else if (wid == 11) {
            if (PF_DIST > 0) {
                uint32_t sink = 0;
                mbar_wait(bars, 0);
                if (PF_WQ) {
                    const char* wqs = (const char*)(P.wqp[blk] + hp * 512) + (size_t)(160 + b * 52) * 8192;
#pragma unroll
                    for (int h = 0; h < 2; h++) {
#pragma unroll
                        for (int j = 0; j < 4; j++) {
                            const int e = (h * 4 + j) * 32 + lane;
                            if (e < 208) sink |= l2_touch(wqs + (size_t)(e >> 2) * 8192 + (e & 3) * 256);
                        }
                        if (sink == 0x9E3779B9u) asm volatile("st.volatile.shared.u32 [%0], %1;" ::"r"(prog + 4), "r"(sink) : "memory");
                    }
                }
                const char* kbase = (const char*)(P.kp[blk] + (size_t)(b * kHkv + hp * 2) * kSk * kDh);
                const char* vbase = (const char*)(P.vp[blk] + (size_t)(b * kHkv + hp * 2) * kSk * kDh);
                const char* wos = (const char*)(P.wop[blk] + (size_t)hp * 512 * kD) + (size_t)b * 73728;
#define WO_POS 16
#define WO_FULL 0
                for (int ii = 0; ii < 17; ii++) {
                    const bool is_wo = (ii == WO_POS);
                    const int i = (ii > WO_POS) ? ii - 1 : ii;
                    if (i >= PF_DIST) {
                        uint32_t pr, n = 0;
                        while (true) {
                            asm volatile("ld.volatile.shared.u32 %0, [%1];" : "=r"(pr) : "r"(prog) : "memory");
                            if ((int)pr + PF_DIST >= i) break;
                            if (++n > (1u << 22)) break;
                            __nanosleep(100);
                        }
                    }
                    if (!is_wo) {
                        const char* p = ((i & 1) ? vbase : kbase) + (size_t)(i >> 1) * 32768 + lane * 256;
#pragma unroll
                        for (int j = 0; j < 4; j++) sink |= l2_touch(p + j * 8192);
                        if (sink == 0x9E3779B9u) asm volatile("st.volatile.shared.u32 [%0], %1;" ::"r"(prog + 4), "r"(sink) : "memory");
                    } else {
                        for (int h = 0; h < (WO_FULL ? 24 : 3); h++) {
                            const char* p = (WO_FULL ? (wos - (size_t)b * 73728 + (size_t)((h + 3 * b) % 24) * 24576) : (wos + (size_t)h * 24576)) + lane * 256;
#pragma unroll
                            for (int j = 0; j < 3; j++) sink |= l2_touch(p + j * 8192);
                            if (sink == 0x9E3779B9u) asm volatile("st.volatile.shared.u32 [%0], %1;" ::"r"(prog + 4), "r"(sink) : "memory");
                        }
                    }
                }
            }
        } else {
            const int hw = wid - 9;
            for (int k = 0; k < 2; k++) {
                mbar_wait(bars + 8 * (2 * NSTAGE + hw * 5 + k), 0);
                const int c = k ? hw : 4;
                asm volatile("fence.acq_rel.gpu;" ::: "memory");
                asm volatile("red.relaxed.gpu.global.add.u32 [%0], 1;" ::"l"(&g_cnt[(grp * 9 + c) * 32 + lane]) : "memory");
            }
        }
    } else {
        asm volatile("setmaxnreg.inc.sync.aligned.u32 232;");
        const int w = wid >> 2;
        const int t = tid & 127;
        int slot = 0, ph = 0;
        uint32_t qf[8][4];
        const uint32_t stash = smR + (1 + w) * 16384 + t * 16;
        {
            float acc[128];
            int pslot = 0;
            for (int s = 0; s < N_WQ; s++) {
                mbar_wait(bars + 8 * slot, ph);
                if (tid == 0 && s == 0) TS(20);
                if (tid == 0 && s == 5) TS(21);
                if (tid == 0 && s == 10) TS(22);
                const uint64_t da = mk_desc(smR + ((s >> 1) & 7) * 8192 + (s & 1) * 64, 16, 1024);
                const uint64_t db = mk_desc(smS + slot * STAGE_BYTES + w * 16384, 4096, 1024);
                wg_fence();
                wgmma_ss_n256_tb(acc, da, db, s != 0);
                wgmma_ss_n256_tb(acc, da + 2, db + 128, 1);
                wg_commit();
                wg_wait<0>();
                if (lane == 0) mbar_arrive(bars + 8 * (NSTAGE + slot));
                pslot = slot;
                if (++slot == NSTAGE) { slot = 0; ph ^= 1; }
            }
            fence_regs(acc);
            if (tid == 0) TS(1);
#pragma unroll
            for (int kk = 0; kk < 8; kk++) {
#pragma unroll
                for (int i = 0; i < 4; i++) qf[kk][i] = pack_bf16(acc[8 * kk + 2 * i], acc[8 * kk + 2 * i + 1]);
                sts128(stash + kk * 2048,
                       pack_bf16(acc[64 + 8 * kk + 0], acc[64 + 8 * kk + 1]), pack_bf16(acc[64 + 8 * kk + 2], acc[64 + 8 * kk + 3]),
                       pack_bf16(acc[64 + 8 * kk + 4], acc[64 + 8 * kk + 5]), pack_bf16(acc[64 + 8 * kk + 6], acc[64 + 8 * kk + 7]));
            }
        }
        if (w == 1) bar_arrive<5, 256>();
        const float sc = 0.08838834764831845f * 1.4426950408889634f;
        uint32_t af[32][4];
#pragma unroll
        for (int u = 0; u < 2; u++) {
            {
                if (u == 1) {
#pragma unroll
                    for (int kk = 0; kk < 8; kk++) lds128(stash + kk * 2048, qf[kk]);
                }
                float o[64], s[64];
                float m0 = -INFINITY, m1 = -INFINITY, l0 = 0.f, l1 = 0.f;
                uint32_t pf[8][4];
#pragma unroll
                for (int i = 0; i < 64; i++) { o[i] = 0.f; s[i] = 0.f; }
#pragma unroll
                for (int i = 0; i < 32; i++) pf[i >> 2][i & 3] = 0u;
#pragma unroll 1
                for (int tt = 0; tt <= 4; tt++) {
                    int vslot = slot;
                    if (tt > 0) {
                        mbar_wait(bars + 8 * slot, ph);
                        if (++slot == NSTAGE) { slot = 0; ph ^= 1; }
                    }
                    if (tt < 4) mbar_wait(bars + 8 * slot, ph);
                    if (tid == 0) TS(32 + u * 20 + tt * 4);
                    if (w == 0) bar_sync<5, 256>(); else bar_sync<6, 256>();
                    wg_fence();
                    if (tt > 0) {
                        const uint64_t db = mk_desc(smS + vslot * STAGE_BYTES, 16384, 1024);
#pragma unroll
                        for (int kk = 0; kk < 8; kk++)
                            wgmma_rs_n128_tb(o, pf[kk][0], pf[kk][1], pf[kk][2], pf[kk][3], db + kk * 128, (tt > 1) || (kk != 0));
                        wg_commit();
                    }
                    if (tt < 4) {
                        const uint64_t db = mk_desc(smS + slot * STAGE_BYTES, 16, 1024);
#pragma unroll
                        for (int kk = 0; kk < 8; kk++)
                            wgmma_rs_n128(s, qf[kk][0], qf[kk][1], qf[kk][2], qf[kk][3], db + (kk >> 2) * 1024 + (kk & 3) * 2, kk != 0);
                        wg_commit();
                    }
                    if (w == 0) bar_arrive<6, 256>(); else if (!(u == 1 && tt == 4)) bar_arrive<5, 256>();
                    if (tid == 0) TS(32 + u * 20 + tt * 4 + 1);
                    wg_wait<0>();
                    fence_regs(o);
                    fence_regs(s);
                    if (tid == 0) TS(32 + u * 20 + tt * 4 + 2);
                    if (tt > 0 && lane == 0) mbar_arrive(bars + 8 * (NSTAGE + vslot));
                    if (tt == 4) break;
                    if (lane == 0) mbar_arrive(bars + 8 * (NSTAGE + slot));
                    if (++slot == NSTAGE) { slot = 0; ph ^= 1; }
                    float mx0 = s[0], mx1 = s[2];
#pragma unroll
                    for (int j = 0; j < 16; j++) {
                        mx0 = fmaxf(mx0, fmaxf(s[4 * j], s[4 * j + 1]));
                        mx1 = fmaxf(mx1, fmaxf(s[4 * j + 2], s[4 * j + 3]));
                    }
                    mx0 = fmaxf(mx0, __shfl_xor_sync(0xffffffffu, mx0, 1));
                    mx1 = fmaxf(mx1, __shfl_xor_sync(0xffffffffu, mx1, 1));
                    mx0 = fmaxf(mx0, __shfl_xor_sync(0xffffffffu, mx0, 2));
                    mx1 = fmaxf(mx1, __shfl_xor_sync(0xffffffffu, mx1, 2));
                    const float mn0 = fmaxf(m0, mx0), mn1 = fmaxf(m1, mx1);
                    const float al0 = ex2((m0 - mn0) * sc), al1 = ex2((m1 - mn1) * sc);
                    m0 = mn0; m1 = mn1;
                    const float ms0 = mn0 * sc, ms1 = mn1 * sc;
                    float rs0 = 0.f, rs1 = 0.f;
#pragma unroll
                    for (int j = 0; j < 16; j++) {
                        const float p0 = ex2(fmaf(s[4 * j], sc, -ms0)), p1 = ex2(fmaf(s[4 * j + 1], sc, -ms0));
                        const float p2 = ex2(fmaf(s[4 * j + 2], sc, -ms1)), p3 = ex2(fmaf(s[4 * j + 3], sc, -ms1));
                        rs0 += p0 + p1; rs1 += p2 + p3;
                        pf[j >> 1][(j & 1) * 2] = pack_bf16(p0, p1);
                        pf[j >> 1][(j & 1) * 2 + 1] = pack_bf16(p2, p3);
                    }
                    l0 = l0 * al0 + rs0; l1 = l1 * al1 + rs1;
                    if (tt > 0) {
#pragma unroll
                        for (int j = 0; j < 16; j++) { o[4 * j] *= al0; o[4 * j + 1] *= al0; o[4 * j + 2] *= al1; o[4 * j + 3] *= al1; }
                    }
                    if (tid == 0) TS(32 + u * 20 + tt * 4 + 3);
                }
                if (tid == 0) TS(2 + u);
                l0 += __shfl_xor_sync(0xffffffffu, l0, 1);
                l1 += __shfl_xor_sync(0xffffffffu, l1, 1);
                l0 += __shfl_xor_sync(0xffffffffu, l0, 2);
                l1 += __shfl_xor_sync(0xffffffffu, l1, 2);
                const float i0 = 1.f / l0, i1 = 1.f / l1;
                const uint32_t zown = smR + ((u == 0) ? (w ? 3 : 0) : (w ? 2 : 1)) * 16384 + t * 16;
#pragma unroll
                for (int kk = 0; kk < 8; kk++) {
                    af[16 + kk][0] = pack_bf16(o[8 * kk + 0] * i0, o[8 * kk + 1] * i0);
                    af[16 + kk][1] = pack_bf16(o[8 * kk + 2] * i1, o[8 * kk + 3] * i1);
                    af[16 + kk][2] = pack_bf16(o[8 * kk + 4] * i0, o[8 * kk + 5] * i0);
                    af[16 + kk][3] = pack_bf16(o[8 * kk + 6] * i1, o[8 * kk + 7] * i1);
                    sts128(zown + kk * 2048, af[16 + kk][0], af[16 + kk][1], af[16 + kk][2], af[16 + kk][3]);
                }
            }
        }
        if (w == 0) bar_arrive<7, 256>(); else bar_arrive<8, 256>();
        {
#pragma unroll
            for (int kk = 0; kk < 8; kk++) {
                lds128(smR + (w ? 3 : 0) * 16384 + kk * 2048 + t * 16, af[kk]);
                lds128(smR + (w ? 0 : 3) * 16384 + kk * 2048 + t * 16, af[8 + kk]);
            }
            uint2* dst0 = g_part + (size_t)(grp * 80 + 2 * w * 8 + hp) * 1024 + t;
            uint2* dst8 = g_part + (size_t)(grp * 80 + 64 + hp * 2 + w) * 1024 + t;
            {
                float acc[32];
#pragma unroll
                for (int i = 0; i < 32; i++) acc[i] = 0.f;
#pragma unroll
                for (int st = 0; st < 2; st++) {
                    mbar_wait(bars + 8 * slot, ph);
                    const uint64_t db = mk_desc(smS + slot * STAGE_BYTES + w * 16384, 8192, 1024);
                    wg_fence();
#pragma unroll
                    for (int kk = 0; kk < 8; kk++)
                        wgmma_rs_n64_tb(acc, af[(1 - st) * 16 + kk][0], af[(1 - st) * 16 + kk][1], af[(1 - st) * 16 + kk][2], af[(1 - st) * 16 + kk][3], db + kk * 128, (st | kk) != 0);
                    wg_commit();
                    wg_wait<0>();
                    if (lane == 0) mbar_arrive(bars + 8 * (NSTAGE + slot));
                    if (++slot == NSTAGE) { slot = 0; ph ^= 1; }
                }
                fence_regs(acc);
#pragma unroll
                for (int j = 0; j < 8; j++)
                    __stcg(dst8 + j * 128, make_uint2(pack_bf16(acc[4 * j], acc[4 * j + 1]), pack_bf16(acc[4 * j + 2], acc[4 * j + 3])));
                __syncwarp();
                if (lane == 0) mbar_arrive(bars + 8 * (2 * NSTAGE + w * 5 + 0));
                if (tid == 0) TS(8);
            }
#pragma unroll
            for (int ps = 0; ps < 2; ps++) {
                float acc[64];
#pragma unroll
                for (int i = 0; i < 64; i++) acc[i] = 0.f;
                int pslot = 0;
#pragma unroll
                for (int st = 0; st < 8; st++) {
                    if (ps == 0 && st == 5) {
                        if (w == 0) bar_sync<8, 256>(); else bar_sync<7, 256>();
#pragma unroll
                        for (int kk = 0; kk < 8; kk++) lds128(smR + (w ? 1 : 2) * 16384 + kk * 2048 + t * 16, af[24 + kk]);
                    }
                    mbar_wait(bars + 8 * slot, ph);
                    if (tid == 0) TS(80 + ps * 16 + 2 * st);
                    const uint64_t db = mk_desc(smS + slot * STAGE_BYTES + w * 16384, 8192, 1024);
                    wg_fence();
#pragma unroll
                    for (int kk = 0; kk < 4; kk++)
                        wgmma_rs_n128_tb(acc, af[st * 4 + kk][0], af[st * 4 + kk][1], af[st * 4 + kk][2], af[st * 4 + kk][3], db + kk * 128, (st | kk) != 0);
                    wg_commit();
                    wg_wait<0>();
                    if (lane == 0) mbar_arrive(bars + 8 * (NSTAGE + slot));
                    if (tid == 0) TS(80 + ps * 16 + 2 * st + 1);
                    pslot = slot;
                    if (++slot == NSTAGE) { slot = 0; ph ^= 1; }
                }
                fence_regs(acc);
                uint2* dst = dst0 + (size_t)ps * 32 * 1024;
#pragma unroll
                for (int j = 0; j < 16; j++)
                    __stcg(dst + (j >> 3) * 8192 + (j & 7) * 128, make_uint2(pack_bf16(acc[4 * j], acc[4 * j + 1]), pack_bf16(acc[4 * j + 2], acc[4 * j + 3])));
                __syncwarp();
                if (ps == 0) {
                    if (lane == 0) mbar_arrive(bars + 8 * (2 * NSTAGE + w * 5 + 1));
                } else if (lane < 8) {
                    asm volatile("red.release.gpu.global.add.u32 [%0], 1;" ::"l"(&g_cnt[(grp * 9 + 2 + w) * 32 + lane * 4 + (wid & 3)]) : "memory");
                }
                if (tid == 0) TS(4 + ps);
            }
        }
        {
            const int nch = (w == 0) ? 3 : 2;
            if (lane < nch) {
                const int c = (lane < 2) ? (2 * lane + w) : 4;
                const unsigned need = (lane < 2) ? 8u : 16u;
                unsigned* cp = &g_cnt[(grp * 9 + c) * 32 + hp * 4 + (wid & 3)];
                unsigned v, n = 0;
                while (true) {
                    asm volatile("ld.acquire.gpu.global.u32 %0, [%1];" : "=r"(v) : "l"(cp) : "memory");
                    if (v >= need) break;
                    if (++n > (1u << 21)) break;
                }
                *cp = 0;
            }
            __syncwarp();
            if (tid == 0) TS(18);
            __nv_bfloat16* orow = P.out + (size_t)(b * 64 + (t >> 5) * 16 + (lane >> 2)) * (2 * kD) + blk * kD + hp * 8 + (lane & 3) * 2;
            const uint2* src = g_part + ((size_t)(grp * 80 + 2 * w * 8) * 8 + hp) * 128 + t;
            uint2 v[4][8];
#pragma unroll
            for (int k = 0; k < 4; k++)
#pragma unroll
                for (int i = 0; i < 8; i++) v[k][i] = __ldcg(src + (size_t)((k >> 1) * 32 + (k & 1) * 8 + i) * 1024);
            if (w == 0) {
                const uint2* src8 = g_part + ((size_t)(grp * 80 + 64) * 8 + hp) * 128 + t;
                uint2 u[16];
#pragma unroll
                for (int i = 0; i < 16; i++) u[i] = __ldcg(src8 + (size_t)i * 1024);
                float a0 = 0.f, a1 = 0.f, a2 = 0.f, a3 = 0.f;
#pragma unroll
                for (int i = 0; i < 16; i++) {
                    a0 += __uint_as_float(u[i].x << 16); a1 += __uint_as_float(u[i].x & 0xffff0000u);
                    a2 += __uint_as_float(u[i].y << 16); a3 += __uint_as_float(u[i].y & 0xffff0000u);
                }
                *(uint32_t*)(orow + 512) = pack_bf16(a0, a1);
                *(uint32_t*)(orow + 512 + 8 * 2 * kD) = pack_bf16(a2, a3);
            }
#pragma unroll
            for (int k = 0; k < 4; k++) {
                float a0 = 0.f, a1 = 0.f, a2 = 0.f, a3 = 0.f;
#pragma unroll
                for (int i = 0; i < 8; i++) {
                    a0 += __uint_as_float(v[k][i].x << 16); a1 += __uint_as_float(v[k][i].x & 0xffff0000u);
                    a2 += __uint_as_float(v[k][i].y << 16); a3 += __uint_as_float(v[k][i].y & 0xffff0000u);
                }
                *(uint32_t*)(orow + ((k >> 1) * 4 + 2 * w + (k & 1)) * 64) = pack_bf16(a0, a1);
                *(uint32_t*)(orow + ((k >> 1) * 4 + 2 * w + (k & 1)) * 64 + 8 * 2 * kD) = pack_bf16(a2, a3);
            }
            if (tid == 0) TS(19);
        }
    }
}

typedef CUresult (*EncodeFn)(CUtensorMap*, CUtensorMapDataType, cuuint32_t, void*, const cuuint64_t*, const cuuint64_t*,
                             const cuuint32_t*, const cuuint32_t*, CUtensorMapInterleave, CUtensorMapSwizzle,
                             CUtensorMapL2promotion, CUtensorMapFloatOOBfill);

void make_map(EncodeFn fn, CUtensorMap* m, const void* ptr, uint64_t cols, uint64_t rows, uint32_t box_rows) {
    cuuint64_t dims[2] = {cols, rows};
    cuuint64_t strides[1] = {cols * 2};
    cuuint32_t box[2] = {64, box_rows};
    cuuint32_t es[2] = {1, 1};
    fn(m, CU_TENSOR_MAP_DATA_TYPE_BFLOAT16, 2, const_cast<void*>(ptr), dims, strides, box, es, CU_TENSOR_MAP_INTERLEAVE_NONE,
       CU_TENSOR_MAP_SWIZZLE_128B, CU_TENSOR_MAP_L2_PROMOTION_L2_256B, CU_TENSOR_MAP_FLOAT_OOB_FILL_NONE);
}

void make_map3(EncodeFn fn, CUtensorMap* m, const void* ptr, uint64_t cols, uint64_t rows, uint32_t box_rows, uint32_t box_groups) {
    cuuint64_t dims[3] = {64, rows, cols / 64};
    cuuint64_t strides[2] = {cols * 2, 128};
    cuuint32_t box[3] = {64, box_rows, box_groups};
    cuuint32_t es[3] = {1, 1, 1};
    fn(m, CU_TENSOR_MAP_DATA_TYPE_BFLOAT16, 3, const_cast<void*>(ptr), dims, strides, box, es, CU_TENSOR_MAP_INTERLEAVE_NONE,
       CU_TENSOR_MAP_SWIZZLE_128B, CU_TENSOR_MAP_L2_PROMOTION_L2_256B, CU_TENSOR_MAP_FLOAT_OOB_FILL_NONE);
}

}

extern "C" void kernel_launch(void* const* d_in, const int* in_sizes, int n_in, void* d_out, int out_size) {
    static EncodeFn enc = nullptr;
    if (!enc) {
        void* fn = nullptr;
        cudaDriverEntryPointQueryResult st;
        cudaGetDriverEntryPoint("cuTensorMapEncodeTiled", &fn, cudaEnableDefault, &st);
        enc = (EncodeFn)fn;
        cudaFuncSetAttribute(fused_gqa_kernel, cudaFuncAttributeMaxDynamicSharedMemorySize, SMEM_BYTES);
    }
    Params P;
    for (int blk = 0; blk < 2; blk++) {
        const void* x = d_in[blk * 5 + 0];
        const void* k = d_in[blk * 5 + 1];
        const void* v = d_in[blk * 5 + 2];
        const void* wq = d_in[blk * 5 + 3];
        const void* wo = d_in[blk * 5 + 4];
        make_map(enc, &P.x[blk], x, kD, kB * kSq, 64);
        make_map3(enc, &P.wq[blk], wq, kHq * kDh, kD, 32, 2);
        make_map3(enc, &P.k[blk], k, kDh, (uint64_t)kB * kHkv * kSk, 128, 2);
        make_map3(enc, &P.v[blk], v, kDh, (uint64_t)kB * kHkv * kSk, 128, 2);
        make_map3(enc, &P.wo[blk], wo, kD, kHq * kDh, 64, 2);
        make_map(enc, &P.wo8[blk], wo, kD, kHq * kDh, 128);
        P.wqp[blk] = (const __nv_bfloat16*)wq;
        P.kp[blk] = (const __nv_bfloat16*)k;
        P.vp[blk] = (const __nv_bfloat16*)v;
        P.wop[blk] = (const __nv_bfloat16*)wo;
    }
    P.out = (__nv_bfloat16*)d_out;
    fused_gqa_kernel<<<128, 384, SMEM_BYTES>>>(P);
}
```

```cpp
#include <cuda_runtime.h>
#include <cuda_bf16.h>
#include <cuda.h>
#include <stdint.h>

namespace {

constexpr int kB = 8, kSq = 64, kD = 576, kHq = 32, kHkv = 16, kSk = 512, kDh = 128;
constexpr int NSTAGE = 5;
constexpr int STAGE_BYTES = 32768;
constexpr int R_BYTES = 65536;
constexpr int SMEM_BYTES = R_BYTES + NSTAGE * STAGE_BYTES + 1024   + 256  ;
constexpr int N_WQ = 18;
#define PF_DIST_V 6
#define OP_WAIT0 1
#define QP_WAIT0 1
#define PF_POS1 9
#define PF_WQ 0
#define PF_SLEEP 1000
constexpr int PF_DIST = PF_DIST_V;

struct __align__(64) Params {
    CUtensorMap x[2], wq[2], k[2], v[2], wo[2], wo8[2];
    const __nv_bfloat16* wqp[2];
    const __nv_bfloat16* kp[2];
    const __nv_bfloat16* vp[2];
    const __nv_bfloat16* wop[2];
    __nv_bfloat16* out;
};

__device__ uint2 g_part[16 * 80 * 8 * 128];
__device__ unsigned int g_cnt[16 * 9 * 32];
#define TS(k) do {} while (0)

__device__ __forceinline__ uint32_t smem_u32(const void* p) { return (uint32_t)__cvta_generic_to_shared(p); }
__device__ __forceinline__ void mbar_init(uint32_t bar, int cnt) {
    asm volatile("mbarrier.init.shared::cta.b64 [%0], %1;" ::"r"(bar), "r"(cnt));
}
__device__ __forceinline__ void mbar_expect_tx(uint32_t bar, uint32_t bytes) {
    asm volatile("mbarrier.arrive.expect_tx.shared::cta.b64 _, [%0], %1;" ::"r"(bar), "r"(bytes) : "memory");
}
__device__ __forceinline__ void mbar_arrive(uint32_t bar) {
    asm volatile("mbarrier.arrive.shared::cta.b64 _, [%0];" ::"r"(bar) : "memory");
}
__device__ __forceinline__ bool mbar_try(uint32_t bar, uint32_t parity) {
    uint32_t ok;
    asm volatile("{\n.reg .pred p;\nmbarrier.try_wait.parity.shared::cta.b64 p, [%1], %2;\nselp.u32 %0, 1, 0, p;\n}\n"
                 : "=r"(ok) : "r"(bar), "r"(parity) : "memory");
    return ok != 0;
}
__device__ __forceinline__ void mbar_wait(uint32_t bar, uint32_t parity) {
    if (mbar_try(bar, parity)) return;
    uint32_t n = 0;
    while (!mbar_try(bar, parity)) {
        if (++n > (1u << 20)) break;
    }
}
__device__ __forceinline__ void tma_2d(uint32_t dst, const CUtensorMap* tm, int c0, int c1, uint32_t bar) {
    asm volatile("cp.async.bulk.tensor.2d.shared::cluster.global.mbarrier::complete_tx::bytes [%0], [%1, {%3, %4}], [%2];"
                 ::"r"(dst), "l"(tm), "r"(bar), "r"(c0), "r"(c1) : "memory");
}
__device__ __forceinline__ void tma_3d(uint32_t dst, const CUtensorMap* tm, int c0, int c1, int c2, uint32_t bar) {
    asm volatile("cp.async.bulk.tensor.3d.shared::cluster.global.mbarrier::complete_tx::bytes [%0], [%1, {%3, %4, %5}], [%2];"
                 ::"r"(dst), "l"(tm), "r"(bar), "r"(c0), "r"(c1), "r"(c2) : "memory");
}
__device__ __forceinline__ void l2_prefetch(const void* p, uint32_t bytes) {
    asm volatile("cp.async.bulk.prefetch.L2.global [%0], %1;" ::"l"(p), "r"(bytes) : "memory");
}
__device__ __forceinline__ uint32_t l2_touch(const void* p) {
    uint32_t v;
    asm volatile("ld.global.L2::256B.b32 %0, [%1];" : "=r"(v) : "l"(p) : "memory");
    return v;
}
__device__ __forceinline__ void wg_fence() { asm volatile("wgmma.fence.sync.aligned;" ::: "memory"); }
__device__ __forceinline__ void wg_commit() { asm volatile("wgmma.commit_group.sync.aligned;" ::: "memory"); }
template <int N> __device__ __forceinline__ void wg_wait() { asm volatile("wgmma.wait_group.sync.aligned %0;" ::"n"(N) : "memory"); }
template <int N> __device__ __forceinline__ void fence_regs(float (&d)[N]) {
#pragma unroll
    for (int i = 0; i < N; i++) asm volatile("" : "+f"(d[i])::"memory");
}
__device__ __forceinline__ uint64_t mk_desc(uint32_t addr, uint32_t lbo, uint32_t sbo) {
    return (uint64_t)((addr & 0x3FFFF) >> 4) | ((uint64_t)(lbo >> 4) << 16) | ((uint64_t)(sbo >> 4) << 32) | (1ull << 62);
}
__device__ __forceinline__ uint32_t pack_bf16(float a, float b) {
    uint32_t r;
    asm("cvt.rn.bf16x2.f32 %0, %1, %2;" : "=r"(r) : "f"(b), "f"(a));
    return r;
}
__device__ __forceinline__ float ex2(float x) {
    float y;
    asm("ex2.approx.ftz.f32 %0, %1;" : "=f"(y) : "f"(x));
    return y;
}
template <int ID, int N> __device__ __forceinline__ void bar_sync() { asm volatile("bar.sync %0, %1;" ::"n"(ID), "n"(N) : "memory"); }
template <int ID, int N> __device__ __forceinline__ void bar_arrive() { asm volatile("bar.arrive %0, %1;" ::"n"(ID), "n"(N) : "memory"); }
__device__ __forceinline__ void sts128(uint32_t addr, uint32_t a, uint32_t b, uint32_t c, uint32_t d) {
    asm volatile("st.shared.v4.b32 [%0], {%1,%2,%3,%4};" ::"r"(addr), "r"(a), "r"(b), "r"(c), "r"(d) : "memory");
}
__device__ __forceinline__ void lds128(uint32_t addr, uint32_t (&r)[4]) {
    asm volatile("ld.shared.v4.b32 {%0,%1,%2,%3}, [%4];" : "=r"(r[0]), "=r"(r[1]), "=r"(r[2]), "=r"(r[3]) : "r"(addr) : "memory");
}

__device__ __forceinline__ void wgmma_ss_n256_tb(float (&d)[128], uint64_t da, uint64_t db, int sd) {
    asm volatile("{\n.reg .pred p;\nsetp.ne.b32 p, %130, 0;\n"
        "wgmma.mma_async.sync.aligned.m64n256k16.f32.bf16.bf16 "
        "{%0, %1, %2, %3, %4, %5, %6, %7, %8, %9, %10, %11, %12, %13, %14, %15, %16, %17, %18, %19, %20, %21, %22, %23, %24, %25, %26, %27, %28, %29, %30, %31, %32, %33, %34, %35, %36, %37, %38, %39, %40, %41, %42, %43, %44, %45, %46, %47, %48, %49, %50, %51, %52, %53, %54, %55, %56, %57, %58, %59, %60, %61, %62, %63, %64, %65, %66, %67, %68, %69, %70, %71, %72, %73, %74, %75, %76, %77, %78, %79, %80, %81, %82, %83, %84, %85, %86, %87, %88, %89, %90, %91, %92, %93, %94, %95, %96, %97, %98, %99, %100, %101, %102, %103, %104, %105, %106, %107, %108, %109, %110, %111, %112, %113, %114, %115, %116, %117, %118, %119, %120, %121, %122, %123, %124, %125, %126, %127}, "
        "%128, %129, p, 1, 1, 0, 1;\n}\n"
        : "+f"(d[0]), "+f"(d[1]), "+f"(d[2]), "+f"(d[3]), "+f"(d[4]), "+f"(d[5]), "+f"(d[6]), "+f"(d[7]), "+f"(d[8]), "+f"(d[9]), "+f"(d[10]), "+f"(d[11]), "+f"(d[12]), "+f"(d[13]), "+f"(d[14]), "+f"(d[15]), "+f"(d[16]), "+f"(d[17]), "+f"(d[18]), "+f"(d[19]), "+f"(d[20]), "+f"(d[21]), "+f"(d[22]), "+f"(d[23]), "+f"(d[24]), "+f"(d[25]), "+f"(d[26]), "+f"(d[27]), "+f"(d[28]), "+f"(d[29]), "+f"(d[30]), "+f"(d[31]), "+f"(d[32]), "+f"(d[33]), "+f"(d[34]), "+f"(d[35]), "+f"(d[36]), "+f"(d[37]), "+f"(d[38]), "+f"(d[39]), "+f"(d[40]), "+f"(d[41]), "+f"(d[42]), "+f"(d[43]), "+f"(d[44]), "+f"(d[45]), "+f"(d[46]), "+f"(d[47]), "+f"(d[48]), "+f"(d[49]), "+f"(d[50]), "+f"(d[51]), "+f"(d[52]), "+f"(d[53]), "+f"(d[54]), "+f"(d[55]), "+f"(d[56]), "+f"(d[57]), "+f"(d[58]), "+f"(d[59]), "+f"(d[60]), "+f"(d[61]), "+f"(d[62]), "+f"(d[63]), "+f"(d[64]), "+f"(d[65]), "+f"(d[66]), "+f"(d[67]), "+f"(d[68]), "+f"(d[69]), "+f"(d[70]), "+f"(d[71]), "+f"(d[72]), "+f"(d[73]), "+f"(d[74]), "+f"(d[75]), "+f"(d[76]), "+f"(d[77]), "+f"(d[78]), "+f"(d[79]), "+f"(d[80]), "+f"(d[81]), "+f"(d[82]), "+f"(d[83]), "+f"(d[84]), "+f"(d[85]), "+f"(d[86]), "+f"(d[87]), "+f"(d[88]), "+f"(d[89]), "+f"(d[90]), "+f"(d[91]), "+f"(d[92]), "+f"(d[93]), "+f"(d[94]), "+f"(d[95]), "+f"(d[96]), "+f"(d[97]), "+f"(d[98]), "+f"(d[99]), "+f"(d[100]), "+f"(d[101]), "+f"(d[102]), "+f"(d[103]), "+f"(d[104]), "+f"(d[105]), "+f"(d[106]), "+f"(d[107]), "+f"(d[108]), "+f"(d[109]), "+f"(d[110]), "+f"(d[111]), "+f"(d[112]), "+f"(d[113]), "+f"(d[114]), "+f"(d[115]), "+f"(d[116]), "+f"(d[117]), "+f"(d[118]), "+f"(d[119]), "+f"(d[120]), "+f"(d[121]), "+f"(d[122]), "+f"(d[123]), "+f"(d[124]), "+f"(d[125]), "+f"(d[126]), "+f"(d[127])
        : "l"(da), "l"(db), "r"(sd));
}
__device__ __forceinline__ void wgmma_rs_n128(float (&d)[64], uint32_t a0, uint32_t a1, uint32_t a2, uint32_t a3, uint64_t db, int sd) {
    asm volatile("{\n.reg .pred p;\nsetp.ne.b32 p, %69, 0;\n"
        "wgmma.mma_async.sync.aligned.m64n128k16.f32.bf16.bf16 "
        "{%0, %1, %2, %3, %4, %5, %6, %7, %8, %9, %10, %11, %12, %13, %14, %15, %16, %17, %18, %19, %20, %21, %22, %23, %24, %25, %26, %27, %28, %29, %30, %31, %32, %33, %34, %35, %36, %37, %38, %39, %40, %41, %42, %43, %44, %45, %46, %47, %48, %49, %50, %51, %52, %53, %54, %55, %56, %57, %58, %59, %60, %61, %62, %63}, "
        "{%64, %65, %66, %67}, %68, p, 1, 1, 0;\n}\n"
        : "+f"(d[0]), "+f"(d[1]), "+f"(d[2]), "+f"(d[3]), "+f"(d[4]), "+f"(d[5]), "+f"(d[6]), "+f"(d[7]), "+f"(d[8]), "+f"(d[9]), "+f"(d[10]), "+f"(d[11]), "+f"(d[12]), "+f"(d[13]), "+f"(d[14]), "+f"(d[15]), "+f"(d[16]), "+f"(d[17]), "+f"(d[18]), "+f"(d[19]), "+f"(d[20]), "+f"(d[21]), "+f"(d[22]), "+f"(d[23]), "+f"(d[24]), "+f"(d[25]), "+f"(d[26]), "+f"(d[27]), "+f"(d[28]), "+f"(d[29]), "+f"(d[30]), "+f"(d[31]), "+f"(d[32]), "+f"(d[33]), "+f"(d[34]), "+f"(d[35]), "+f"(d[36]), "+f"(d[37]), "+f"(d[38]), "+f"(d[39]), "+f"(d[40]), "+f"(d[41]), "+f"(d[42]), "+f"(d[43]), "+f"(d[44]), "+f"(d[45]), "+f"(d[46]), "+f"(d[47]), "+f"(d[48]), "+f"(d[49]), "+f"(d[50]), "+f"(d[51]), "+f"(d[52]), "+f"(d[53]), "+f"(d[54]), "+f"(d[55]), "+f"(d[56]), "+f"(d[57]), "+f"(d[58]), "+f"(d[59]), "+f"(d[60]), "+f"(d[61]), "+f"(d[62]), "+f"(d[63])
        : "r"(a0), "r"(a1), "r"(a2), "r"(a3), "l"(db), "r"(sd));
}
__device__ __forceinline__ void wgmma_rs_n128_tb(float (&d)[64], uint32_t a0, uint32_t a1, uint32_t a2, uint32_t a3, uint64_t db, int sd) {
    asm volatile("{\n.reg .pred p;\nsetp.ne.b32 p, %69, 0;\n"
        "wgmma.mma_async.sync.aligned.m64n128k16.f32.bf16.bf16 "
        "{%0, %1, %2, %3, %4, %5, %6, %7, %8, %9, %10, %11, %12, %13, %14, %15, %16, %17, %18, %19, %20, %21, %22, %23, %24, %25, %26, %27, %28, %29, %30, %31, %32, %33, %34, %35, %36, %37, %38, %39, %40, %41, %42, %43, %44, %45, %46, %47, %48, %49, %50, %51, %52, %53, %54, %55, %56, %57, %58, %59, %60, %61, %62, %63}, "
        "{%64, %65, %66, %67}, %68, p, 1, 1, 1;\n}\n"
        : "+f"(d[0]), "+f"(d[1]), "+f"(d[2]), "+f"(d[3]), "+f"(d[4]), "+f"(d[5]), "+f"(d[6]), "+f"(d[7]), "+f"(d[8]), "+f"(d[9]), "+f"(d[10]), "+f"(d[11]), "+f"(d[12]), "+f"(d[13]), "+f"(d[14]), "+f"(d[15]), "+f"(d[16]), "+f"(d[17]), "+f"(d[18]), "+f"(d[19]), "+f"(d[20]), "+f"(d[21]), "+f"(d[22]), "+f"(d[23]), "+f"(d[24]), "+f"(d[25]), "+f"(d[26]), "+f"(d[27]), "+f"(d[28]), "+f"(d[29]), "+f"(d[30]), "+f"(d[31]), "+f"(d[32]), "+f"(d[33]), "+f"(d[34]), "+f"(d[35]), "+f"(d[36]), "+f"(d[37]), "+f"(d[38]), "+f"(d[39]), "+f"(d[40]), "+f"(d[41]), "+f"(d[42]), "+f"(d[43]), "+f"(d[44]), "+f"(d[45]), "+f"(d[46]), "+f"(d[47]), "+f"(d[48]), "+f"(d[49]), "+f"(d[50]), "+f"(d[51]), "+f"(d[52]), "+f"(d[53]), "+f"(d[54]), "+f"(d[55]), "+f"(d[56]), "+f"(d[57]), "+f"(d[58]), "+f"(d[59]), "+f"(d[60]), "+f"(d[61]), "+f"(d[62]), "+f"(d[63])
        : "r"(a0), "r"(a1), "r"(a2), "r"(a3), "l"(db), "r"(sd));
}
__device__ __forceinline__ void wgmma_rs_n64_tb(float (&d)[32], uint32_t a0, uint32_t a1, uint32_t a2, uint32_t a3, uint64_t db, int sd) {
    asm volatile("{\n.reg .pred p;\nsetp.ne.b32 p, %37, 0;\n"
        "wgmma.mma_async.sync.aligned.m64n64k16.f32.bf16.bf16 "
        "{%0, %1, %2, %3, %4, %5, %6, %7, %8, %9, %10, %11, %12, %13, %14, %15, %16, %17, %18, %19, %20, %21, %22, %23, %24, %25, %26, %27, %28, %29, %30, %31}, "
        "{%32, %33, %34, %35}, %36, p, 1, 1, 1;\n}\n"
        : "+f"(d[0]), "+f"(d[1]), "+f"(d[2]), "+f"(d[3]), "+f"(d[4]), "+f"(d[5]), "+f"(d[6]), "+f"(d[7]), "+f"(d[8]), "+f"(d[9]), "+f"(d[10]), "+f"(d[11]), "+f"(d[12]), "+f"(d[13]), "+f"(d[14]), "+f"(d[15]), "+f"(d[16]), "+f"(d[17]), "+f"(d[18]), "+f"(d[19]), "+f"(d[20]), "+f"(d[21]), "+f"(d[22]), "+f"(d[23]), "+f"(d[24]), "+f"(d[25]), "+f"(d[26]), "+f"(d[27]), "+f"(d[28]), "+f"(d[29]), "+f"(d[30]), "+f"(d[31])
        : "r"(a0), "r"(a1), "r"(a2), "r"(a3), "l"(db), "r"(sd));
}

__global__ void __launch_bounds__(384, 1) fused_gqa_kernel(const __grid_constant__ Params P) {
    extern __shared__ uint8_t smem_raw[];
    const uint32_t base = (smem_u32(smem_raw) + 1023u) & ~1023u;
    const uint32_t smR = base;
    const uint32_t smS = base + R_BYTES;
    const uint32_t bars = smS + NSTAGE * STAGE_BYTES;
    const uint32_t prog = bars + 8 * (2 * NSTAGE + 10);
    const int tid = threadIdx.x;
    const int wid = __shfl_sync(0xffffffffu, tid >> 5, 0);
    const int lane = tid & 31;

    const int cta = blockIdx.x;
    const int blk = cta >> 6;
    const int hp = (cta >> 3) & 7;
    const int b = cta & 7;
    const int grp = blk * 8 + b;

    if (tid == 0) {
        TS(0);
        for (int i = 0; i < NSTAGE; i++) {
            mbar_init(bars + 8 * i, 1);
            mbar_init(bars + 8 * (NSTAGE + i), 8);
        }
        for (int i = 0; i < 10; i++) mbar_init(bars + 8 * (2 * NSTAGE + i), 4);
        asm volatile("st.volatile.shared.u32 [%0], %1;" ::"r"(prog), "r"(0) : "memory");
        asm volatile("fence.mbarrier_init.release.cluster;" ::: "memory");
        asm volatile("fence.proxy.async.shared::cta;" ::: "memory");
    }
    __syncthreads();

    if (wid >= 8) {
        asm volatile("setmaxnreg.dec.sync.aligned.u32 40;");
        if (wid == 8) {
            if (lane == 0) {
                int slot = 0, ph = 1;
                for (int s = 0; s < N_WQ; s++) {
                    const uint32_t fb = bars + 8 * slot;
                    mbar_wait(bars + 8 * (NSTAGE + slot), ph);
                    const uint32_t dst = smS + slot * STAGE_BYTES;
                    mbar_expect_tx(fb, (s & 1) ? STAGE_BYTES : STAGE_BYTES + 8192);
                    if (!(s & 1)) tma_2d(smR + ((s >> 1) & 7) * 8192, &P.x[blk], (s >> 1) * 64, b * 64, fb);
#pragma unroll
                    for (int p = 0; p < 4; p++) {
                        const int w = p >> 1, j = p & 1;
                        tma_3d(dst + p * 8192, &P.wq[blk], 0, s * 32, hp * 8 + j * 4 + w * 2, fb);
                    }
                    if (++slot == NSTAGE) { slot = 0; ph ^= 1; }
                }
                int lim = NSTAGE;
                for (int i = 0; i < 34; i++) {
                    const int u = (i >= 17), r = i - 17 * u;
                    const uint32_t fb = bars + 8 * slot;
                    mbar_wait(bars + 8 * (NSTAGE + slot), ph);
                    const uint32_t dst = smS + slot * STAGE_BYTES;
                    mbar_expect_tx(fb, STAGE_BYTES);
                    if (r < 8) {
                        const int row = (b * kHkv + hp * 2 + u) * kSk + (r >> 1) * 128;
                        tma_3d(dst, (r & 1) ? &P.v[blk] : &P.k[blk], 0, row, 0, fb);
                    } else {
                        const int q = r - 8, row = hp * 512 + u * 256;
                        if (q < 8) {
                            tma_3d(dst, &P.wo[blk], 0, row + (q & 3) * 64, (q >> 2) * 4, fb);
                            tma_3d(dst + 16384, &P.wo[blk], 0, row + ((q & 3) ^ 2) * 64, (q >> 2) * 4 + 2, fb);
                        } else {
                            tma_2d(dst, &P.wo8[blk], 512, row, fb);
                            tma_2d(dst + 16384, &P.wo8[blk], 512, row + 128, fb);
                        }
                    }
                    asm volatile("st.volatile.shared.u32 [%0], %1;" ::"r"(prog), "r"(i + 1) : "memory");
                    if (i == 7) lim = 3;
                    if (++slot == lim) { slot = 0; ph ^= 1; }
                }
            }
        } else if (wid == 11) {
            if (PF_DIST > 0) {
                uint32_t sink = 0;
                mbar_wait(bars, 0);
                if (PF_WQ) {
                    const char* wqs = (const char*)(P.wqp[blk] + hp * 512) + (size_t)(160 + b * 52) * 8192;
#pragma unroll
                    for (int h = 0; h < 2; h++) {
#pragma unroll
                        for (int j = 0; j < 4; j++) {
                            const int e = (h * 4 + j) * 32 + lane;
                            if (e < 208) sink |= l2_touch(wqs + (size_t)(e >> 2) * 8192 + (e & 3) * 256);
                        }
                        if (sink == 0x9E3779B9u) asm volatile("st.volatile.shared.u32 [%0], %1;" ::"r"(prog + 4), "r"(sink) : "memory");
                    }
                }
                const char* kbase = (const char*)(P.kp[blk] + (size_t)(b * kHkv + hp * 2) * kSk * kDh);
                const char* vbase = (const char*)(P.vp[blk] + (size_t)(b * kHkv + hp * 2) * kSk * kDh);
                const char* wos = (const char*)(P.wop[blk] + (size_t)hp * 512 * kD) + (size_t)b * 36864;
                for (int i = 0; i < 18; i++) {
                    const int u = (i >= 9), r = i - 9 * u;
                    const int pos = u ? (PF_POS1 + r) : r;
                    if (pos >= PF_DIST) {
                        uint32_t pr, n = 0;
                        while (true) {
                            asm volatile("ld.volatile.shared.u32 %0, [%1];" : "=r"(pr) : "r"(prog) : "memory");
                            const int prk = ((int)pr <= 8) ? (int)pr : (((int)pr <= 17) ? 8 + (((int)pr - 8) * (PF_POS1 - 8)) / 9 : (int)pr - 17 + PF_POS1);
                            if (prk + PF_DIST >= pos) break;
                            if (++n > (1u << 22)) break;
                            __nanosleep(100);
                        }
                    }
                    if (r < 8) {
                        const char* p = ((r & 1) ? vbase : kbase) + (size_t)(u * 4 + (r >> 1)) * 32768 + lane * 256;
#pragma unroll
                        for (int j = 0; j < 4; j++) sink |= l2_touch(p + j * 8192);
                    } else {
                        const char* p = wos + (size_t)u * 294912 + lane * 256;
#pragma unroll
                        for (int j = 0; j < 5; j++) if (j * 32 + lane < 144) sink |= l2_touch(p + j * 8192);
                    }
                    if (sink == 0x9E3779B9u) asm volatile("st.volatile.shared.u32 [%0], %1;" ::"r"(prog + 4), "r"(sink) : "memory");
                }
            }
        } else {
            const int hw = wid - 9;
            for (int k = 0; k < 3; k++) {
                mbar_wait(bars + 8 * (2 * NSTAGE + hw * 5 + k), 0);
                const int c = (k < 2) ? (2 * k + hw) : 4;
                asm volatile("fence.acq_rel.gpu;" ::: "memory");
                asm volatile("red.relaxed.gpu.global.add.u32 [%0], 1;" ::"l"(&g_cnt[(grp * 9 + c) * 32 + lane]) : "memory");
            }
        }
    } else {
        asm volatile("setmaxnreg.inc.sync.aligned.u32 232;");
        const int w = wid >> 2;
        const int t = tid & 127;
        int slot = 0, ph = 0, lim = NSTAGE;
        uint32_t qf[8][4];
        const uint32_t stash = smR + (1 + w) * 16384 + t * 16;
        {
            float acc[128];
            int pslot = 0;
            for (int s = 0; s < N_WQ; s++) {
                mbar_wait(bars + 8 * slot, ph);
                if (tid == 0 && s == 0) TS(20);
                if (tid == 0 && s == 5) TS(21);
                if (tid == 0 && s == 10) TS(22);
                const uint64_t da = mk_desc(smR + ((s >> 1) & 7) * 8192 + (s & 1) * 64, 16, 1024);
                const uint64_t db = mk_desc(smS + slot * STAGE_BYTES + w * 16384, 4096, 1024);
                wg_fence();
                wgmma_ss_n256_tb(acc, da, db, s != 0);
                wgmma_ss_n256_tb(acc, da + 2, db + 128, 1);
                wg_commit();
                wg_wait<0>();
                if (lane == 0) mbar_arrive(bars + 8 * (NSTAGE + slot));
                pslot = slot;
                if (++slot == NSTAGE) { slot = 0; ph ^= 1; }
            }
            fence_regs(acc);
            if (tid == 0) TS(1);
#pragma unroll
            for (int kk = 0; kk < 8; kk++) {
#pragma unroll
                for (int i = 0; i < 4; i++) qf[kk][i] = pack_bf16(acc[8 * kk + 2 * i], acc[8 * kk + 2 * i + 1]);
                sts128(stash + kk * 2048,
                       pack_bf16(acc[64 + 8 * kk + 0], acc[64 + 8 * kk + 1]), pack_bf16(acc[64 + 8 * kk + 2], acc[64 + 8 * kk + 3]),
                       pack_bf16(acc[64 + 8 * kk + 4], acc[64 + 8 * kk + 5]), pack_bf16(acc[64 + 8 * kk + 6], acc[64 + 8 * kk + 7]));
            }
        }
        if (w == 1) bar_arrive<5, 256>();
        const float sc = 0.08838834764831845f * 1.4426950408889634f;
        uint2* dst0 = g_part + (size_t)(grp * 80 + 2 * w * 8 + hp) * 1024 + t;
        uint2* dst8 = g_part + (size_t)(grp * 80 + 64 + hp * 2 + w) * 1024 + t;
#pragma unroll
        for (int u = 0; u < 2; u++) {
            uint32_t af[16][4];
            {
                float o[64], s[64];
                float m0 = -INFINITY, m1 = -INFINITY, l0 = 0.f, l1 = 0.f;
                uint32_t pf[8][4];
#pragma unroll
                for (int i = 0; i < 64; i++) { o[i] = 0.f; s[i] = 0.f; }
#pragma unroll
                for (int i = 0; i < 32; i++) pf[i >> 2][i & 3] = 0u;
#pragma unroll 1
                for (int tt = 0; tt <= 4; tt++) {
                    int vslot = slot;
                    if (tt > 0) {
                        mbar_wait(bars + 8 * slot, ph);
                        if (++slot == lim) { slot = 0; ph ^= 1; }
                    }
                    if (tt < 4) mbar_wait(bars + 8 * slot, ph);
                    if (tid == 0) TS(32 + u * 20 + tt * 4);
                    if (w == 0) bar_sync<5, 256>(); else bar_sync<6, 256>();
                    wg_fence();
                    if (tt > 0) {
                        const uint64_t db = mk_desc(smS + vslot * STAGE_BYTES, 16384, 1024);
#pragma unroll
                        for (int kk = 0; kk < 8; kk++)
                            wgmma_rs_n128_tb(o, pf[kk][0], pf[kk][1], pf[kk][2], pf[kk][3], db + kk * 128, (tt > 1) || (kk != 0));
                        wg_commit();
                    }
                    if (tt < 4) {
                        const uint64_t db = mk_desc(smS + slot * STAGE_BYTES, 16, 1024);
#pragma unroll
                        for (int kk = 0; kk < 8; kk++)
                            wgmma_rs_n128(s, qf[kk][0], qf[kk][1], qf[kk][2], qf[kk][3], db + (kk >> 2) * 1024 + (kk & 3) * 2, kk != 0);
                        wg_commit();
                    }
                    if (w == 0) bar_arrive<6, 256>(); else if (!(u == 1 && tt == 4)) bar_arrive<5, 256>();
                    if (tid == 0) TS(32 + u * 20 + tt * 4 + 1);
                    wg_wait<0>();
                    fence_regs(o);
                    fence_regs(s);
                    if (tid == 0) TS(32 + u * 20 + tt * 4 + 2);
                    if (tt > 0 && lane == 0) mbar_arrive(bars + 8 * (NSTAGE + vslot));
                    if (tt == 4) break;
                    if (lane == 0) mbar_arrive(bars + 8 * (NSTAGE + slot));
                    if (++slot == lim) { slot = 0; ph ^= 1; }
                    float mx0 = s[0], mx1 = s[2];
#pragma unroll
                    for (int j = 0; j < 16; j++) {
                        mx0 = fmaxf(mx0, fmaxf(s[4 * j], s[4 * j + 1]));
                        mx1 = fmaxf(mx1, fmaxf(s[4 * j + 2], s[4 * j + 3]));
                    }
                    mx0 = fmaxf(mx0, __shfl_xor_sync(0xffffffffu, mx0, 1));
                    mx1 = fmaxf(mx1, __shfl_xor_sync(0xffffffffu, mx1, 1));
                    mx0 = fmaxf(mx0, __shfl_xor_sync(0xffffffffu, mx0, 2));
                    mx1 = fmaxf(mx1, __shfl_xor_sync(0xffffffffu, mx1, 2));
                    const float mn0 = fmaxf(m0, mx0), mn1 = fmaxf(m1, mx1);
                    const float al0 = ex2((m0 - mn0) * sc), al1 = ex2((m1 - mn1) * sc);
                    m0 = mn0; m1 = mn1;
                    const float ms0 = mn0 * sc, ms1 = mn1 * sc;
                    float rs0 = 0.f, rs1 = 0.f;
#pragma unroll
                    for (int j = 0; j < 16; j++) {
                        const float p0 = ex2(fmaf(s[4 * j], sc, -ms0)), p1 = ex2(fmaf(s[4 * j + 1], sc, -ms0));
                        const float p2 = ex2(fmaf(s[4 * j + 2], sc, -ms1)), p3 = ex2(fmaf(s[4 * j + 3], sc, -ms1));
                        rs0 += p0 + p1; rs1 += p2 + p3;
                        pf[j >> 1][(j & 1) * 2] = pack_bf16(p0, p1);
                        pf[j >> 1][(j & 1) * 2 + 1] = pack_bf16(p2, p3);
                    }
                    l0 = l0 * al0 + rs0; l1 = l1 * al1 + rs1;
                    if (tt > 0) {
#pragma unroll
                        for (int j = 0; j < 16; j++) { o[4 * j] *= al0; o[4 * j + 1] *= al0; o[4 * j + 2] *= al1; o[4 * j + 3] *= al1; }
                    }
                    if (tid == 0) TS(32 + u * 20 + tt * 4 + 3);
                }
                if (tid == 0) TS(2 + u);
                l0 += __shfl_xor_sync(0xffffffffu, l0, 1);
                l1 += __shfl_xor_sync(0xffffffffu, l1, 1);
                l0 += __shfl_xor_sync(0xffffffffu, l0, 2);
                l1 += __shfl_xor_sync(0xffffffffu, l1, 2);
                const float i0 = 1.f / l0, i1 = 1.f / l1;
                const uint32_t zown = smR + (w ? 3 : 0) * 16384 + t * 16;
#pragma unroll
                for (int kk = 0; kk < 8; kk++) {
                    af[kk][0] = pack_bf16(o[8 * kk + 0] * i0, o[8 * kk + 1] * i0);
                    af[kk][1] = pack_bf16(o[8 * kk + 2] * i1, o[8 * kk + 3] * i1);
                    af[kk][2] = pack_bf16(o[8 * kk + 4] * i0, o[8 * kk + 5] * i0);
                    af[kk][3] = pack_bf16(o[8 * kk + 6] * i1, o[8 * kk + 7] * i1);
                    sts128(zown + kk * 2048, af[kk][0], af[kk][1], af[kk][2], af[kk][3]);
                }
            }
            if (w == 0) bar_arrive<7, 256>(); else bar_arrive<8, 256>();
            lim = 3;
            if (u == 0) {
#pragma unroll
                for (int kk = 0; kk < 8; kk++) lds128(stash + kk * 2048, qf[kk]);
            }
#pragma unroll
            for (int ps = 0; ps < 2; ps++) {
                float acc[64];
                const uint32_t keep = smS + (3 + ps) * STAGE_BYTES + w * 16384 + t * 16;
                if (u == 0) {
#pragma unroll
                    for (int i = 0; i < 64; i++) acc[i] = 0.f;
                } else {
#pragma unroll
                    for (int j = 0; j < 8; j++) {
                        uint32_t r[4];
                        lds128(keep + j * 2048, r);
#pragma unroll
                        for (int i = 0; i < 4; i++) { acc[8 * j + 2 * i] = __uint_as_float(r[i] << 16); acc[8 * j + 2 * i + 1] = __uint_as_float(r[i] & 0xffff0000u); }
                    }
                }
#pragma unroll
                for (int st = 0; st < 4; st++) {
                    if (ps == 0 && st == 2) {
                        if (w == 0) bar_sync<8, 256>(); else bar_sync<7, 256>();
#pragma unroll
                        for (int kk = 0; kk < 8; kk++) lds128(smR + (w ? 0 : 3) * 16384 + kk * 2048 + t * 16, af[8 + kk]);
                    }
                    mbar_wait(bars + 8 * slot, ph);
                    const uint64_t db = mk_desc(smS + slot * STAGE_BYTES + w * 16384, 8192, 1024);
                    wg_fence();
#pragma unroll
                    for (int kk = 0; kk < 4; kk++)
                        wgmma_rs_n128_tb(acc, af[st * 4 + kk][0], af[st * 4 + kk][1], af[st * 4 + kk][2], af[st * 4 + kk][3], db + kk * 128, 1);
                    wg_commit();
                    wg_wait<0>();
                    if (lane == 0) mbar_arrive(bars + 8 * (NSTAGE + slot));
                    if (++slot == 3) { slot = 0; ph ^= 1; }
                }
                fence_regs(acc);
                if (u == 0) {
#pragma unroll
                    for (int j = 0; j < 8; j++)
                        sts128(keep + j * 2048, pack_bf16(acc[8 * j], acc[8 * j + 1]), pack_bf16(acc[8 * j + 2], acc[8 * j + 3]),
                               pack_bf16(acc[8 * j + 4], acc[8 * j + 5]), pack_bf16(acc[8 * j + 6], acc[8 * j + 7]));
                } else {
                    uint2* dst = dst0 + (size_t)ps * 32 * 1024;
#pragma unroll
                    for (int j = 0; j < 16; j++)
                        __stcg(dst + (j >> 3) * 8192 + (j & 7) * 128, make_uint2(pack_bf16(acc[4 * j], acc[4 * j + 1]), pack_bf16(acc[4 * j + 2], acc[4 * j + 3])));
                    __syncwarp();
                    if (lane == 0) mbar_arrive(bars + 8 * (2 * NSTAGE + w * 5 + ps));
                }
                if (tid == 0) TS(4 + u * 8 + ps);
            }
            {
                float acc[32];
                if (u == 0) {
#pragma unroll
                    for (int i = 0; i < 32; i++) acc[i] = 0.f;
                } else {
#pragma unroll
                    for (int j = 0; j < 4; j++) {
                        uint32_t r[4];
                        lds128(stash + j * 2048, r);
#pragma unroll
                        for (int i = 0; i < 4; i++) { acc[8 * j + 2 * i] = __uint_as_float(r[i] << 16); acc[8 * j + 2 * i + 1] = __uint_as_float(r[i] & 0xffff0000u); }
                    }
                }
                mbar_wait(bars + 8 * slot, ph);
                const uint64_t db = mk_desc(smS + slot * STAGE_BYTES + w * 16384, 8192, 1024);
                wg_fence();
#pragma unroll
                for (int kk = 0; kk < 8; kk++)
                    wgmma_rs_n64_tb(acc, af[kk][0], af[kk][1], af[kk][2], af[kk][3], db + kk * 128, 1);
                wg_commit();
                wg_wait<0>();
                if (lane == 0) mbar_arrive(bars + 8 * (NSTAGE + slot));
                if (++slot == 3) { slot = 0; ph ^= 1; }
                fence_regs(acc);
                if (u == 0) {
#pragma unroll
                    for (int j = 0; j < 4; j++)
                        sts128(stash + j * 2048, pack_bf16(acc[8 * j], acc[8 * j + 1]), pack_bf16(acc[8 * j + 2], acc[8 * j + 3]),
                               pack_bf16(acc[8 * j + 4], acc[8 * j + 5]), pack_bf16(acc[8 * j + 6], acc[8 * j + 7]));
                } else {
#pragma unroll
                    for (int j = 0; j < 8; j++)
                        __stcg(dst8 + j * 128, make_uint2(pack_bf16(acc[4 * j], acc[4 * j + 1]), pack_bf16(acc[4 * j + 2], acc[4 * j + 3])));
                    __syncwarp();
                    if (lane == 0) mbar_arrive(bars + 8 * (2 * NSTAGE + w * 5 + 2));
                }
                if (tid == 0) TS(6 + u * 8);
            }
        }
        {
            const int nch = (w == 0) ? 3 : 2;
            if (lane < nch) {
                const int c = (lane < 2) ? (2 * lane + w) : 4;
                const unsigned need = (lane < 2) ? 8u : 16u;
                unsigned* cp = &g_cnt[(grp * 9 + c) * 32 + hp * 4 + (wid & 3)];
                unsigned v, n = 0;
                while (true) {
                    asm volatile("ld.acquire.gpu.global.u32 %0, [%1];" : "=r"(v) : "l"(cp) : "memory");
                    if (v >= need) break;
                    if (++n > (1u << 21)) break;
                }
                *cp = 0;
            }
            __syncwarp();
            if (tid == 0) TS(18);
            __nv_bfloat16* orow = P.out + (size_t)(b * 64 + (t >> 5) * 16 + (lane >> 2)) * (2 * kD) + blk * kD + hp * 8 + (lane & 3) * 2;
            const uint2* src = g_part + ((size_t)(grp * 80 + 2 * w * 8) * 8 + hp) * 128 + t;
            uint2 v[4][8];
#pragma unroll
            for (int k = 0; k < 4; k++)
#pragma unroll
                for (int i = 0; i < 8; i++) v[k][i] = __ldcg(src + (size_t)((k >> 1) * 32 + (k & 1) * 8 + i) * 1024);
            if (w == 0) {
                const uint2* src8 = g_part + ((size_t)(grp * 80 + 64) * 8 + hp) * 128 + t;
                uint2 u[16];
#pragma unroll
                for (int i = 0; i < 16; i++) u[i] = __ldcg(src8 + (size_t)i * 1024);
                float a0 = 0.f, a1 = 0.f, a2 = 0.f, a3 = 0.f;
#pragma unroll
                for (int i = 0; i < 16; i++) {
                    a0 += __uint_as_float(u[i].x << 16); a1 += __uint_as_float(u[i].x & 0xffff0000u);
                    a2 += __uint_as_float(u[i].y << 16); a3 += __uint_as_float(u[i].y & 0xffff0000u);
                }
                *(uint32_t*)(orow + 512) = pack_bf16(a0, a1);
                *(uint32_t*)(orow + 512 + 8 * 2 * kD) = pack_bf16(a2, a3);
            }
#pragma unroll
            for (int k = 0; k < 4; k++) {
                float a0 = 0.f, a1 = 0.f, a2 = 0.f, a3 = 0.f;
#pragma unroll
                for (int i = 0; i < 8; i++) {
                    a0 += __uint_as_float(v[k][i].x << 16); a1 += __uint_as_float(v[k][i].x & 0xffff0000u);
                    a2 += __uint_as_float(v[k][i].y << 16); a3 += __uint_as_float(v[k][i].y & 0xffff0000u);
                }
                *(uint32_t*)(orow + ((k >> 1) * 4 + 2 * w + (k & 1)) * 64) = pack_bf16(a0, a1);
                *(uint32_t*)(orow + ((k >> 1) * 4 + 2 * w + (k & 1)) * 64 + 8 * 2 * kD) = pack_bf16(a2, a3);
            }
            if (tid == 0) TS(19);
        }
    }
}

typedef CUresult (*EncodeFn)(CUtensorMap*, CUtensorMapDataType, cuuint32_t, void*, const cuuint64_t*, const cuuint64_t*,
                             const cuuint32_t*, const cuuint32_t*, CUtensorMapInterleave, CUtensorMapSwizzle,
                             CUtensorMapL2promotion, CUtensorMapFloatOOBfill);

void make_map(EncodeFn fn, CUtensorMap* m, const void* ptr, uint64_t cols, uint64_t rows, uint32_t box_rows) {
    cuuint64_t dims[2] = {cols, rows};
    cuuint64_t strides[1] = {cols * 2};
    cuuint32_t box[2] = {64, box_rows};
    cuuint32_t es[2] = {1, 1};
    fn(m, CU_TENSOR_MAP_DATA_TYPE_BFLOAT16, 2, const_cast<void*>(ptr), dims, strides, box, es, CU_TENSOR_MAP_INTERLEAVE_NONE,
       CU_TENSOR_MAP_SWIZZLE_128B, CU_TENSOR_MAP_L2_PROMOTION_L2_256B, CU_TENSOR_MAP_FLOAT_OOB_FILL_NONE);
}

void make_map3(EncodeFn fn, CUtensorMap* m, const void* ptr, uint64_t cols, uint64_t rows, uint32_t box_rows, uint32_t box_groups) {
    cuuint64_t dims[3] = {64, rows, cols / 64};
    cuuint64_t strides[2] = {cols * 2, 128};
    cuuint32_t box[3] = {64, box_rows, box_groups};
    cuuint32_t es[3] = {1, 1, 1};
    fn(m, CU_TENSOR_MAP_DATA_TYPE_BFLOAT16, 3, const_cast<void*>(ptr), dims, strides, box, es, CU_TENSOR_MAP_INTERLEAVE_NONE,
       CU_TENSOR_MAP_SWIZZLE_128B, CU_TENSOR_MAP_L2_PROMOTION_L2_256B, CU_TENSOR_MAP_FLOAT_OOB_FILL_NONE);
}

}

extern "C" void kernel_launch(void* const* d_in, const int* in_sizes, int n_in, void* d_out, int out_size) {
    static EncodeFn enc = nullptr;
    if (!enc) {
        void* fn = nullptr;
        cudaDriverEntryPointQueryResult st;
        cudaGetDriverEntryPoint("cuTensorMapEncodeTiled", &fn, cudaEnableDefault, &st);
        enc = (EncodeFn)fn;
        cudaFuncSetAttribute(fused_gqa_kernel, cudaFuncAttributeMaxDynamicSharedMemorySize, SMEM_BYTES);
    }
    Params P;
    for (int blk = 0; blk < 2; blk++) {
        const void* x = d_in[blk * 5 + 0];
        const void* k = d_in[blk * 5 + 1];
        const void* v = d_in[blk * 5 + 2];
        const void* wq = d_in[blk * 5 + 3];
        const void* wo = d_in[blk * 5 + 4];
        make_map(enc, &P.x[blk], x, kD, kB * kSq, 64);
        make_map3(enc, &P.wq[blk], wq, kHq * kDh, kD, 32, 2);
        make_map3(enc, &P.k[blk], k, kDh, (uint64_t)kB * kHkv * kSk, 128, 2);
        make_map3(enc, &P.v[blk], v, kDh, (uint64_t)kB * kHkv * kSk, 128, 2);
        make_map3(enc, &P.wo[blk], wo, kD, kHq * kDh, 64, 2);
        make_map(enc, &P.wo8[blk], wo, kD, kHq * kDh, 128);
        P.wqp[blk] = (const __nv_bfloat16*)wq;
        P.kp[blk] = (const __nv_bfloat16*)k;
        P.vp[blk] = (const __nv_bfloat16*)v;
        P.wop[blk] = (const __nv_bfloat16*)wo;
    }
    P.out = (__nv_bfloat16*)d_out;
    fused_gqa_kernel<<<128, 384, SMEM_BYTES>>>(P);
}
```

```cpp
#include <cuda_runtime.h>
#include <cuda_bf16.h>
#include <cuda.h>
#include <stdint.h>

namespace {

constexpr int kB = 8, kSq = 64, kD = 576, kHq = 32, kHkv = 16, kSk = 512, kDh = 128;
constexpr int NSTAGE = 5;
constexpr int STAGE_BYTES = 32768;
constexpr int R_BYTES = 65536;
constexpr int SMEM_BYTES = R_BYTES + NSTAGE * STAGE_BYTES + 1024   + 256  ;
constexpr int N_WQ = 18;
#define PF_DIST_V 6
#define OP_WAIT0 1
#define QP_WAIT0 1
#define PF_POS1 9
#define PF_WQ 0
#define PF_SLEEP 1000
constexpr int PF_DIST = PF_DIST_V;

struct __align__(64) Params {
    CUtensorMap x[2], wq[2], k[2], v[2], wo[2], wo8[2];
    const __nv_bfloat16* wqp[2];
    const __nv_bfloat16* kp[2];
    const __nv_bfloat16* vp[2];
    const __nv_bfloat16* wop[2];
    __nv_bfloat16* out;
};

__device__ uint2 g_part[16 * 80 * 8 * 128];
__device__ unsigned int g_cnt[16 * 9 * 32];
#define TS(k) do {} while (0)

__device__ __forceinline__ uint32_t smem_u32(const void* p) { return (uint32_t)__cvta_generic_to_shared(p); }
__device__ __forceinline__ void mbar_init(uint32_t bar, int cnt) {
    asm volatile("mbarrier.init.shared::cta.b64 [%0], %1;" ::"r"(bar), "r"(cnt));
}
__device__ __forceinline__ void mbar_expect_tx(uint32_t bar, uint32_t bytes) {
    asm volatile("mbarrier.arrive.expect_tx.shared::cta.b64 _, [%0], %1;" ::"r"(bar), "r"(bytes) : "memory");
}
__device__ __forceinline__ void mbar_arrive(uint32_t bar) {
    asm volatile("mbarrier.arrive.shared::cta.b64 _, [%0];" ::"r"(bar) : "memory");
}
__device__ __forceinline__ bool mbar_try(uint32_t bar, uint32_t parity) {
    uint32_t ok;
    asm volatile("{\n.reg .pred p;\nmbarrier.try_wait.parity.shared::cta.b64 p, [%1], %2;\nselp.u32 %0, 1, 0, p;\n}\n"
                 : "=r"(ok) : "r"(bar), "r"(parity) : "memory");
    return ok != 0;
}
__device__ __forceinline__ void mbar_wait(uint32_t bar, uint32_t parity) {
    if (mbar_try(bar, parity)) return;
    uint32_t n = 0;
    while (!mbar_try(bar, parity)) {
        if (++n > (1u << 20)) break;
    }
}
__device__ __forceinline__ void tma_2d(uint32_t dst, const CUtensorMap* tm, int c0, int c1, uint32_t bar) {
    asm volatile("cp.async.bulk.tensor.2d.shared::cluster.global.mbarrier::complete_tx::bytes [%0], [%1, {%3, %4}], [%2];"
                 ::"r"(dst), "l"(tm), "r"(bar), "r"(c0), "r"(c1) : "memory");
}
__device__ __forceinline__ void tma_3d(uint32_t dst, const CUtensorMap* tm, int c0, int c1, int c2, uint32_t bar) {
    asm volatile("cp.async.bulk.tensor.3d.shared::cluster.global.mbarrier::complete_tx::bytes [%0], [%1, {%3, %4, %5}], [%2];"
                 ::"r"(dst), "l"(tm), "r"(bar), "r"(c0), "r"(c1), "r"(c2) : "memory");
}
__device__ __forceinline__ void l2_prefetch(const void* p, uint32_t bytes) {
    asm volatile("cp.async.bulk.prefetch.L2.global [%0], %1;" ::"l"(p), "r"(bytes) : "memory");
}
__device__ __forceinline__ uint32_t l2_touch(const void* p) {
    uint32_t v;
    asm volatile("ld.global.L2::256B.b32 %0, [%1];" : "=r"(v) : "l"(p) : "memory");
    return v;
}
__device__ __forceinline__ void wg_fence() { asm volatile("wgmma.fence.sync.aligned;" ::: "memory"); }
__device__ __forceinline__ void wg_commit() { asm volatile("wgmma.commit_group.sync.aligned;" ::: "memory"); }
template <int N> __device__ __forceinline__ void wg_wait() { asm volatile("wgmma.wait_group.sync.aligned %0;" ::"n"(N) : "memory"); }
template <int N> __device__ __forceinline__ void fence_regs(float (&d)[N]) {
#pragma unroll
    for (int i = 0; i < N; i++) asm volatile("" : "+f"(d[i])::"memory");
}
__device__ __forceinline__ uint64_t mk_desc(uint32_t addr, uint32_t lbo, uint32_t sbo) {
    return (uint64_t)((addr & 0x3FFFF) >> 4) | ((uint64_t)(lbo >> 4) << 16) | ((uint64_t)(sbo >> 4) << 32) | (1ull << 62);
}
__device__ __forceinline__ uint32_t pack_bf16(float a, float b) {
    uint32_t r;
    asm("cvt.rn.bf16x2.f32 %0, %1, %2;" : "=r"(r) : "f"(b), "f"(a));
    return r;
}
__device__ __forceinline__ float ex2(float x) {
    float y;
    asm("ex2.approx.ftz.f32 %0, %1;" : "=f"(y) : "f"(x));
    return y;
}
template <int ID, int N> __device__ __forceinline__ void bar_sync() { asm volatile("bar.sync %0, %1;" ::"n"(ID), "n"(N) : "memory"); }
template <int ID, int N> __device__ __forceinline__ void bar_arrive() { asm volatile("bar.arrive %0, %1;" ::"n"(ID), "n"(N) : "memory"); }
__device__ __forceinline__ void sts128(uint32_t addr, uint32_t a, uint32_t b, uint32_t c, uint32_t d) {
    asm volatile("st.shared.v4.b32 [%0], {%1,%2,%3,%4};" ::"r"(addr), "r"(a), "r"(b), "r"(c), "r"(d) : "memory");
}
__device__ __forceinline__ void lds128(uint32_t addr, uint32_t (&r)[4]) {
    asm volatile("ld.shared.v4.b32 {%0,%1,%2,%3}, [%4];" : "=r"(r[0]), "=r"(r[1]), "=r"(r[2]), "=r"(r[3]) : "r"(addr) : "memory");
}

__device__ __forceinline__ void wgmma_ss_n256_tb(float (&d)[128], uint64_t da, uint64_t db, int sd) {
    asm volatile("{\n.reg .pred p;\nsetp.ne.b32 p, %130, 0;\n"
        "wgmma.mma_async.sync.aligned.m64n256k16.f32.bf16.bf16 "
        "{%0, %1, %2, %3, %4, %5, %6, %7, %8, %9, %10, %11, %12, %13, %14, %15, %16, %17, %18, %19, %20, %21, %22, %23, %24, %25, %26, %27, %28, %29, %30, %31, %32, %33, %34, %35, %36, %37, %38, %39, %40, %41, %42, %43, %44, %45, %46, %47, %48, %49, %50, %51, %52, %53, %54, %55, %56, %57, %58, %59, %60, %61, %62, %63, %64, %65, %66, %67, %68, %69, %70, %71, %72, %73, %74, %75, %76, %77, %78, %79, %80, %81, %82, %83, %84, %85, %86, %87, %88, %89, %90, %91, %92, %93, %94, %95, %96, %97, %98, %99, %100, %101, %102, %103, %104, %105, %106, %107, %108, %109, %110, %111, %112, %113, %114, %115, %116, %117, %118, %119, %120, %121, %122, %123, %124, %125, %126, %127}, "
        "%128, %129, p, 1, 1, 0, 1;\n}\n"
        : "+f"(d[0]), "+f"(d[1]), "+f"(d[2]), "+f"(d[3]), "+f"(d[4]), "+f"(d[5]), "+f"(d[6]), "+f"(d[7]), "+f"(d[8]), "+f"(d[9]), "+f"(d[10]), "+f"(d[11]), "+f"(d[12]), "+f"(d[13]), "+f"(d[14]), "+f"(d[15]), "+f"(d[16]), "+f"(d[17]), "+f"(d[18]), "+f"(d[19]), "+f"(d[20]), "+f"(d[21]), "+f"(d[22]), "+f"(d[23]), "+f"(d[24]), "+f"(d[25]), "+f"(d[26]), "+f"(d[27]), "+f"(d[28]), "+f"(d[29]), "+f"(d[30]), "+f"(d[31]), "+f"(d[32]), "+f"(d[33]), "+f"(d[34]), "+f"(d[35]), "+f"(d[36]), "+f"(d[37]), "+f"(d[38]), "+f"(d[39]), "+f"(d[40]), "+f"(d[41]), "+f"(d[42]), "+f"(d[43]), "+f"(d[44]), "+f"(d[45]), "+f"(d[46]), "+f"(d[47]), "+f"(d[48]), "+f"(d[49]), "+f"(d[50]), "+f"(d[51]), "+f"(d[52]), "+f"(d[53]), "+f"(d[54]), "+f"(d[55]), "+f"(d[56]), "+f"(d[57]), "+f"(d[58]), "+f"(d[59]), "+f"(d[60]), "+f"(d[61]), "+f"(d[62]), "+f"(d[63]), "+f"(d[64]), "+f"(d[65]), "+f"(d[66]), "+f"(d[67]), "+f"(d[68]), "+f"(d[69]), "+f"(d[70]), "+f"(d[71]), "+f"(d[72]), "+f"(d[73]), "+f"(d[74]), "+f"(d[75]), "+f"(d[76]), "+f"(d[77]), "+f"(d[78]), "+f"(d[79]), "+f"(d[80]), "+f"(d[81]), "+f"(d[82]), "+f"(d[83]), "+f"(d[84]), "+f"(d[85]), "+f"(d[86]), "+f"(d[87]), "+f"(d[88]), "+f"(d[89]), "+f"(d[90]), "+f"(d[91]), "+f"(d[92]), "+f"(d[93]), "+f"(d[94]), "+f"(d[95]), "+f"(d[96]), "+f"(d[97]), "+f"(d[98]), "+f"(d[99]), "+f"(d[100]), "+f"(d[101]), "+f"(d[102]), "+f"(d[103]), "+f"(d[104]), "+f"(d[105]), "+f"(d[106]), "+f"(d[107]), "+f"(d[108]), "+f"(d[109]), "+f"(d[110]), "+f"(d[111]), "+f"(d[112]), "+f"(d[113]), "+f"(d[114]), "+f"(d[115]), "+f"(d[116]), "+f"(d[117]), "+f"(d[118]), "+f"(d[119]), "+f"(d[120]), "+f"(d[121]), "+f"(d[122]), "+f"(d[123]), "+f"(d[124]), "+f"(d[125]), "+f"(d[126]), "+f"(d[127])
        : "l"(da), "l"(db), "r"(sd));
}
__device__ __forceinline__ void wgmma_rs_n128(float (&d)[64], uint32_t a0, uint32_t a1, uint32_t a2, uint32_t a3, uint64_t db, int sd) {
    asm volatile("{\n.reg .pred p;\nsetp.ne.b32 p, %69, 0;\n"
        "wgmma.mma_async.sync.aligned.m64n128k16.f32.bf16.bf16 "
        "{%0, %1, %2, %3, %4, %5, %6, %7, %8, %9, %10, %11, %12, %13, %14, %15, %16, %17, %18, %19, %20, %21, %22, %23, %24, %25, %26, %27, %28, %29, %30, %31, %32, %33, %34, %35, %36, %37, %38, %39, %40, %41, %42, %43, %44, %45, %46, %47, %48, %49, %50, %51, %52, %53, %54, %55, %56, %57, %58, %59, %60, %61, %62, %63}, "
        "{%64, %65, %66, %67}, %68, p, 1, 1, 0;\n}\n"
        : "+f"(d[0]), "+f"(d[1]), "+f"(d[2]), "+f"(d[3]), "+f"(d[4]), "+f"(d[5]), "+f"(d[6]), "+f"(d[7]), "+f"(d[8]), "+f"(d[9]), "+f"(d[10]), "+f"(d[11]), "+f"(d[12]), "+f"(d[13]), "+f"(d[14]), "+f"(d[15]), "+f"(d[16]), "+f"(d[17]), "+f"(d[18]), "+f"(d[19]), "+f"(d[20]), "+f"(d[21]), "+f"(d[22]), "+f"(d[23]), "+f"(d[24]), "+f"(d[25]), "+f"(d[26]), "+f"(d[27]), "+f"(d[28]), "+f"(d[29]), "+f"(d[30]), "+f"(d[31]), "+f"(d[32]), "+f"(d[33]), "+f"(d[34]), "+f"(d[35]), "+f"(d[36]), "+f"(d[37]), "+f"(d[38]), "+f"(d[39]), "+f"(d[40]), "+f"(d[41]), "+f"(d[42]), "+f"(d[43]), "+f"(d[44]), "+f"(d[45]), "+f"(d[46]), "+f"(d[47]), "+f"(d[48]), "+f"(d[49]), "+f"(d[50]), "+f"(d[51]), "+f"(d[52]), "+f"(d[53]), "+f"(d[54]), "+f"(d[55]), "+f"(d[56]), "+f"(d[57]), "+f"(d[58]), "+f"(d[59]), "+f"(d[60]), "+f"(d[61]), "+f"(d[62]), "+f"(d[63])
        : "r"(a0), "r"(a1), "r"(a2), "r"(a3), "l"(db), "r"(sd));
}
__device__ __forceinline__ void wgmma_rs_n128_tb(float (&d)[64], uint32_t a0, uint32_t a1, uint32_t a2, uint32_t a3, uint64_t db, int sd) {
    asm volatile("{\n.reg .pred p;\nsetp.ne.b32 p, %69, 0;\n"
        "wgmma.mma_async.sync.aligned.m64n128k16.f32.bf16.bf16 "
        "{%0, %1, %2, %3, %4, %5, %6, %7, %8, %9, %10, %11, %12, %13, %14, %15, %16, %17, %18, %19, %20, %21, %22, %23, %24, %25, %26, %27, %28, %29, %30, %31, %32, %33, %34, %35, %36, %37, %38, %39, %40, %41, %42, %43, %44, %45, %46, %47, %48, %49, %50, %51, %52, %53, %54, %55, %56, %57, %58, %59, %60, %61, %62, %63}, "
        "{%64, %65, %66, %67}, %68, p, 1, 1, 1;\n}\n"
        : "+f"(d[0]), "+f"(d[1]), "+f"(d[2]), "+f"(d[3]), "+f"(d[4]), "+f"(d[5]), "+f"(d[6]), "+f"(d[7]), "+f"(d[8]), "+f"(d[9]), "+f"(d[10]), "+f"(d[11]), "+f"(d[12]), "+f"(d[13]), "+f"(d[14]), "+f"(d[15]), "+f"(d[16]), "+f"(d[17]), "+f"(d[18]), "+f"(d[19]), "+f"(d[20]), "+f"(d[21]), "+f"(d[22]), "+f"(d[23]), "+f"(d[24]), "+f"(d[25]), "+f"(d[26]), "+f"(d[27]), "+f"(d[28]), "+f"(d[29]), "+f"(d[30]), "+f"(d[31]), "+f"(d[32]), "+f"(d[33]), "+f"(d[34]), "+f"(d[35]), "+f"(d[36]), "+f"(d[37]), "+f"(d[38]), "+f"(d[39]), "+f"(d[40]), "+f"(d[41]), "+f"(d[42]), "+f"(d[43]), "+f"(d[44]), "+f"(d[45]), "+f"(d[46]), "+f"(d[47]), "+f"(d[48]), "+f"(d[49]), "+f"(d[50]), "+f"(d[51]), "+f"(d[52]), "+f"(d[53]), "+f"(d[54]), "+f"(d[55]), "+f"(d[56]), "+f"(d[57]), "+f"(d[58]), "+f"(d[59]), "+f"(d[60]), "+f"(d[61]), "+f"(d[62]), "+f"(d[63])
        : "r"(a0), "r"(a1), "r"(a2), "r"(a3), "l"(db), "r"(sd));
}
__device__ __forceinline__ void wgmma_rs_n64_tb(float (&d)[32], uint32_t a0, uint32_t a1, uint32_t a2, uint32_t a3, uint64_t db, int sd) {
    asm volatile("{\n.reg .pred p;\nsetp.ne.b32 p, %37, 0;\n"
        "wgmma.mma_async.sync.aligned.m64n64k16.f32.bf16.bf16 "
        "{%0, %1, %2, %3, %4, %5, %6, %7, %8, %9, %10, %11, %12, %13, %14, %15, %16, %17, %18, %19, %20, %21, %22, %23, %24, %25, %26, %27, %28, %29, %30, %31}, "
        "{%32, %33, %34, %35}, %36, p, 1, 1, 1;\n}\n"
        : "+f"(d[0]), "+f"(d[1]), "+f"(d[2]), "+f"(d[3]), "+f"(d[4]), "+f"(d[5]), "+f"(d[6]), "+f"(d[7]), "+f"(d[8]), "+f"(d[9]), "+f"(d[10]), "+f"(d[11]), "+f"(d[12]), "+f"(d[13]), "+f"(d[14]), "+f"(d[15]), "+f"(d[16]), "+f"(d[17]), "+f"(d[18]), "+f"(d[19]), "+f"(d[20]), "+f"(d[21]), "+f"(d[22]), "+f"(d[23]), "+f"(d[24]), "+f"(d[25]), "+f"(d[26]), "+f"(d[27]), "+f"(d[28]), "+f"(d[29]), "+f"(d[30]), "+f"(d[31])
        : "r"(a0), "r"(a1), "r"(a2), "r"(a3), "l"(db), "r"(sd));
}

__global__ void __launch_bounds__(384, 1) fused_gqa_kernel(const __grid_constant__ Params P) {
    extern __shared__ uint8_t smem_raw[];
    const uint32_t base = (smem_u32(smem_raw) + 1023u) & ~1023u;
    const uint32_t smR = base;
    const uint32_t smS = base + R_BYTES;
    const uint32_t bars = smS + NSTAGE * STAGE_BYTES;
    const uint32_t prog = bars + 8 * (2 * NSTAGE + 10);
    const int tid = threadIdx.x;
    const int wid = __shfl_sync(0xffffffffu, tid >> 5, 0);
    const int lane = tid & 31;

    const int cta = blockIdx.x;
    const int blk = cta >> 6;
    const int hp = (cta >> 3) & 7;
    const int b = cta & 7;
    const int grp = blk * 8 + b;

    if (tid == 0) {
        TS(0);
        for (int i = 0; i < NSTAGE; i++) {
            mbar_init(bars + 8 * i, 1);
            mbar_init(bars + 8 * (NSTAGE + i), 8);
        }
        for (int i = 0; i < 10; i++) mbar_init(bars + 8 * (2 * NSTAGE + i), 4);
        asm volatile("st.volatile.shared.u32 [%0], %1;" ::"r"(prog), "r"(0) : "memory");
        asm volatile("fence.mbarrier_init.release.cluster;" ::: "memory");
        asm volatile("fence.proxy.async.shared::cta;" ::: "memory");
    }
    __syncthreads();

    if (wid >= 8) {
        asm volatile("setmaxnreg.dec.sync.aligned.u32 40;");
        if (wid == 8) {
            if (lane == 0) {
                int slot = 0, ph = 1;
                for (int s = 0; s < N_WQ; s++) {
                    const uint32_t fb = bars + 8 * slot;
                    mbar_wait(bars + 8 * (NSTAGE + slot), ph);
                    const uint32_t dst = smS + slot * STAGE_BYTES;
                    mbar_expect_tx(fb, (s & 1) ? STAGE_BYTES : STAGE_BYTES + 8192);
                    if (!(s & 1)) tma_2d(smR + ((s >> 1) & 7) * 8192, &P.x[blk], (s >> 1) * 64, b * 64, fb);
#pragma unroll
                    for (int p = 0; p < 4; p++) {
                        const int w = p >> 1, j = p & 1;
                        tma_3d(dst + p * 8192, &P.wq[blk], 0, s * 32, hp * 8 + j * 4 + w * 2, fb);
                    }
                    if (++slot == NSTAGE) { slot = 0; ph ^= 1; }
                }
                int lim = NSTAGE;
                for (int i = 0; i < 34; i++) {
                    const int u = (i >= 17), r = i - 17 * u;
                    const bool extra = (i == 28) || (i == 31);
                    const int sl = extra ? ((i == 28) ? 3 : 4) : slot;
                    const uint32_t fb = bars + 8 * sl;
                    mbar_wait(bars + 8 * (NSTAGE + sl), extra ? 1 : ph);
                    const uint32_t dst = smS + sl * STAGE_BYTES;
                    mbar_expect_tx(fb, STAGE_BYTES);
                    if (r < 8) {
                        const int row = (b * kHkv + hp * 2 + u) * kSk + (r >> 1) * 128;
                        tma_3d(dst, (r & 1) ? &P.v[blk] : &P.k[blk], 0, row, 0, fb);
                    } else {
                        const int q = r - 8, row = hp * 512 + u * 256;
                        if (q < 8) {
                            tma_3d(dst, &P.wo[blk], 0, row + (q & 3) * 64, (q >> 2) * 4, fb);
                            tma_3d(dst + 16384, &P.wo[blk], 0, row + ((q & 3) ^ 2) * 64, (q >> 2) * 4 + 2, fb);
                        } else {
                            tma_2d(dst, &P.wo8[blk], 512, row, fb);
                            tma_2d(dst + 16384, &P.wo8[blk], 512, row + 128, fb);
                        }
                    }
                    asm volatile("st.volatile.shared.u32 [%0], %1;" ::"r"(prog), "r"(i + 1) : "memory");
                    if (i == 7) lim = 3;
                    if (!extra && ++slot == lim) { slot = 0; ph ^= 1; }
                }
            }
        } else if (wid == 11) {
            if (PF_DIST > 0) {
                uint32_t sink = 0;
                mbar_wait(bars, 0);
                if (PF_WQ) {
                    const char* wqs = (const char*)(P.wqp[blk] + hp * 512) + (size_t)(160 + b * 52) * 8192;
#pragma unroll
                    for (int h = 0; h < 2; h++) {
#pragma unroll
                        for (int j = 0; j < 4; j++) {
                            const int e = (h * 4 + j) * 32 + lane;
                            if (e < 208) sink |= l2_touch(wqs + (size_t)(e >> 2) * 8192 + (e & 3) * 256);
                        }
                        if (sink == 0x9E3779B9u) asm volatile("st.volatile.shared.u32 [%0], %1;" ::"r"(prog + 4), "r"(sink) : "memory");
                    }
                }
                const char* kbase = (const char*)(P.kp[blk] + (size_t)(b * kHkv + hp * 2) * kSk * kDh);
                const char* vbase = (const char*)(P.vp[blk] + (size_t)(b * kHkv + hp * 2) * kSk * kDh);
                const char* wos = (const char*)(P.wop[blk] + (size_t)hp * 512 * kD) + (size_t)b * 36864;
                for (int i = 0; i < 18; i++) {
                    const int u = (i >= 9), r = i - 9 * u;
                    const int pos = u ? (PF_POS1 + r) : r;
                    if (pos >= PF_DIST) {
                        uint32_t pr, n = 0;
                        while (true) {
                            asm volatile("ld.volatile.shared.u32 %0, [%1];" : "=r"(pr) : "r"(prog) : "memory");
                            const int prk = ((int)pr <= 8) ? (int)pr : (((int)pr <= 17) ? 8 + (((int)pr - 8) * (PF_POS1 - 8)) / 9 : (int)pr - 17 + PF_POS1);
                            if (prk + PF_DIST >= pos) break;
                            if (++n > (1u << 22)) break;
                            __nanosleep(100);
                        }
                    }
                    if (r < 8) {
                        const char* p = ((r & 1) ? vbase : kbase) + (size_t)(u * 4 + (r >> 1)) * 32768 + lane * 256;
#pragma unroll
                        for (int j = 0; j < 4; j++) sink |= l2_touch(p + j * 8192);
                    } else {
                        const char* p = wos + (size_t)u * 294912 + lane * 256;
#pragma unroll
                        for (int j = 0; j < 5; j++) if (j * 32 + lane < 144) sink |= l2_touch(p + j * 8192);
                    }
                    if (sink == 0x9E3779B9u) asm volatile("st.volatile.shared.u32 [%0], %1;" ::"r"(prog + 4), "r"(sink) : "memory");
                }
            }
        } else {
            const int hw = wid - 9;
            for (int k = 0; k < 3; k++) {
                mbar_wait(bars + 8 * (2 * NSTAGE + hw * 5 + k), 0);
                const int c = (k < 2) ? (2 * k + hw) : 4;
                asm volatile("fence.acq_rel.gpu;" ::: "memory");
                asm volatile("red.relaxed.gpu.global.add.u32 [%0], 1;" ::"l"(&g_cnt[(grp * 9 + c) * 32 + lane]) : "memory");
            }
        }
    } else {
        asm volatile("setmaxnreg.inc.sync.aligned.u32 232;");
        const int w = wid >> 2;
        const int t = tid & 127;
        int slot = 0, ph = 0, lim = NSTAGE;
        uint32_t qf[8][4];
        const uint32_t stash = smR + (1 + w) * 16384 + t * 16;
        {
            float acc[128];
            int pslot = 0;
            for (int s = 0; s < N_WQ; s++) {
                mbar_wait(bars + 8 * slot, ph);
                if (tid == 0 && s == 0) TS(20);
                if (tid == 0 && s == 5) TS(21);
                if (tid == 0 && s == 10) TS(22);
                const uint64_t da = mk_desc(smR + ((s >> 1) & 7) * 8192 + (s & 1) * 64, 16, 1024);
                const uint64_t db = mk_desc(smS + slot * STAGE_BYTES + w * 16384, 4096, 1024);
                wg_fence();
                wgmma_ss_n256_tb(acc, da, db, s != 0);
                wgmma_ss_n256_tb(acc, da + 2, db + 128, 1);
                wg_commit();
                wg_wait<0>();
                if (lane == 0) mbar_arrive(bars + 8 * (NSTAGE + slot));
                pslot = slot;
                if (++slot == NSTAGE) { slot = 0; ph ^= 1; }
            }
            fence_regs(acc);
            if (tid == 0) TS(1);
#pragma unroll
            for (int kk = 0; kk < 8; kk++) {
#pragma unroll
                for (int i = 0; i < 4; i++) qf[kk][i] = pack_bf16(acc[8 * kk + 2 * i], acc[8 * kk + 2 * i + 1]);
                sts128(stash + kk * 2048,
                       pack_bf16(acc[64 + 8 * kk + 0], acc[64 + 8 * kk + 1]), pack_bf16(acc[64 + 8 * kk + 2], acc[64 + 8 * kk + 3]),
                       pack_bf16(acc[64 + 8 * kk + 4], acc[64 + 8 * kk + 5]), pack_bf16(acc[64 + 8 * kk + 6], acc[64 + 8 * kk + 7]));
            }
        }
        if (w == 1) bar_arrive<5, 256>();
        const float sc = 0.08838834764831845f * 1.4426950408889634f;
        uint2* dst0 = g_part + (size_t)(grp * 80 + 2 * w * 8 + hp) * 1024 + t;
        uint2* dst8 = g_part + (size_t)(grp * 80 + 64 + hp * 2 + w) * 1024 + t;
#pragma unroll
        for (int u = 0; u < 2; u++) {
            uint32_t af[16][4];
            {
                float o[64], s[64];
                float m0 = -INFINITY, m1 = -INFINITY, l0 = 0.f, l1 = 0.f;
                uint32_t pf[8][4];
#pragma unroll
                for (int i = 0; i < 64; i++) { o[i] = 0.f; s[i] = 0.f; }
#pragma unroll
                for (int i = 0; i < 32; i++) pf[i >> 2][i & 3] = 0u;
#pragma unroll 1
                for (int tt = 0; tt <= 4; tt++) {
                    int vslot = slot;
                    if (tt > 0) {
                        mbar_wait(bars + 8 * slot, ph);
                        if (++slot == lim) { slot = 0; ph ^= 1; }
                    }
                    if (tt < 4) mbar_wait(bars + 8 * slot, ph);
                    if (tid == 0) TS(32 + u * 20 + tt * 4);
                    if (w == 0) bar_sync<5, 256>(); else bar_sync<6, 256>();
                    wg_fence();
                    if (tt > 0) {
                        const uint64_t db = mk_desc(smS + vslot * STAGE_BYTES, 16384, 1024);
#pragma unroll
                        for (int kk = 0; kk < 8; kk++)
                            wgmma_rs_n128_tb(o, pf[kk][0], pf[kk][1], pf[kk][2], pf[kk][3], db + kk * 128, (tt > 1) || (kk != 0));
                        wg_commit();
                    }
                    if (tt < 4) {
                        const uint64_t db = mk_desc(smS + slot * STAGE_BYTES, 16, 1024);
#pragma unroll
                        for (int kk = 0; kk < 8; kk++)
                            wgmma_rs_n128(s, qf[kk][0], qf[kk][1], qf[kk][2], qf[kk][3], db + (kk >> 2) * 1024 + (kk & 3) * 2, kk != 0);
                        wg_commit();
                    }
                    if (w == 0) bar_arrive<6, 256>(); else if (!(u == 1 && tt == 4)) bar_arrive<5, 256>();
                    if (tid == 0) TS(32 + u * 20 + tt * 4 + 1);
                    wg_wait<0>();
                    fence_regs(o);
                    fence_regs(s);
                    if (tid == 0) TS(32 + u * 20 + tt * 4 + 2);
                    if (tt > 0 && lane == 0) mbar_arrive(bars + 8 * (NSTAGE + vslot));
                    if (tt == 4) break;
                    if (lane == 0) mbar_arrive(bars + 8 * (NSTAGE + slot));
                    if (++slot == lim) { slot = 0; ph ^= 1; }
                    float mx0 = s[0], mx1 = s[2];
#pragma unroll
                    for (int j = 0; j < 16; j++) {
                        mx0 = fmaxf(mx0, fmaxf(s[4 * j], s[4 * j + 1]));
                        mx1 = fmaxf(mx1, fmaxf(s[4 * j + 2], s[4 * j + 3]));
                    }
                    mx0 = fmaxf(mx0, __shfl_xor_sync(0xffffffffu, mx0, 1));
                    mx1 = fmaxf(mx1, __shfl_xor_sync(0xffffffffu, mx1, 1));
                    mx0 = fmaxf(mx0, __shfl_xor_sync(0xffffffffu, mx0, 2));
                    mx1 = fmaxf(mx1, __shfl_xor_sync(0xffffffffu, mx1, 2));
                    const float mn0 = fmaxf(m0, mx0), mn1 = fmaxf(m1, mx1);
                    const float al0 = ex2((m0 - mn0) * sc), al1 = ex2((m1 - mn1) * sc);
                    m0 = mn0; m1 = mn1;
                    const float ms0 = mn0 * sc, ms1 = mn1 * sc;
                    float rs0 = 0.f, rs1 = 0.f;
#pragma unroll
                    for (int j = 0; j < 16; j++) {
                        const float p0 = ex2(fmaf(s[4 * j], sc, -ms0)), p1 = ex2(fmaf(s[4 * j + 1], sc, -ms0));
                        const float p2 = ex2(fmaf(s[4 * j + 2], sc, -ms1)), p3 = ex2(fmaf(s[4 * j + 3], sc, -ms1));
                        rs0 += p0 + p1; rs1 += p2 + p3;
                        pf[j >> 1][(j & 1) * 2] = pack_bf16(p0, p1);
                        pf[j >> 1][(j & 1) * 2 + 1] = pack_bf16(p2, p3);
                    }
                    l0 = l0 * al0 + rs0; l1 = l1 * al1 + rs1;
                    if (tt > 0) {
#pragma unroll
                        for (int j = 0; j < 16; j++) { o[4 * j] *= al0; o[4 * j + 1] *= al0; o[4 * j + 2] *= al1; o[4 * j + 3] *= al1; }
                    }
                    if (tid == 0) TS(32 + u * 20 + tt * 4 + 3);
                }
                if (tid == 0) TS(2 + u);
                l0 += __shfl_xor_sync(0xffffffffu, l0, 1);
                l1 += __shfl_xor_sync(0xffffffffu, l1, 1);
                l0 += __shfl_xor_sync(0xffffffffu, l0, 2);
                l1 += __shfl_xor_sync(0xffffffffu, l1, 2);
                const float i0 = 1.f / l0, i1 = 1.f / l1;
                const uint32_t zown = smR + (w ? 3 : 0) * 16384 + t * 16;
#pragma unroll
                for (int kk = 0; kk < 8; kk++) {
                    af[kk][0] = pack_bf16(o[8 * kk + 0] * i0, o[8 * kk + 1] * i0);
                    af[kk][1] = pack_bf16(o[8 * kk + 2] * i1, o[8 * kk + 3] * i1);
                    af[kk][2] = pack_bf16(o[8 * kk + 4] * i0, o[8 * kk + 5] * i0);
                    af[kk][3] = pack_bf16(o[8 * kk + 6] * i1, o[8 * kk + 7] * i1);
                    sts128(zown + kk * 2048, af[kk][0], af[kk][1], af[kk][2], af[kk][3]);
                }
            }
            if (w == 0) bar_arrive<7, 256>(); else bar_arrive<8, 256>();
            lim = 3;
            if (u == 0) {
#pragma unroll
                for (int kk = 0; kk < 8; kk++) lds128(stash + kk * 2048, qf[kk]);
            }
#pragma unroll
            for (int ps = 0; ps < 2; ps++) {
                float acc[64];
                const uint32_t keep = smS + (3 + ps) * STAGE_BYTES + w * 16384 + t * 16;
                if (u == 0) {
#pragma unroll
                    for (int i = 0; i < 64; i++) acc[i] = 0.f;
                } else {
#pragma unroll
                    for (int j = 0; j < 8; j++) {
                        uint32_t r[4];
                        lds128(keep + j * 2048, r);
#pragma unroll
                        for (int i = 0; i < 4; i++) { acc[8 * j + 2 * i] = __uint_as_float(r[i] << 16); acc[8 * j + 2 * i + 1] = __uint_as_float(r[i] & 0xffff0000u); }
                    }
                    asm volatile("fence.proxy.async.shared::cta;" ::: "memory");
                    __syncwarp();
                    if (lane == 0) mbar_arrive(bars + 8 * (NSTAGE + 3 + ps));
                }
#pragma unroll
                for (int st = 0; st < 4; st++) {
                    if (ps == 0 && st == 2) {
                        if (w == 0) bar_sync<8, 256>(); else bar_sync<7, 256>();
#pragma unroll
                        for (int kk = 0; kk < 8; kk++) lds128(smR + (w ? 0 : 3) * 16384 + kk * 2048 + t * 16, af[8 + kk]);
                    }
                    const bool extra = (u == 1) && ((ps == 0 && st == 3) || (ps == 1 && st == 2));
                    const int sl = extra ? (3 + ps) : slot;
                    mbar_wait(bars + 8 * sl, extra ? 1 : ph);
                    const uint64_t db = mk_desc(smS + sl * STAGE_BYTES + w * 16384, 8192, 1024);
                    wg_fence();
#pragma unroll
                    for (int kk = 0; kk < 4; kk++)
                        wgmma_rs_n128_tb(acc, af[st * 4 + kk][0], af[st * 4 + kk][1], af[st * 4 + kk][2], af[st * 4 + kk][3], db + kk * 128, 1);
                    wg_commit();
                    wg_wait<0>();
                    if (!extra) {
                        if (lane == 0) mbar_arrive(bars + 8 * (NSTAGE + slot));
                        if (++slot == 3) { slot = 0; ph ^= 1; }
                    }
                }
                fence_regs(acc);
                if (u == 0) {
#pragma unroll
                    for (int j = 0; j < 8; j++)
                        sts128(keep + j * 2048, pack_bf16(acc[8 * j], acc[8 * j + 1]), pack_bf16(acc[8 * j + 2], acc[8 * j + 3]),
                               pack_bf16(acc[8 * j + 4], acc[8 * j + 5]), pack_bf16(acc[8 * j + 6], acc[8 * j + 7]));
                } else {
                    uint2* dst = dst0 + (size_t)ps * 32 * 1024;
#pragma unroll
                    for (int j = 0; j < 16; j++)
                        __stcg(dst + (j >> 3) * 8192 + (j & 7) * 128, make_uint2(pack_bf16(acc[4 * j], acc[4 * j + 1]), pack_bf16(acc[4 * j + 2], acc[4 * j + 3])));
                    __syncwarp();
                    if (lane == 0) mbar_arrive(bars + 8 * (2 * NSTAGE + w * 5 + ps));
                }
                if (tid == 0) TS(4 + u * 8 + ps);
            }
            {
                float acc[32];
                if (u == 0) {
#pragma unroll
                    for (int i = 0; i < 32; i++) acc[i] = 0.f;
                } else {
#pragma unroll
                    for (int j = 0; j < 4; j++) {
                        uint32_t r[4];
                        lds128(stash + j * 2048, r);
#pragma unroll
                        for (int i = 0; i < 4; i++) { acc[8 * j + 2 * i] = __uint_as_float(r[i] << 16); acc[8 * j + 2 * i + 1] = __uint_as_float(r[i] & 0xffff0000u); }
                    }
                }
                mbar_wait(bars + 8 * slot, ph);
                const uint64_t db = mk_desc(smS + slot * STAGE_BYTES + w * 16384, 8192, 1024);
                wg_fence();
#pragma unroll
                for (int kk = 0; kk < 8; kk++)
                    wgmma_rs_n64_tb(acc, af[kk][0], af[kk][1], af[kk][2], af[kk][3], db + kk * 128, 1);
                wg_commit();
                wg_wait<0>();
                if (lane == 0) mbar_arrive(bars + 8 * (NSTAGE + slot));
                if (++slot == 3) { slot = 0; ph ^= 1; }
                fence_regs(acc);
                if (u == 0) {
#pragma unroll
                    for (int j = 0; j < 4; j++)
                        sts128(stash + j * 2048, pack_bf16(acc[8 * j], acc[8 * j + 1]), pack_bf16(acc[8 * j + 2], acc[8 * j + 3]),
                               pack_bf16(acc[8 * j + 4], acc[8 * j + 5]), pack_bf16(acc[8 * j + 6], acc[8 * j + 7]));
                } else {
#pragma unroll
                    for (int j = 0; j < 8; j++)
                        __stcg(dst8 + j * 128, make_uint2(pack_bf16(acc[4 * j], acc[4 * j + 1]), pack_bf16(acc[4 * j + 2], acc[4 * j + 3])));
                    __syncwarp();
                    if (lane == 0) mbar_arrive(bars + 8 * (2 * NSTAGE + w * 5 + 2));
                }
                if (tid == 0) TS(6 + u * 8);
            }
        }
        {
            const int nch = (w == 0) ? 3 : 2;
            if (lane < nch) {
                const int c = (lane < 2) ? (2 * lane + w) : 4;
                const unsigned need = (lane < 2) ? 8u : 16u;
                unsigned* cp = &g_cnt[(grp * 9 + c) * 32 + hp * 4 + (wid & 3)];
                unsigned v, n = 0;
                while (true) {
                    asm volatile("ld.acquire.gpu.global.u32 %0, [%1];" : "=r"(v) : "l"(cp) : "memory");
                    if (v >= need) break;
                    if (++n > (1u << 21)) break;
                }
                *cp = 0;
            }
            __syncwarp();
            if (tid == 0) TS(18);
            __nv_bfloat16* orow = P.out + (size_t)(b * 64 + (t >> 5) * 16 + (lane >> 2)) * (2 * kD) + blk * kD + hp * 8 + (lane & 3) * 2;
            const uint2* src = g_part + ((size_t)(grp * 80 + 2 * w * 8) * 8 + hp) * 128 + t;
            uint2 v[4][8];
#pragma unroll
            for (int k = 0; k < 4; k++)
#pragma unroll
                for (int i = 0; i < 8; i++) v[k][i] = __ldcg(src + (size_t)((k >> 1) * 32 + (k & 1) * 8 + i) * 1024);
            if (w == 0) {
                const uint2* src8 = g_part + ((size_t)(grp * 80 + 64) * 8 + hp) * 128 + t;
                uint2 u[16];
#pragma unroll
                for (int i = 0; i < 16; i++) u[i] = __ldcg(src8 + (size_t)i * 1024);
                float a0 = 0.f, a1 = 0.f, a2 = 0.f, a3 = 0.f;
#pragma unroll
                for (int i = 0; i < 16; i++) {
                    a0 += __uint_as_float(u[i].x << 16); a1 += __uint_as_float(u[i].x & 0xffff0000u);
                    a2 += __uint_as_float(u[i].y << 16); a3 += __uint_as_float(u[i].y & 0xffff0000u);
                }
                *(uint32_t*)(orow + 512) = pack_bf16(a0, a1);
                *(uint32_t*)(orow + 512 + 8 * 2 * kD) = pack_bf16(a2, a3);
            }
#pragma unroll
            for (int k = 0; k < 4; k++) {
                float a0 = 0.f, a1 = 0.f, a2 = 0.f, a3 = 0.f;
#pragma unroll
                for (int i = 0; i < 8; i++) {
                    a0 += __uint_as_float(v[k][i].x << 16); a1 += __uint_as_float(v[k][i].x & 0xffff0000u);
                    a2 += __uint_as_float(v[k][i].y << 16); a3 += __uint_as_float(v[k][i].y & 0xffff0000u);
                }
                *(uint32_t*)(orow + ((k >> 1) * 4 + 2 * w + (k & 1)) * 64) = pack_bf16(a0, a1);
                *(uint32_t*)(orow + ((k >> 1) * 4 + 2 * w + (k & 1)) * 64 + 8 * 2 * kD) = pack_bf16(a2, a3);
            }
            if (tid == 0) TS(19);
        }
    }
}

typedef CUresult (*EncodeFn)(CUtensorMap*, CUtensorMapDataType, cuuint32_t, void*, const cuuint64_t*, const cuuint64_t*,
                             const cuuint32_t*, const cuuint32_t*, CUtensorMapInterleave, CUtensorMapSwizzle,
                             CUtensorMapL2promotion, CUtensorMapFloatOOBfill);

void make_map(EncodeFn fn, CUtensorMap* m, const void* ptr, uint64_t cols, uint64_t rows, uint32_t box_rows) {
    cuuint64_t dims[2] = {cols, rows};
    cuuint64_t strides[1] = {cols * 2};
    cuuint32_t box[2] = {64, box_rows};
    cuuint32_t es[2] = {1, 1};
    fn(m, CU_TENSOR_MAP_DATA_TYPE_BFLOAT16, 2, const_cast<void*>(ptr), dims, strides, box, es, CU_TENSOR_MAP_INTERLEAVE_NONE,
       CU_TENSOR_MAP_SWIZZLE_128B, CU_TENSOR_MAP_L2_PROMOTION_L2_256B, CU_TENSOR_MAP_FLOAT_OOB_FILL_NONE);
}

void make_map3(EncodeFn fn, CUtensorMap* m, const void* ptr, uint64_t cols, uint64_t rows, uint32_t box_rows, uint32_t box_groups) {
    cuuint64_t dims[3] = {64, rows, cols / 64};
    cuuint64_t strides[2] = {cols * 2, 128};
    cuuint32_t box[3] = {64, box_rows, box_groups};
    cuuint32_t es[3] = {1, 1, 1};
    fn(m, CU_TENSOR_MAP_DATA_TYPE_BFLOAT16, 3, const_cast<void*>(ptr), dims, strides, box, es, CU_TENSOR_MAP_INTERLEAVE_NONE,
       CU_TENSOR_MAP_SWIZZLE_128B, CU_TENSOR_MAP_L2_PROMOTION_L2_256B, CU_TENSOR_MAP_FLOAT_OOB_FILL_NONE);
}

}

extern "C" void kernel_launch(void* const* d_in, const int* in_sizes, int n_in, void* d_out, int out_size) {
    static EncodeFn enc = nullptr;
    if (!enc) {
        void* fn = nullptr;
        cudaDriverEntryPointQueryResult st;
        cudaGetDriverEntryPoint("cuTensorMapEncodeTiled", &fn, cudaEnableDefault, &st);
        enc = (EncodeFn)fn;
        cudaFuncSetAttribute(fused_gqa_kernel, cudaFuncAttributeMaxDynamicSharedMemorySize, SMEM_BYTES);
    }
    Params P;
    for (int blk = 0; blk < 2; blk++) {
        const void* x = d_in[blk * 5 + 0];
        const void* k = d_in[blk * 5 + 1];
        const void* v = d_in[blk * 5 + 2];
        const void* wq = d_in[blk * 5 + 3];
        const void* wo = d_in[blk * 5 + 4];
        make_map(enc, &P.x[blk], x, kD, kB * kSq, 64);
        make_map3(enc, &P.wq[blk], wq, kHq * kDh, kD, 32, 2);
        make_map3(enc, &P.k[blk], k, kDh, (uint64_t)kB * kHkv * kSk, 128, 2);
        make_map3(enc, &P.v[blk], v, kDh, (uint64_t)kB * kHkv * kSk, 128, 2);
        make_map3(enc, &P.wo[blk], wo, kD, kHq * kDh, 64, 2);
        make_map(enc, &P.wo8[blk], wo, kD, kHq * kDh, 128);
        P.wqp[blk] = (const __nv_bfloat16*)wq;
        P.kp[blk] = (const __nv_bfloat16*)k;
        P.vp[blk] = (const __nv_bfloat16*)v;
        P.wop[blk] = (const __nv_bfloat16*)wo;
    }
    P.out = (__nv_bfloat16*)d_out;
    fused_gqa_kernel<<<128, 384, SMEM_BYTES>>>(P);
}
```

```cpp
#include <cuda_runtime.h>
#include <cuda_bf16.h>
#include <cuda.h>
#include <stdint.h>

namespace {

constexpr int kB = 8, kSq = 64, kD = 576, kHq = 32, kHkv = 16, kSk = 512, kDh = 128;
constexpr int NSTAGE = 5;
constexpr int STAGE_BYTES = 32768;
constexpr int R_BYTES = 65536;
constexpr int SMEM_BYTES = R_BYTES + NSTAGE * STAGE_BYTES + 1024   + 256  ;
constexpr int N_WQ = 18;
#define PF_DIST_V 6
#define OP_WAIT0 1
#define QP_WAIT0 1
#define PF_POS1 9
#define PF_WQ 0
#define PF_SLEEP 1000
constexpr int PF_DIST = PF_DIST_V;

struct __align__(64) Params {
    CUtensorMap x[2], wq[2], k[2], v[2], wo[2], wo8[2];
    const __nv_bfloat16* wqp[2];
    const __nv_bfloat16* kp[2];
    const __nv_bfloat16* vp[2];
    const __nv_bfloat16* wop[2];
    __nv_bfloat16* out;
};

__device__ uint2 g_part[16 * 80 * 8 * 128];
__device__ unsigned int g_cnt[16 * 9 * 32];
#define TS(k) do {} while (0)

__device__ __forceinline__ uint32_t smem_u32(const void* p) { return (uint32_t)__cvta_generic_to_shared(p); }
__device__ __forceinline__ void mbar_init(uint32_t bar, int cnt) {
    asm volatile("mbarrier.init.shared::cta.b64 [%0], %1;" ::"r"(bar), "r"(cnt));
}
__device__ __forceinline__ void mbar_expect_tx(uint32_t bar, uint32_t bytes) {
    asm volatile("mbarrier.arrive.expect_tx.shared::cta.b64 _, [%0], %1;" ::"r"(bar), "r"(bytes) : "memory");
}
__device__ __forceinline__ void mbar_arrive(uint32_t bar) {
    asm volatile("mbarrier.arrive.shared::cta.b64 _, [%0];" ::"r"(bar) : "memory");
}
__device__ __forceinline__ bool mbar_try(uint32_t bar, uint32_t parity) {
    uint32_t ok;
    asm volatile("{\n.reg .pred p;\nmbarrier.try_wait.parity.shared::cta.b64 p, [%1], %2;\nselp.u32 %0, 1, 0, p;\n}\n"
                 : "=r"(ok) : "r"(bar), "r"(parity) : "memory");
    return ok != 0;
}
__device__ __forceinline__ void mbar_wait(uint32_t bar, uint32_t parity) {
    if (mbar_try(bar, parity)) return;
    uint32_t n = 0;
    while (!mbar_try(bar, parity)) {
        if (++n > (1u << 20)) break;
    }
}
__device__ __forceinline__ void tma_2d(uint32_t dst, const CUtensorMap* tm, int c0, int c1, uint32_t bar) {
    asm volatile("cp.async.bulk.tensor.2d.shared::cluster.global.mbarrier::complete_tx::bytes [%0], [%1, {%3, %4}], [%2];"
                 ::"r"(dst), "l"(tm), "r"(bar), "r"(c0), "r"(c1) : "memory");
}
__device__ __forceinline__ void tma_3d(uint32_t dst, const CUtensorMap* tm, int c0, int c1, int c2, uint32_t bar) {
    asm volatile("cp.async.bulk.tensor.3d.shared::cluster.global.mbarrier::complete_tx::bytes [%0], [%1, {%3, %4, %5}], [%2];"
                 ::"r"(dst), "l"(tm), "r"(bar), "r"(c0), "r"(c1), "r"(c2) : "memory");
}
__device__ __forceinline__ void l2_prefetch(const void* p, uint32_t bytes) {
    asm volatile("cp.async.bulk.prefetch.L2.global [%0], %1;" ::"l"(p), "r"(bytes) : "memory");
}
__device__ __forceinline__ uint32_t l2_touch(const void* p) {
    uint32_t v;
    asm volatile("ld.global.L2::256B.b32 %0, [%1];" : "=r"(v) : "l"(p) : "memory");
    return v;
}
__device__ __forceinline__ void wg_fence() { asm volatile("wgmma.fence.sync.aligned;" ::: "memory"); }
__device__ __forceinline__ void wg_commit() { asm volatile("wgmma.commit_group.sync.aligned;" ::: "memory"); }
template <int N> __device__ __forceinline__ void wg_wait() { asm volatile("wgmma.wait_group.sync.aligned %0;" ::"n"(N) : "memory"); }
template <int N> __device__ __forceinline__ void fence_regs(float (&d)[N]) {
#pragma unroll
    for (int i = 0; i < N; i++) asm volatile("" : "+f"(d[i])::"memory");
}
__device__ __forceinline__ uint64_t mk_desc(uint32_t addr, uint32_t lbo, uint32_t sbo) {
    return (uint64_t)((addr & 0x3FFFF) >> 4) | ((uint64_t)(lbo >> 4) << 16) | ((uint64_t)(sbo >> 4) << 32) | (1ull << 62);
}
__device__ __forceinline__ uint32_t pack_bf16(float a, float b) {
    uint32_t r;
    asm("cvt.rn.bf16x2.f32 %0, %1, %2;" : "=r"(r) : "f"(b), "f"(a));
    return r;
}
__device__ __forceinline__ float ex2(float x) {
    float y;
    asm("ex2.approx.ftz.f32 %0, %1;" : "=f"(y) : "f"(x));
    return y;
}
template <int ID, int N> __device__ __forceinline__ void bar_sync() { asm volatile("bar.sync %0, %1;" ::"n"(ID), "n"(N) : "memory"); }
template <int ID, int N> __device__ __forceinline__ void bar_arrive() { asm volatile("bar.arrive %0, %1;" ::"n"(ID), "n"(N) : "memory"); }
__device__ __forceinline__ void sts128(uint32_t addr, uint32_t a, uint32_t b, uint32_t c, uint32_t d) {
    asm volatile("st.shared.v4.b32 [%0], {%1,%2,%3,%4};" ::"r"(addr), "r"(a), "r"(b), "r"(c), "r"(d) : "memory");
}
__device__ __forceinline__ void sts64(uint32_t addr, uint32_t a, uint32_t b) {
    asm volatile("st.shared.v2.b32 [%0], {%1,%2};" ::"r"(addr), "r"(a), "r"(b) : "memory");
}
__device__ __forceinline__ void bulk_store(void* dst, uint32_t src, uint32_t bytes) {
    asm volatile("cp.async.bulk.global.shared::cta.bulk_group [%0], [%1], %2;" ::"l"(dst), "r"(src), "r"(bytes) : "memory");
}
__device__ __forceinline__ void lds128(uint32_t addr, uint32_t (&r)[4]) {
    asm volatile("ld.shared.v4.b32 {%0,%1,%2,%3}, [%4];" : "=r"(r[0]), "=r"(r[1]), "=r"(r[2]), "=r"(r[3]) : "r"(addr) : "memory");
}

__device__ __forceinline__ void wgmma_ss_n256_tb(float (&d)[128], uint64_t da, uint64_t db, int sd) {
    asm volatile("{\n.reg .pred p;\nsetp.ne.b32 p, %130, 0;\n"
        "wgmma.mma_async.sync.aligned.m64n256k16.f32.bf16.bf16 "
        "{%0, %1, %2, %3, %4, %5, %6, %7, %8, %9, %10, %11, %12, %13, %14, %15, %16, %17, %18, %19, %20, %21, %22, %23, %24, %25, %26, %27, %28, %29, %30, %31, %32, %33, %34, %35, %36, %37, %38, %39, %40, %41, %42, %43, %44, %45, %46, %47, %48, %49, %50, %51, %52, %53, %54, %55, %56, %57, %58, %59, %60, %61, %62, %63, %64, %65, %66, %67, %68, %69, %70, %71, %72, %73, %74, %75, %76, %77, %78, %79, %80, %81, %82, %83, %84, %85, %86, %87, %88, %89, %90, %91, %92, %93, %94, %95, %96, %97, %98, %99, %100, %101, %102, %103, %104, %105, %106, %107, %108, %109, %110, %111, %112, %113, %114, %115, %116, %117, %118, %119, %120, %121, %122, %123, %124, %125, %126, %127}, "
        "%128, %129, p, 1, 1, 0, 1;\n}\n"
        : "+f"(d[0]), "+f"(d[1]), "+f"(d[2]), "+f"(d[3]), "+f"(d[4]), "+f"(d[5]), "+f"(d[6]), "+f"(d[7]), "+f"(d[8]), "+f"(d[9]), "+f"(d[10]), "+f"(d[11]), "+f"(d[12]), "+f"(d[13]), "+f"(d[14]), "+f"(d[15]), "+f"(d[16]), "+f"(d[17]), "+f"(d[18]), "+f"(d[19]), "+f"(d[20]), "+f"(d[21]), "+f"(d[22]), "+f"(d[23]), "+f"(d[24]), "+f"(d[25]), "+f"(d[26]), "+f"(d[27]), "+f"(d[28]), "+f"(d[29]), "+f"(d[30]), "+f"(d[31]), "+f"(d[32]), "+f"(d[33]), "+f"(d[34]), "+f"(d[35]), "+f"(d[36]), "+f"(d[37]), "+f"(d[38]), "+f"(d[39]), "+f"(d[40]), "+f"(d[41]), "+f"(d[42]), "+f"(d[43]), "+f"(d[44]), "+f"(d[45]), "+f"(d[46]), "+f"(d[47]), "+f"(d[48]), "+f"(d[49]), "+f"(d[50]), "+f"(d[51]), "+f"(d[52]), "+f"(d[53]), "+f"(d[54]), "+f"(d[55]), "+f"(d[56]), "+f"(d[57]), "+f"(d[58]), "+f"(d[59]), "+f"(d[60]), "+f"(d[61]), "+f"(d[62]), "+f"(d[63]), "+f"(d[64]), "+f"(d[65]), "+f"(d[66]), "+f"(d[67]), "+f"(d[68]), "+f"(d[69]), "+f"(d[70]), "+f"(d[71]), "+f"(d[72]), "+f"(d[73]), "+f"(d[74]), "+f"(d[75]), "+f"(d[76]), "+f"(d[77]), "+f"(d[78]), "+f"(d[79]), "+f"(d[80]), "+f"(d[81]), "+f"(d[82]), "+f"(d[83]), "+f"(d[84]), "+f"(d[85]), "+f"(d[86]), "+f"(d[87]), "+f"(d[88]), "+f"(d[89]), "+f"(d[90]), "+f"(d[91]), "+f"(d[92]), "+f"(d[93]), "+f"(d[94]), "+f"(d[95]), "+f"(d[96]), "+f"(d[97]), "+f"(d[98]), "+f"(d[99]), "+f"(d[100]), "+f"(d[101]), "+f"(d[102]), "+f"(d[103]), "+f"(d[104]), "+f"(d[105]), "+f"(d[106]), "+f"(d[107]), "+f"(d[108]), "+f"(d[109]), "+f"(d[110]), "+f"(d[111]), "+f"(d[112]), "+f"(d[113]), "+f"(d[114]), "+f"(d[115]), "+f"(d[116]), "+f"(d[117]), "+f"(d[118]), "+f"(d[119]), "+f"(d[120]), "+f"(d[121]), "+f"(d[122]), "+f"(d[123]), "+f"(d[124]), "+f"(d[125]), "+f"(d[126]), "+f"(d[127])
        : "l"(da), "l"(db), "r"(sd));
}
__device__ __forceinline__ void wgmma_rs_n128(float (&d)[64], uint32_t a0, uint32_t a1, uint32_t a2, uint32_t a3, uint64_t db, int sd) {
    asm volatile("{\n.reg .pred p;\nsetp.ne.b32 p, %69, 0;\n"
        "wgmma.mma_async.sync.aligned.m64n128k16.f32.bf16.bf16 "
        "{%0, %1, %2, %3, %4, %5, %6, %7, %8, %9, %10, %11, %12, %13, %14, %15, %16, %17, %18, %19, %20, %21, %22, %23, %24, %25, %26, %27, %28, %29, %30, %31, %32, %33, %34, %35, %36, %37, %38, %39, %40, %41, %42, %43, %44, %45, %46, %47, %48, %49, %50, %51, %52, %53, %54, %55, %56, %57, %58, %59, %60, %61, %62, %63}, "
        "{%64, %65, %66, %67}, %68, p, 1, 1, 0;\n}\n"
        : "+f"(d[0]), "+f"(d[1]), "+f"(d[2]), "+f"(d[3]), "+f"(d[4]), "+f"(d[5]), "+f"(d[6]), "+f"(d[7]), "+f"(d[8]), "+f"(d[9]), "+f"(d[10]), "+f"(d[11]), "+f"(d[12]), "+f"(d[13]), "+f"(d[14]), "+f"(d[15]), "+f"(d[16]), "+f"(d[17]), "+f"(d[18]), "+f"(d[19]), "+f"(d[20]), "+f"(d[21]), "+f"(d[22]), "+f"(d[23]), "+f"(d[24]), "+f"(d[25]), "+f"(d[26]), "+f"(d[27]), "+f"(d[28]), "+f"(d[29]), "+f"(d[30]), "+f"(d[31]), "+f"(d[32]), "+f"(d[33]), "+f"(d[34]), "+f"(d[35]), "+f"(d[36]), "+f"(d[37]), "+f"(d[38]), "+f"(d[39]), "+f"(d[40]), "+f"(d[41]), "+f"(d[42]), "+f"(d[43]), "+f"(d[44]), "+f"(d[45]), "+f"(d[46]), "+f"(d[47]), "+f"(d[48]), "+f"(d[49]), "+f"(d[50]), "+f"(d[51]), "+f"(d[52]), "+f"(d[53]), "+f"(d[54]), "+f"(d[55]), "+f"(d[56]), "+f"(d[57]), "+f"(d[58]), "+f"(d[59]), "+f"(d[60]), "+f"(d[61]), "+f"(d[62]), "+f"(d[63])
        : "r"(a0), "r"(a1), "r"(a2), "r"(a3), "l"(db), "r"(sd));
}
__device__ __forceinline__ void wgmma_rs_n128_tb(float (&d)[64], uint32_t a0, uint32_t a1, uint32_t a2, uint32_t a3, uint64_t db, int sd) {
    asm volatile("{\n.reg .pred p;\nsetp.ne.b32 p, %69, 0;\n"
        "wgmma.mma_async.sync.aligned.m64n128k16.f32.bf16.bf16 "
        "{%0, %1, %2, %3, %4, %5, %6, %7, %8, %9, %10, %11, %12, %13, %14, %15, %16, %17, %18, %19, %20, %21, %22, %23, %24, %25, %26, %27, %28, %29, %30, %31, %32, %33, %34, %35, %36, %37, %38, %39, %40, %41, %42, %43, %44, %45, %46, %47, %48, %49, %50, %51, %52, %53, %54, %55, %56, %57, %58, %59, %60, %61, %62, %63}, "
        "{%64, %65, %66, %67}, %68, p, 1, 1, 1;\n}\n"
        : "+f"(d[0]), "+f"(d[1]), "+f"(d[2]), "+f"(d[3]), "+f"(d[4]), "+f"(d[5]), "+f"(d[6]), "+f"(d[7]), "+f"(d[8]), "+f"(d[9]), "+f"(d[10]), "+f"(d[11]), "+f"(d[12]), "+f"(d[13]), "+f"(d[14]), "+f"(d[15]), "+f"(d[16]), "+f"(d[17]), "+f"(d[18]), "+f"(d[19]), "+f"(d[20]), "+f"(d[21]), "+f"(d[22]), "+f"(d[23]), "+f"(d[24]), "+f"(d[25]), "+f"(d[26]), "+f"(d[27]), "+f"(d[28]), "+f"(d[29]), "+f"(d[30]), "+f"(d[31]), "+f"(d[32]), "+f"(d[33]), "+f"(d[34]), "+f"(d[35]), "+f"(d[36]), "+f"(d[37]), "+f"(d[38]), "+f"(d[39]), "+f"(d[40]), "+f"(d[41]), "+f"(d[42]), "+f"(d[43]), "+f"(d[44]), "+f"(d[45]), "+f"(d[46]), "+f"(d[47]), "+f"(d[48]), "+f"(d[49]), "+f"(d[50]), "+f"(d[51]), "+f"(d[52]), "+f"(d[53]), "+f"(d[54]), "+f"(d[55]), "+f"(d[56]), "+f"(d[57]), "+f"(d[58]), "+f"(d[59]), "+f"(d[60]), "+f"(d[61]), "+f"(d[62]), "+f"(d[63])
        : "r"(a0), "r"(a1), "r"(a2), "r"(a3), "l"(db), "r"(sd));
}
__device__ __forceinline__ void wgmma_rs_n64_tb(float (&d)[32], uint32_t a0, uint32_t a1, uint32_t a2, uint32_t a3, uint64_t db, int sd) {
    asm volatile("{\n.reg .pred p;\nsetp.ne.b32 p, %37, 0;\n"
        "wgmma.mma_async.sync.aligned.m64n64k16.f32.bf16.bf16 "
        "{%0, %1, %2, %3, %4, %5, %6, %7, %8, %9, %10, %11, %12, %13, %14, %15, %16, %17, %18, %19, %20, %21, %22, %23, %24, %25, %26, %27, %28, %29, %30, %31}, "
        "{%32, %33, %34, %35}, %36, p, 1, 1, 1;\n}\n"
        : "+f"(d[0]), "+f"(d[1]), "+f"(d[2]), "+f"(d[3]), "+f"(d[4]), "+f"(d[5]), "+f"(d[6]), "+f"(d[7]), "+f"(d[8]), "+f"(d[9]), "+f"(d[10]), "+f"(d[11]), "+f"(d[12]), "+f"(d[13]), "+f"(d[14]), "+f"(d[15]), "+f"(d[16]), "+f"(d[17]), "+f"(d[18]), "+f"(d[19]), "+f"(d[20]), "+f"(d[21]), "+f"(d[22]), "+f"(d[23]), "+f"(d[24]), "+f"(d[25]), "+f"(d[26]), "+f"(d[27]), "+f"(d[28]), "+f"(d[29]), "+f"(d[30]), "+f"(d[31])
        : "r"(a0), "r"(a1), "r"(a2), "r"(a3), "l"(db), "r"(sd));
}

__global__ void __launch_bounds__(384, 1) fused_gqa_kernel(const __grid_constant__ Params P) {
    extern __shared__ uint8_t smem_raw[];
    const uint32_t base = (smem_u32(smem_raw) + 1023u) & ~1023u;
    const uint32_t smR = base;
    const uint32_t smS = base + R_BYTES;
    const uint32_t bars = smS + NSTAGE * STAGE_BYTES;
    const uint32_t prog = bars + 8 * (2 * NSTAGE + 10);
    const int tid = threadIdx.x;
    const int wid = __shfl_sync(0xffffffffu, tid >> 5, 0);
    const int lane = tid & 31;

    const int cta = blockIdx.x;
    const int blk = cta >> 6;
    const int hp = (cta >> 3) & 7;
    const int b = cta & 7;
    const int grp = blk * 8 + b;

    if (tid == 0) {
        TS(0);
        for (int i = 0; i < NSTAGE; i++) {
            mbar_init(bars + 8 * i, 1);
            mbar_init(bars + 8 * (NSTAGE + i), 8);
        }
        for (int i = 0; i < 10; i++) mbar_init(bars + 8 * (2 * NSTAGE + i), 4);
        asm volatile("st.volatile.shared.u32 [%0], %1;" ::"r"(prog), "r"(0) : "memory");
        asm volatile("fence.mbarrier_init.release.cluster;" ::: "memory");
        asm volatile("fence.proxy.async.shared::cta;" ::: "memory");
    }
    __syncthreads();

    if (wid >= 8) {
        asm volatile("setmaxnreg.dec.sync.aligned.u32 40;");
        if (wid == 8) {
            if (lane == 0) {
                int slot = 0, ph = 1;
                for (int s = 0; s < N_WQ; s++) {
                    const uint32_t fb = bars + 8 * slot;
                    mbar_wait(bars + 8 * (NSTAGE + slot), ph);
                    const uint32_t dst = smS + slot * STAGE_BYTES;
                    mbar_expect_tx(fb, (s & 1) ? STAGE_BYTES : STAGE_BYTES + 8192);
                    if (!(s & 1)) tma_2d(smR + ((s >> 1) & 7) * 8192, &P.x[blk], (s >> 1) * 64, b * 64, fb);
#pragma unroll
                    for (int p = 0; p < 4; p++) {
                        const int w = p >> 1, j = p & 1;
                        tma_3d(dst + p * 8192, &P.wq[blk], 0, s * 32, hp * 8 + j * 4 + w * 2, fb);
                    }
                    if (++slot == NSTAGE) { slot = 0; ph ^= 1; }
                }
                int lim = NSTAGE;
                for (int i = 0; i < 34; i++) {
                    const int u = (i >= 17), r = i - 17 * u;
                    const uint32_t fb = bars + 8 * slot;
                    mbar_wait(bars + 8 * (NSTAGE + slot), ph);
                    const uint32_t dst = smS + slot * STAGE_BYTES;
                    mbar_expect_tx(fb, STAGE_BYTES);
                    if (r < 8) {
                        const int row = (b * kHkv + hp * 2 + u) * kSk + (r >> 1) * 128;
                        tma_3d(dst, (r & 1) ? &P.v[blk] : &P.k[blk], 0, row, 0, fb);
                    } else {
                        const int q = r - 8, row = hp * 512 + u * 256;
                        if (q < 8) {
                            tma_3d(dst, &P.wo[blk], 0, row + (q & 3) * 64, (q >> 2) * 4, fb);
                            tma_3d(dst + 16384, &P.wo[blk], 0, row + ((q & 3) ^ 2) * 64, (q >> 2) * 4 + 2, fb);
                        } else {
                            tma_2d(dst, &P.wo8[blk], 512, row, fb);
                            tma_2d(dst + 16384, &P.wo8[blk], 512, row + 128, fb);
                        }
                    }
                    asm volatile("st.volatile.shared.u32 [%0], %1;" ::"r"(prog), "r"(i + 1) : "memory");
                    if (i == 7) lim = 3;
                    if (++slot == lim) { slot = 0; ph ^= 1; }
                }
            }
        } else if (wid == 11) {
            if (PF_DIST > 0) {
                uint32_t sink = 0;
                mbar_wait(bars, 0);
                if (PF_WQ) {
                    const char* wqs = (const char*)(P.wqp[blk] + hp * 512) + (size_t)(160 + b * 52) * 8192;
#pragma unroll
                    for (int h = 0; h < 2; h++) {
#pragma unroll
                        for (int j = 0; j < 4; j++) {
                            const int e = (h * 4 + j) * 32 + lane;
                            if (e < 208) sink |= l2_touch(wqs + (size_t)(e >> 2) * 8192 + (e & 3) * 256);
                        }
                        if (sink == 0x9E3779B9u) asm volatile("st.volatile.shared.u32 [%0], %1;" ::"r"(prog + 4), "r"(sink) : "memory");
                    }
                }
                const char* kbase = (const char*)(P.kp[blk] + (size_t)(b * kHkv + hp * 2) * kSk * kDh);
                const char* vbase = (const char*)(P.vp[blk] + (size_t)(b * kHkv + hp * 2) * kSk * kDh);
                const char* wos = (const char*)(P.wop[blk] + (size_t)hp * 512 * kD) + (size_t)b * 36864;
                for (int i = 0; i < 18; i++) {
                    const int u = (i >= 9), r = i - 9 * u;
                    const int pos = u ? (PF_POS1 + r) : r;
                    if (pos >= PF_DIST) {
                        uint32_t pr, n = 0;
                        while (true) {
                            asm volatile("ld.volatile.shared.u32 %0, [%1];" : "=r"(pr) : "r"(prog) : "memory");
                            const int prk = ((int)pr <= 8) ? (int)pr : (((int)pr <= 17) ? 8 + (((int)pr - 8) * (PF_POS1 - 8)) / 9 : (int)pr - 17 + PF_POS1);
                            if (prk + PF_DIST >= pos) break;
                            if (++n > (1u << 22)) break;
                            __nanosleep(100);
                        }
                    }
                    if (r < 8) {
                        const char* p = ((r & 1) ? vbase : kbase) + (size_t)(u * 4 + (r >> 1)) * 32768 + lane * 256;
#pragma unroll
                        for (int j = 0; j < 4; j++) sink |= l2_touch(p + j * 8192);
                    } else {
                        const char* p = wos + (size_t)u * 294912 + lane * 256;
#pragma unroll
                        for (int j = 0; j < 5; j++) if (j * 32 + lane < 144) sink |= l2_touch(p + j * 8192);
                    }
                    if (sink == 0x9E3779B9u) asm volatile("st.volatile.shared.u32 [%0], %1;" ::"r"(prog + 4), "r"(sink) : "memory");
                }
            }
        } else {
            const int hw = wid - 9;
            for (int k = 0; k < 3; k++) {
                mbar_wait(bars + 8 * (2 * NSTAGE + hw * 5 + k), 0);
                const int c = (k < 2) ? (2 * k + hw) : 4;
                if (lane == 0) {
                    if (k < 2) {
                        uint2* dst = g_part + (size_t)(grp * 80 + (4 * k + 2 * hw) * 8 + hp) * 1024;
                        const uint32_t src = smS + (3 + k) * STAGE_BYTES + hw * 16384;
                        bulk_store(dst, src, 8192);
                        bulk_store(dst + 8192, src + 8192, 8192);
                    } else {
                        bulk_store(g_part + (size_t)(grp * 80 + 64 + hp * 2 + hw) * 1024, smR + (1 + hw) * 16384, 8192);
                    }
                    asm volatile("cp.async.bulk.commit_group;" ::: "memory");
                    asm volatile("cp.async.bulk.wait_group 0;" ::: "memory");
                    asm volatile("fence.acq_rel.gpu;" ::: "memory");
                }
                __syncwarp();
                asm volatile("red.release.gpu.global.add.u32 [%0], 1;" ::"l"(&g_cnt[(grp * 9 + c) * 32 + lane]) : "memory");
            }
        }
    } else {
        asm volatile("setmaxnreg.inc.sync.aligned.u32 232;");
        const int w = wid >> 2;
        const int t = tid & 127;
        int slot = 0, ph = 0, lim = NSTAGE;
        uint32_t qf[8][4];
        const uint32_t stash = smR + (1 + w) * 16384 + t * 16;
        {
            float acc[128];
            int pslot = 0;
            for (int s = 0; s < N_WQ; s++) {
                mbar_wait(bars + 8 * slot, ph);
                if (tid == 0 && s == 0) TS(20);
                if (tid == 0 && s == 5) TS(21);
                if (tid == 0 && s == 10) TS(22);
                const uint64_t da = mk_desc(smR + ((s >> 1) & 7) * 8192 + (s & 1) * 64, 16, 1024);
                const uint64_t db = mk_desc(smS + slot * STAGE_BYTES + w * 16384, 4096, 1024);
                wg_fence();
                wgmma_ss_n256_tb(acc, da, db, s != 0);
                wgmma_ss_n256_tb(acc, da + 2, db + 128, 1);
                wg_commit();
                wg_wait<0>();
                if (lane == 0) mbar_arrive(bars + 8 * (NSTAGE + slot));
                pslot = slot;
                if (++slot == NSTAGE) { slot = 0; ph ^= 1; }
            }
            fence_regs(acc);
            if (tid == 0) TS(1);
#pragma unroll
            for (int kk = 0; kk < 8; kk++) {
#pragma unroll
                for (int i = 0; i < 4; i++) qf[kk][i] = pack_bf16(acc[8 * kk + 2 * i], acc[8 * kk + 2 * i + 1]);
                sts128(stash + kk * 2048,
                       pack_bf16(acc[64 + 8 * kk + 0], acc[64 + 8 * kk + 1]), pack_bf16(acc[64 + 8 * kk + 2], acc[64 + 8 * kk + 3]),
                       pack_bf16(acc[64 + 8 * kk + 4], acc[64 + 8 * kk + 5]), pack_bf16(acc[64 + 8 * kk + 6], acc[64 + 8 * kk + 7]));
            }
        }
        if (w == 1) bar_arrive<5, 256>();
        const float sc = 0.08838834764831845f * 1.4426950408889634f;
#pragma unroll
        for (int u = 0; u < 2; u++) {
            uint32_t af[16][4];
            {
                float o[64], s[64];
                float m0 = -INFINITY, m1 = -INFINITY, l0 = 0.f, l1 = 0.f;
                uint32_t pf[8][4];
#pragma unroll
                for (int i = 0; i < 64; i++) { o[i] = 0.f; s[i] = 0.f; }
#pragma unroll
                for (int i = 0; i < 32; i++) pf[i >> 2][i & 3] = 0u;
#pragma unroll 1
                for (int tt = 0; tt <= 4; tt++) {
                    int vslot = slot;
                    if (tt > 0) {
                        mbar_wait(bars + 8 * slot, ph);
                        if (++slot == lim) { slot = 0; ph ^= 1; }
                    }
                    if (tt < 4) mbar_wait(bars + 8 * slot, ph);
                    if (tid == 0) TS(32 + u * 20 + tt * 4);
                    if (w == 0) bar_sync<5, 256>(); else bar_sync<6, 256>();
                    wg_fence();
                    if (tt > 0) {
                        const uint64_t db = mk_desc(smS + vslot * STAGE_BYTES, 16384, 1024);
#pragma unroll
                        for (int kk = 0; kk < 8; kk++)
                            wgmma_rs_n128_tb(o, pf[kk][0], pf[kk][1], pf[kk][2], pf[kk][3], db + kk * 128, (tt > 1) || (kk != 0));
                        wg_commit();
                    }
                    if (tt < 4) {
                        const uint64_t db = mk_desc(smS + slot * STAGE_BYTES, 16, 1024);
#pragma unroll
                        for (int kk = 0; kk < 8; kk++)
                            wgmma_rs_n128(s, qf[kk][0], qf[kk][1], qf[kk][2], qf[kk][3], db + (kk >> 2) * 1024 + (kk & 3) * 2, kk != 0);
                        wg_commit();
                    }
                    if (w == 0) bar_arrive<6, 256>(); else if (!(u == 1 && tt == 4)) bar_arrive<5, 256>();
                    if (tid == 0) TS(32 + u * 20 + tt * 4 + 1);
                    wg_wait<0>();
                    fence_regs(o);
                    fence_regs(s);
                    if (tid == 0) TS(32 + u * 20 + tt * 4 + 2);
                    if (tt > 0 && lane == 0) mbar_arrive(bars + 8 * (NSTAGE + vslot));
                    if (tt == 4) break;
                    if (lane == 0) mbar_arrive(bars + 8 * (NSTAGE + slot));
                    if (++slot == lim) { slot = 0; ph ^= 1; }
                    float mx0 = s[0], mx1 = s[2];
#pragma unroll
                    for (int j = 0; j < 16; j++) {
                        mx0 = fmaxf(mx0, fmaxf(s[4 * j], s[4 * j + 1]));
                        mx1 = fmaxf(mx1, fmaxf(s[4 * j + 2], s[4 * j + 3]));
                    }
                    mx0 = fmaxf(mx0, __shfl_xor_sync(0xffffffffu, mx0, 1));
                    mx1 = fmaxf(mx1, __shfl_xor_sync(0xffffffffu, mx1, 1));
                    mx0 = fmaxf(mx0, __shfl_xor_sync(0xffffffffu, mx0, 2));
                    mx1 = fmaxf(mx1, __shfl_xor_sync(0xffffffffu, mx1, 2));
                    const float mn0 = fmaxf(m0, mx0), mn1 = fmaxf(m1, mx1);
                    const float al0 = ex2((m0 - mn0) * sc), al1 = ex2((m1 - mn1) * sc);
                    m0 = mn0; m1 = mn1;
                    const float ms0 = mn0 * sc, ms1 = mn1 * sc;
                    float rs0 = 0.f, rs1 = 0.f;
#pragma unroll
                    for (int j = 0; j < 16; j++) {
                        const float p0 = ex2(fmaf(s[4 * j], sc, -ms0)), p1 = ex2(fmaf(s[4 * j + 1], sc, -ms0));
                        const float p2 = ex2(fmaf(s[4 * j + 2], sc, -ms1)), p3 = ex2(fmaf(s[4 * j + 3], sc, -ms1));
                        rs0 += p0 + p1; rs1 += p2 + p3;
                        pf[j >> 1][(j & 1) * 2] = pack_bf16(p0, p1);
                        pf[j >> 1][(j & 1) * 2 + 1] = pack_bf16(p2, p3);
                    }
                    l0 = l0 * al0 + rs0; l1 = l1 * al1 + rs1;
                    if (tt > 0) {
#pragma unroll
                        for (int j = 0; j < 16; j++) { o[4 * j] *= al0; o[4 * j + 1] *= al0; o[4 * j + 2] *= al1; o[4 * j + 3] *= al1; }
                    }
                    if (tid == 0) TS(32 + u * 20 + tt * 4 + 3);
                }
                if (tid == 0) TS(2 + u);
                l0 += __shfl_xor_sync(0xffffffffu, l0, 1);
                l1 += __shfl_xor_sync(0xffffffffu, l1, 1);
                l0 += __shfl_xor_sync(0xffffffffu, l0, 2);
                l1 += __shfl_xor_sync(0xffffffffu, l1, 2);
                const float i0 = 1.f / l0, i1 = 1.f / l1;
                const uint32_t zown = smR + (w ? 3 : 0) * 16384 + t * 16;
#pragma unroll
                for (int kk = 0; kk < 8; kk++) {
                    af[kk][0] = pack_bf16(o[8 * kk + 0] * i0, o[8 * kk + 1] * i0);
                    af[kk][1] = pack_bf16(o[8 * kk + 2] * i1, o[8 * kk + 3] * i1);
                    af[kk][2] = pack_bf16(o[8 * kk + 4] * i0, o[8 * kk + 5] * i0);
                    af[kk][3] = pack_bf16(o[8 * kk + 6] * i1, o[8 * kk + 7] * i1);
                    sts128(zown + kk * 2048, af[kk][0], af[kk][1], af[kk][2], af[kk][3]);
                }
            }
            if (w == 0) bar_arrive<7, 256>(); else bar_arrive<8, 256>();
            lim = 3;
            if (u == 0) {
#pragma unroll
                for (int kk = 0; kk < 8; kk++) lds128(stash + kk * 2048, qf[kk]);
            }
#pragma unroll
            for (int ps = 0; ps < 2; ps++) {
                float acc[64];
                const uint32_t keep = smS + (3 + ps) * STAGE_BYTES + w * 16384 + t * 16;
                if (u == 0) {
#pragma unroll
                    for (int i = 0; i < 64; i++) acc[i] = 0.f;
                } else {
#pragma unroll
                    for (int j = 0; j < 8; j++) {
                        uint32_t r[4];
                        lds128(keep + j * 2048, r);
#pragma unroll
                        for (int i = 0; i < 4; i++) { acc[8 * j + 2 * i] = __uint_as_float(r[i] << 16); acc[8 * j + 2 * i + 1] = __uint_as_float(r[i] & 0xffff0000u); }
                    }
                }
#pragma unroll
                for (int st = 0; st < 4; st++) {
                    if (ps == 0 && st == 2) {
                        if (w == 0) bar_sync<8, 256>(); else bar_sync<7, 256>();
#pragma unroll
                        for (int kk = 0; kk < 8; kk++) lds128(smR + (w ? 0 : 3) * 16384 + kk * 2048 + t * 16, af[8 + kk]);
                    }
                    mbar_wait(bars + 8 * slot, ph);
                    const uint64_t db = mk_desc(smS + slot * STAGE_BYTES + w * 16384, 8192, 1024);
                    wg_fence();
#pragma unroll
                    for (int kk = 0; kk < 4; kk++)
                        wgmma_rs_n128_tb(acc, af[st * 4 + kk][0], af[st * 4 + kk][1], af[st * 4 + kk][2], af[st * 4 + kk][3], db + kk * 128, 1);
                    wg_commit();
                    wg_wait<0>();
                    if (lane == 0) mbar_arrive(bars + 8 * (NSTAGE + slot));
                    if (++slot == 3) { slot = 0; ph ^= 1; }
                }
                fence_regs(acc);
                if (u == 0) {
#pragma unroll
                    for (int j = 0; j < 8; j++)
                        sts128(keep + j * 2048, pack_bf16(acc[8 * j], acc[8 * j + 1]), pack_bf16(acc[8 * j + 2], acc[8 * j + 3]),
                               pack_bf16(acc[8 * j + 4], acc[8 * j + 5]), pack_bf16(acc[8 * j + 6], acc[8 * j + 7]));
                } else {
                    const uint32_t stg = smS + (3 + ps) * STAGE_BYTES + w * 16384 + t * 8;
#pragma unroll
                    for (int j = 0; j < 16; j++) sts64(stg + j * 1024, pack_bf16(acc[4 * j], acc[4 * j + 1]), pack_bf16(acc[4 * j + 2], acc[4 * j + 3]));
                    asm volatile("fence.proxy.async.shared::cta;" ::: "memory");
                    __syncwarp();
                    if (lane == 0) mbar_arrive(bars + 8 * (2 * NSTAGE + w * 5 + ps));
                }
                if (tid == 0) TS(4 + u * 8 + ps);
            }
            {
                float acc[32];
                if (u == 0) {
#pragma unroll
                    for (int i = 0; i < 32; i++) acc[i] = 0.f;
                } else {
#pragma unroll
                    for (int j = 0; j < 4; j++) {
                        uint32_t r[4];
                        lds128(stash + j * 2048, r);
#pragma unroll
                        for (int i = 0; i < 4; i++) { acc[8 * j + 2 * i] = __uint_as_float(r[i] << 16); acc[8 * j + 2 * i + 1] = __uint_as_float(r[i] & 0xffff0000u); }
                    }
                }
                mbar_wait(bars + 8 * slot, ph);
                const uint64_t db = mk_desc(smS + slot * STAGE_BYTES + w * 16384, 8192, 1024);
                wg_fence();
#pragma unroll
                for (int kk = 0; kk < 8; kk++)
                    wgmma_rs_n64_tb(acc, af[kk][0], af[kk][1], af[kk][2], af[kk][3], db + kk * 128, 1);
                wg_commit();
                wg_wait<0>();
                if (lane == 0) mbar_arrive(bars + 8 * (NSTAGE + slot));
                if (++slot == 3) { slot = 0; ph ^= 1; }
                fence_regs(acc);
                if (u == 0) {
#pragma unroll
                    for (int j = 0; j < 4; j++)
                        sts128(stash + j * 2048, pack_bf16(acc[8 * j], acc[8 * j + 1]), pack_bf16(acc[8 * j + 2], acc[8 * j + 3]),
                               pack_bf16(acc[8 * j + 4], acc[8 * j + 5]), pack_bf16(acc[8 * j + 6], acc[8 * j + 7]));
                } else {
                    const uint32_t stg = smR + (1 + w) * 16384 + t * 8;
#pragma unroll
                    for (int j = 0; j < 8; j++) sts64(stg + j * 1024, pack_bf16(acc[4 * j], acc[4 * j + 1]), pack_bf16(acc[4 * j + 2], acc[4 * j + 3]));
                    asm volatile("fence.proxy.async.shared::cta;" ::: "memory");
                    __syncwarp();
                    if (lane == 0) mbar_arrive(bars + 8 * (2 * NSTAGE + w * 5 + 2));
                }
                if (tid == 0) TS(6 + u * 8);
            }
        }
        {
            const int nch = (w == 0) ? 3 : 2;
            if (lane < nch) {
                const int c = (lane < 2) ? (2 * lane + w) : 4;
                const unsigned need = (lane < 2) ? 8u : 16u;
                unsigned* cp = &g_cnt[(grp * 9 + c) * 32 + hp * 4 + (wid & 3)];
                unsigned v, n = 0;
                while (true) {
                    asm volatile("ld.acquire.gpu.global.u32 %0, [%1];" : "=r"(v) : "l"(cp) : "memory");
                    if (v >= need) break;
                    if (++n > (1u << 21)) break;
                }
                *cp = 0;
            }
            __syncwarp();
            if (tid == 0) TS(18);
            __nv_bfloat16* orow = P.out + (size_t)(b * 64 + (t >> 5) * 16 + (lane >> 2)) * (2 * kD) + blk * kD + hp * 8 + (lane & 3) * 2;
            const uint2* src = g_part + ((size_t)(grp * 80 + 2 * w * 8) * 8 + hp) * 128 + t;
            uint2 v[4][8];
#pragma unroll
            for (int k = 0; k < 4; k++)
#pragma unroll
                for (int i = 0; i < 8; i++) v[k][i] = __ldcg(src + (size_t)((k >> 1) * 32 + (k & 1) * 8 + i) * 1024);
            if (w == 0) {
                const uint2* src8 = g_part + ((size_t)(grp * 80 + 64) * 8 + hp) * 128 + t;
                uint2 u[16];
#pragma unroll
                for (int i = 0; i < 16; i++) u[i] = __ldcg(src8 + (size_t)i * 1024);
                float a0 = 0.f, a1 = 0.f, a2 = 0.f, a3 = 0.f;
#pragma unroll
                for (int i = 0; i < 16; i++) {
                    a0 += __uint_as_float(u[i].x << 16); a1 += __uint_as_float(u[i].x & 0xffff0000u);
                    a2 += __uint_as_float(u[i].y << 16); a3 += __uint_as_float(u[i].y & 0xffff0000u);
                }
                *(uint32_t*)(orow + 512) = pack_bf16(a0, a1);
                *(uint32_t*)(orow + 512 + 8 * 2 * kD) = pack_bf16(a2, a3);
            }
#pragma unroll
            for (int k = 0; k < 4; k++) {
                float a0 = 0.f, a1 = 0.f, a2 = 0.f, a3 = 0.f;
#pragma unroll
                for (int i = 0; i < 8; i++) {
                    a0 += __uint_as_float(v[k][i].x << 16); a1 += __uint_as_float(v[k][i].x & 0xffff0000u);
                    a2 += __uint_as_float(v[k][i].y << 16); a3 += __uint_as_float(v[k][i].y & 0xffff0000u);
                }
                *(uint32_t*)(orow + ((k >> 1) * 4 + 2 * w + (k & 1)) * 64) = pack_bf16(a0, a1);
                *(uint32_t*)(orow + ((k >> 1) * 4 + 2 * w + (k & 1)) * 64 + 8 * 2 * kD) = pack_bf16(a2, a3);
            }
            if (tid == 0) TS(19);
        }
    }
}

typedef CUresult (*EncodeFn)(CUtensorMap*, CUtensorMapDataType, cuuint32_t, void*, const cuuint64_t*, const cuuint64_t*,
                             const cuuint32_t*, const cuuint32_t*, CUtensorMapInterleave, CUtensorMapSwizzle,
                             CUtensorMapL2promotion, CUtensorMapFloatOOBfill);

void make_map(EncodeFn fn, CUtensorMap* m, const void* ptr, uint64_t cols, uint64_t rows, uint32_t box_rows) {
    cuuint64_t dims[2] = {cols, rows};
    cuuint64_t strides[1] = {cols * 2};
    cuuint32_t box[2] = {64, box_rows};
    cuuint32_t es[2] = {1, 1};
    fn(m, CU_TENSOR_MAP_DATA_TYPE_BFLOAT16, 2, const_cast<void*>(ptr), dims, strides, box, es, CU_TENSOR_MAP_INTERLEAVE_NONE,
       CU_TENSOR_MAP_SWIZZLE_128B, CU_TENSOR_MAP_L2_PROMOTION_L2_256B, CU_TENSOR_MAP_FLOAT_OOB_FILL_NONE);
}

void make_map3(EncodeFn fn, CUtensorMap* m, const void* ptr, uint64_t cols, uint64_t rows, uint32_t box_rows, uint32_t box_groups) {
    cuuint64_t dims[3] = {64, rows, cols / 64};
    cuuint64_t strides[2] = {cols * 2, 128};
    cuuint32_t box[3] = {64, box_rows, box_groups};
    cuuint32_t es[3] = {1, 1, 1};
    fn(m, CU_TENSOR_MAP_DATA_TYPE_BFLOAT16, 3, const_cast<void*>(ptr), dims, strides, box, es, CU_TENSOR_MAP_INTERLEAVE_NONE,
       CU_TENSOR_MAP_SWIZZLE_128B, CU_TENSOR_MAP_L2_PROMOTION_L2_256B, CU_TENSOR_MAP_FLOAT_OOB_FILL_NONE);
}

}

extern "C" void kernel_launch(void* const* d_in, const int* in_sizes, int n_in, void* d_out, int out_size) {
    static EncodeFn enc = nullptr;
    if (!enc) {
        void* fn = nullptr;
        cudaDriverEntryPointQueryResult st;
        cudaGetDriverEntryPoint("cuTensorMapEncodeTiled", &fn, cudaEnableDefault, &st);
        enc = (EncodeFn)fn;
        cudaFuncSetAttribute(fused_gqa_kernel, cudaFuncAttributeMaxDynamicSharedMemorySize, SMEM_BYTES);
    }
    Params P;
    for (int blk = 0; blk < 2; blk++) {
        const void* x = d_in[blk * 5 + 0];
        const void* k = d_in[blk * 5 + 1];
        const void* v = d_in[blk * 5 + 2];
        const void* wq = d_in[blk * 5 + 3];
        const void* wo = d_in[blk * 5 + 4];
        make_map(enc, &P.x[blk], x, kD, kB * kSq, 64);
        make_map3(enc, &P.wq[blk], wq, kHq * kDh, kD, 32, 2);
        make_map3(enc, &P.k[blk], k, kDh, (uint64_t)kB * kHkv * kSk, 128, 2);
        make_map3(enc, &P.v[blk], v, kDh, (uint64_t)kB * kHkv * kSk, 128, 2);
        make_map3(enc, &P.wo[blk], wo, kD, kHq * kDh, 64, 2);
        make_map(enc, &P.wo8[blk], wo, kD, kHq * kDh, 128);
        P.wqp[blk] = (const __nv_bfloat16*)wq;
        P.kp[blk] = (const __nv_bfloat16*)k;
        P.vp[blk] = (const __nv_bfloat16*)v;
        P.wop[blk] = (const __nv_bfloat16*)wo;
    }
    P.out = (__nv_bfloat16*)d_out;
    fused_gqa_kernel<<<128, 384, SMEM_BYTES>>>(P);
}
```

```cpp
#include <cuda_runtime.h>
#include <cuda_bf16.h>
#include <cuda.h>
#include <stdint.h>

namespace {

constexpr int kB = 8, kSq = 64, kD = 576, kHq = 32, kHkv = 16, kSk = 512, kDh = 128;
constexpr int NSTAGE = 5;
constexpr int STAGE_BYTES = 32768;
constexpr int R_BYTES = 65536;
constexpr int SMEM_BYTES = R_BYTES + NSTAGE * STAGE_BYTES + 1024   + 256  ;
constexpr int N_WQ = 18;
#define PF_DIST_V 6
#define OP_WAIT0 1
#define QP_WAIT0 1
#define PF_POS1 9
#define PF_WQ 0
#define PF_SLEEP 1000
constexpr int PF_DIST = PF_DIST_V;

struct __align__(64) Params {
    CUtensorMap x[2], wq[2], k[2], v[2], wo[2], wo8[2];
    const __nv_bfloat16* wqp[2];
    const __nv_bfloat16* kp[2];
    const __nv_bfloat16* vp[2];
    const __nv_bfloat16* wop[2];
    __nv_bfloat16* out;
};

__device__ uint2 g_part[16 * 80 * 8 * 128];
__device__ unsigned int g_cnt[16 * 9 * 32];
#define TS(k) do {} while (0)

__device__ __forceinline__ uint32_t smem_u32(const void* p) { return (uint32_t)__cvta_generic_to_shared(p); }
__device__ __forceinline__ void mbar_init(uint32_t bar, int cnt) {
    asm volatile("mbarrier.init.shared::cta.b64 [%0], %1;" ::"r"(bar), "r"(cnt));
}
__device__ __forceinline__ void mbar_expect_tx(uint32_t bar, uint32_t bytes) {
    asm volatile("mbarrier.arrive.expect_tx.shared::cta.b64 _, [%0], %1;" ::"r"(bar), "r"(bytes) : "memory");
}
__device__ __forceinline__ void mbar_arrive(uint32_t bar) {
    asm volatile("mbarrier.arrive.shared::cta.b64 _, [%0];" ::"r"(bar) : "memory");
}
__device__ __forceinline__ bool mbar_try(uint32_t bar, uint32_t parity) {
    uint32_t ok;
    asm volatile("{\n.reg .pred p;\nmbarrier.try_wait.parity.shared::cta.b64 p, [%1], %2;\nselp.u32 %0, 1, 0, p;\n}\n"
                 : "=r"(ok) : "r"(bar), "r"(parity) : "memory");
    return ok != 0;
}
__device__ __forceinline__ void mbar_wait(uint32_t bar, uint32_t parity) {
    if (mbar_try(bar, parity)) return;
    uint32_t n = 0;
    while (!mbar_try(bar, parity)) {
        if (++n > (1u << 20)) break;
    }
}
__device__ __forceinline__ void tma_2d(uint32_t dst, const CUtensorMap* tm, int c0, int c1, uint32_t bar) {
    asm volatile("cp.async.bulk.tensor.2d.shared::cluster.global.mbarrier::complete_tx::bytes [%0], [%1, {%3, %4}], [%2];"
                 ::"r"(dst), "l"(tm), "r"(bar), "r"(c0), "r"(c1) : "memory");
}
__device__ __forceinline__ void tma_3d(uint32_t dst, const CUtensorMap* tm, int c0, int c1, int c2, uint32_t bar) {
    asm volatile("cp.async.bulk.tensor.3d.shared::cluster.global.mbarrier::complete_tx::bytes [%0], [%1, {%3, %4, %5}], [%2];"
                 ::"r"(dst), "l"(tm), "r"(bar), "r"(c0), "r"(c1), "r"(c2) : "memory");
}
__device__ __forceinline__ void l2_prefetch(const void* p, uint32_t bytes) {
    asm volatile("cp.async.bulk.prefetch.L2.global [%0], %1;" ::"l"(p), "r"(bytes) : "memory");
}
__device__ __forceinline__ uint32_t l2_touch(const void* p) {
    uint32_t v;
    asm volatile("ld.global.L2::256B.b32 %0, [%1];" : "=r"(v) : "l"(p) : "memory");
    return v;
}
__device__ __forceinline__ void wg_fence() { asm volatile("wgmma.fence.sync.aligned;" ::: "memory"); }
__device__ __forceinline__ void wg_commit() { asm volatile("wgmma.commit_group.sync.aligned;" ::: "memory"); }
template <int N> __device__ __forceinline__ void wg_wait() { asm volatile("wgmma.wait_group.sync.aligned %0;" ::"n"(N) : "memory"); }
template <int N> __device__ __forceinline__ void fence_regs(float (&d)[N]) {
#pragma unroll
    for (int i = 0; i < N; i++) asm volatile("" : "+f"(d[i])::"memory");
}
__device__ __forceinline__ uint64_t mk_desc(uint32_t addr, uint32_t lbo, uint32_t sbo) {
    return (uint64_t)((addr & 0x3FFFF) >> 4) | ((uint64_t)(lbo >> 4) << 16) | ((uint64_t)(sbo >> 4) << 32) | (1ull << 62);
}
__device__ __forceinline__ uint32_t pack_bf16(float a, float b) {
    uint32_t r;
    asm("cvt.rn.bf16x2.f32 %0, %1, %2;" : "=r"(r) : "f"(b), "f"(a));
    return r;
}
__device__ __forceinline__ float ex2(float x) {
    float y;
    asm("ex2.approx.ftz.f32 %0, %1;" : "=f"(y) : "f"(x));
    return y;
}
template <int ID, int N> __device__ __forceinline__ void bar_sync() { asm volatile("bar.sync %0, %1;" ::"n"(ID), "n"(N) : "memory"); }
template <int ID, int N> __device__ __forceinline__ void bar_arrive() { asm volatile("bar.arrive %0, %1;" ::"n"(ID), "n"(N) : "memory"); }
__device__ __forceinline__ void sts128(uint32_t addr, uint32_t a, uint32_t b, uint32_t c, uint32_t d) {
    asm volatile("st.shared.v4.b32 [%0], {%1,%2,%3,%4};" ::"r"(addr), "r"(a), "r"(b), "r"(c), "r"(d) : "memory");
}
__device__ __forceinline__ void sts64(uint32_t addr, uint32_t a, uint32_t b) {
    asm volatile("st.shared.v2.b32 [%0], {%1,%2};" ::"r"(addr), "r"(a), "r"(b) : "memory");
}
__device__ __forceinline__ void bulk_store(void* dst, uint32_t src, uint32_t bytes) {
    asm volatile("cp.async.bulk.global.shared::cta.bulk_group [%0], [%1], %2;" ::"l"(dst), "r"(src), "r"(bytes) : "memory");
}
__device__ __forceinline__ void lds128(uint32_t addr, uint32_t (&r)[4]) {
    asm volatile("ld.shared.v4.b32 {%0,%1,%2,%3}, [%4];" : "=r"(r[0]), "=r"(r[1]), "=r"(r[2]), "=r"(r[3]) : "r"(addr) : "memory");
}

__device__ __forceinline__ void wgmma_ss_n256_tb(float (&d)[128], uint64_t da, uint64_t db, int sd) {
    asm volatile("{\n.reg .pred p;\nsetp.ne.b32 p, %130, 0;\n"
        "wgmma.mma_async.sync.aligned.m64n256k16.f32.bf16.bf16 "
        "{%0, %1, %2, %3, %4, %5, %6, %7, %8, %9, %10, %11, %12, %13, %14, %15, %16, %17, %18, %19, %20, %21, %22, %23, %24, %25, %26, %27, %28, %29, %30, %31, %32, %33, %34, %35, %36, %37, %38, %39, %40, %41, %42, %43, %44, %45, %46, %47, %48, %49, %50, %51, %52, %53, %54, %55, %56, %57, %58, %59, %60, %61, %62, %63, %64, %65, %66, %67, %68, %69, %70, %71, %72, %73, %74, %75, %76, %77, %78, %79, %80, %81, %82, %83, %84, %85, %86, %87, %88, %89, %90, %91, %92, %93, %94, %95, %96, %97, %98, %99, %100, %101, %102, %103, %104, %105, %106, %107, %108, %109, %110, %111, %112, %113, %114, %115, %116, %117, %118, %119, %120, %121, %122, %123, %124, %125, %126, %127}, "
        "%128, %129, p, 1, 1, 0, 1;\n}\n"
        : "+f"(d[0]), "+f"(d[1]), "+f"(d[2]), "+f"(d[3]), "+f"(d[4]), "+f"(d[5]), "+f"(d[6]), "+f"(d[7]), "+f"(d[8]), "+f"(d[9]), "+f"(d[10]), "+f"(d[11]), "+f"(d[12]), "+f"(d[13]), "+f"(d[14]), "+f"(d[15]), "+f"(d[16]), "+f"(d[17]), "+f"(d[18]), "+f"(d[19]), "+f"(d[20]), "+f"(d[21]), "+f"(d[22]), "+f"(d[23]), "+f"(d[24]), "+f"(d[25]), "+f"(d[26]), "+f"(d[27]), "+f"(d[28]), "+f"(d[29]), "+f"(d[30]), "+f"(d[31]), "+f"(d[32]), "+f"(d[33]), "+f"(d[34]), "+f"(d[35]), "+f"(d[36]), "+f"(d[37]), "+f"(d[38]), "+f"(d[39]), "+f"(d[40]), "+f"(d[41]), "+f"(d[42]), "+f"(d[43]), "+f"(d[44]), "+f"(d[45]), "+f"(d[46]), "+f"(d[47]), "+f"(d[48]), "+f"(d[49]), "+f"(d[50]), "+f"(d[51]), "+f"(d[52]), "+f"(d[53]), "+f"(d[54]), "+f"(d[55]), "+f"(d[56]), "+f"(d[57]), "+f"(d[58]), "+f"(d[59]), "+f"(d[60]), "+f"(d[61]), "+f"(d[62]), "+f"(d[63]), "+f"(d[64]), "+f"(d[65]), "+f"(d[66]), "+f"(d[67]), "+f"(d[68]), "+f"(d[69]), "+f"(d[70]), "+f"(d[71]), "+f"(d[72]), "+f"(d[73]), "+f"(d[74]), "+f"(d[75]), "+f"(d[76]), "+f"(d[77]), "+f"(d[78]), "+f"(d[79]), "+f"(d[80]), "+f"(d[81]), "+f"(d[82]), "+f"(d[83]), "+f"(d[84]), "+f"(d[85]), "+f"(d[86]), "+f"(d[87]), "+f"(d[88]), "+f"(d[89]), "+f"(d[90]), "+f"(d[91]), "+f"(d[92]), "+f"(d[93]), "+f"(d[94]), "+f"(d[95]), "+f"(d[96]), "+f"(d[97]), "+f"(d[98]), "+f"(d[99]), "+f"(d[100]), "+f"(d[101]), "+f"(d[102]), "+f"(d[103]), "+f"(d[104]), "+f"(d[105]), "+f"(d[106]), "+f"(d[107]), "+f"(d[108]), "+f"(d[109]), "+f"(d[110]), "+f"(d[111]), "+f"(d[112]), "+f"(d[113]), "+f"(d[114]), "+f"(d[115]), "+f"(d[116]), "+f"(d[117]), "+f"(d[118]), "+f"(d[119]), "+f"(d[120]), "+f"(d[121]), "+f"(d[122]), "+f"(d[123]), "+f"(d[124]), "+f"(d[125]), "+f"(d[126]), "+f"(d[127])
        : "l"(da), "l"(db), "r"(sd));
}
__device__ __forceinline__ void wgmma_rs_n128(float (&d)[64], uint32_t a0, uint32_t a1, uint32_t a2, uint32_t a3, uint64_t db, int sd) {
    asm volatile("{\n.reg .pred p;\nsetp.ne.b32 p, %69, 0;\n"
        "wgmma.mma_async.sync.aligned.m64n128k16.f32.bf16.bf16 "
        "{%0, %1, %2, %3, %4, %5, %6, %7, %8, %9, %10, %11, %12, %13, %14, %15, %16, %17, %18, %19, %20, %21, %22, %23, %24, %25, %26, %27, %28, %29, %30, %31, %32, %33, %34, %35, %36, %37, %38, %39, %40, %41, %42, %43, %44, %45, %46, %47, %48, %49, %50, %51, %52, %53, %54, %55, %56, %57, %58, %59, %60, %61, %62, %63}, "
        "{%64, %65, %66, %67}, %68, p, 1, 1, 0;\n}\n"
        : "+f"(d[0]), "+f"(d[1]), "+f"(d[2]), "+f"(d[3]), "+f"(d[4]), "+f"(d[5]), "+f"(d[6]), "+f"(d[7]), "+f"(d[8]), "+f"(d[9]), "+f"(d[10]), "+f"(d[11]), "+f"(d[12]), "+f"(d[13]), "+f"(d[14]), "+f"(d[15]), "+f"(d[16]), "+f"(d[17]), "+f"(d[18]), "+f"(d[19]), "+f"(d[20]), "+f"(d[21]), "+f"(d[22]), "+f"(d[23]), "+f"(d[24]), "+f"(d[25]), "+f"(d[26]), "+f"(d[27]), "+f"(d[28]), "+f"(d[29]), "+f"(d[30]), "+f"(d[31]), "+f"(d[32]), "+f"(d[33]), "+f"(d[34]), "+f"(d[35]), "+f"(d[36]), "+f"(d[37]), "+f"(d[38]), "+f"(d[39]), "+f"(d[40]), "+f"(d[41]), "+f"(d[42]), "+f"(d[43]), "+f"(d[44]), "+f"(d[45]), "+f"(d[46]), "+f"(d[47]), "+f"(d[48]), "+f"(d[49]), "+f"(d[50]), "+f"(d[51]), "+f"(d[52]), "+f"(d[53]), "+f"(d[54]), "+f"(d[55]), "+f"(d[56]), "+f"(d[57]), "+f"(d[58]), "+f"(d[59]), "+f"(d[60]), "+f"(d[61]), "+f"(d[62]), "+f"(d[63])
        : "r"(a0), "r"(a1), "r"(a2), "r"(a3), "l"(db), "r"(sd));
}
__device__ __forceinline__ void wgmma_rs_n128_tb(float (&d)[64], uint32_t a0, uint32_t a1, uint32_t a2, uint32_t a3, uint64_t db, int sd) {
    asm volatile("{\n.reg .pred p;\nsetp.ne.b32 p, %69, 0;\n"
        "wgmma.mma_async.sync.aligned.m64n128k16.f32.bf16.bf16 "
        "{%0, %1, %2, %3, %4, %5, %6, %7, %8, %9, %10, %11, %12, %13, %14, %15, %16, %17, %18, %19, %20, %21, %22, %23, %24, %25, %26, %27, %28, %29, %30, %31, %32, %33, %34, %35, %36, %37, %38, %39, %40, %41, %42, %43, %44, %45, %46, %47, %48, %49, %50, %51, %52, %53, %54, %55, %56, %57, %58, %59, %60, %61, %62, %63}, "
        "{%64, %65, %66, %67}, %68, p, 1, 1, 1;\n}\n"
        : "+f"(d[0]), "+f"(d[1]), "+f"(d[2]), "+f"(d[3]), "+f"(d[4]), "+f"(d[5]), "+f"(d[6]), "+f"(d[7]), "+f"(d[8]), "+f"(d[9]), "+f"(d[10]), "+f"(d[11]), "+f"(d[12]), "+f"(d[13]), "+f"(d[14]), "+f"(d[15]), "+f"(d[16]), "+f"(d[17]), "+f"(d[18]), "+f"(d[19]), "+f"(d[20]), "+f"(d[21]), "+f"(d[22]), "+f"(d[23]), "+f"(d[24]), "+f"(d[25]), "+f"(d[26]), "+f"(d[27]), "+f"(d[28]), "+f"(d[29]), "+f"(d[30]), "+f"(d[31]), "+f"(d[32]), "+f"(d[33]), "+f"(d[34]), "+f"(d[35]), "+f"(d[36]), "+f"(d[37]), "+f"(d[38]), "+f"(d[39]), "+f"(d[40]), "+f"(d[41]), "+f"(d[42]), "+f"(d[43]), "+f"(d[44]), "+f"(d[45]), "+f"(d[46]), "+f"(d[47]), "+f"(d[48]), "+f"(d[49]), "+f"(d[50]), "+f"(d[51]), "+f"(d[52]), "+f"(d[53]), "+f"(d[54]), "+f"(d[55]), "+f"(d[56]), "+f"(d[57]), "+f"(d[58]), "+f"(d[59]), "+f"(d[60]), "+f"(d[61]), "+f"(d[62]), "+f"(d[63])
        : "r"(a0), "r"(a1), "r"(a2), "r"(a3), "l"(db), "r"(sd));
}
__device__ __forceinline__ void wgmma_rs_n64_tb(float (&d)[32], uint32_t a0, uint32_t a1, uint32_t a2, uint32_t a3, uint64_t db, int sd) {
    asm volatile("{\n.reg .pred p;\nsetp.ne.b32 p, %37, 0;\n"
        "wgmma.mma_async.sync.aligned.m64n64k16.f32.bf16.bf16 "
        "{%0, %1, %2, %3, %4, %5, %6, %7, %8, %9, %10, %11, %12, %13, %14, %15, %16, %17, %18, %19, %20, %21, %22, %23, %24, %25, %26, %27, %28, %29, %30, %31}, "
        "{%32, %33, %34, %35}, %36, p, 1, 1, 1;\n}\n"
        : "+f"(d[0]), "+f"(d[1]), "+f"(d[2]), "+f"(d[3]), "+f"(d[4]), "+f"(d[5]), "+f"(d[6]), "+f"(d[7]), "+f"(d[8]), "+f"(d[9]), "+f"(d[10]), "+f"(d[11]), "+f"(d[12]), "+f"(d[13]), "+f"(d[14]), "+f"(d[15]), "+f"(d[16]), "+f"(d[17]), "+f"(d[18]), "+f"(d[19]), "+f"(d[20]), "+f"(d[21]), "+f"(d[22]), "+f"(d[23]), "+f"(d[24]), "+f"(d[25]), "+f"(d[26]), "+f"(d[27]), "+f"(d[28]), "+f"(d[29]), "+f"(d[30]), "+f"(d[31])
        : "r"(a0), "r"(a1), "r"(a2), "r"(a3), "l"(db), "r"(sd));
}

__global__ void __launch_bounds__(384, 1) fused_gqa_kernel(const __grid_constant__ Params P) {
    extern __shared__ uint8_t smem_raw[];
    const uint32_t base = (smem_u32(smem_raw) + 1023u) & ~1023u;
    const uint32_t smR = base;
    const uint32_t smS = base + R_BYTES;
    const uint32_t bars = smS + NSTAGE * STAGE_BYTES;
    const uint32_t prog = bars + 8 * (2 * NSTAGE + 10);
    const int tid = threadIdx.x;
    const int wid = __shfl_sync(0xffffffffu, tid >> 5, 0);
    const int lane = tid & 31;

    const int cta = blockIdx.x;
    const int blk = cta >> 6;
    const int hp = (cta >> 3) & 7;
    const int b = cta & 7;
    const int grp = blk * 8 + b;

    if (tid == 0) {
        TS(0);
        for (int i = 0; i < NSTAGE; i++) {
            mbar_init(bars + 8 * i, 1);
            mbar_init(bars + 8 * (NSTAGE + i), 8);
        }
        for (int i = 0; i < 10; i++) mbar_init(bars + 8 * (2 * NSTAGE + i), 4);
        asm volatile("st.volatile.shared.u32 [%0], %1;" ::"r"(prog), "r"(0) : "memory");
        asm volatile("fence.mbarrier_init.release.cluster;" ::: "memory");
        asm volatile("fence.proxy.async.shared::cta;" ::: "memory");
    }
    __syncthreads();

    if (wid >= 8) {
        asm volatile("setmaxnreg.dec.sync.aligned.u32 40;");
        auto publish = [&](int hw, int k) {
            mbar_wait(bars + 8 * (2 * NSTAGE + hw * 5 + k), 0);
            const int c = (k < 2) ? (2 * k + hw) : 4;
            if (lane == 0) {
                if (k < 2) {
                    uint2* dst = g_part + (size_t)(grp * 80 + (4 * k + 2 * hw) * 8 + hp) * 1024;
                    const uint32_t src = smS + (3 + k) * STAGE_BYTES + hw * 16384;
                    bulk_store(dst, src, 8192);
                    bulk_store(dst + 8192, src + 8192, 8192);
                } else {
                    bulk_store(g_part + (size_t)(grp * 80 + 64 + hp * 2 + hw) * 1024, smR + (1 + hw) * 16384, 8192);
                }
                asm volatile("cp.async.bulk.commit_group;" ::: "memory");
                asm volatile("cp.async.bulk.wait_group 0;" ::: "memory");
                asm volatile("fence.acq_rel.gpu;" ::: "memory");
            }
            __syncwarp();
            asm volatile("red.relaxed.gpu.global.add.u32 [%0], 1;" ::"l"(&g_cnt[(grp * 9 + c) * 32 + lane]) : "memory");
        };
        if (wid == 8) {
            if (lane == 0) {
                int slot = 0, ph = 1;
                for (int s = 0; s < N_WQ; s++) {
                    const uint32_t fb = bars + 8 * slot;
                    mbar_wait(bars + 8 * (NSTAGE + slot), ph);
                    const uint32_t dst = smS + slot * STAGE_BYTES;
                    mbar_expect_tx(fb, (s & 1) ? STAGE_BYTES : STAGE_BYTES + 8192);
                    if (!(s & 1)) tma_2d(smR + ((s >> 1) & 7) * 8192, &P.x[blk], (s >> 1) * 64, b * 64, fb);
#pragma unroll
                    for (int p = 0; p < 4; p++) {
                        const int w = p >> 1, j = p & 1;
                        tma_3d(dst + p * 8192, &P.wq[blk], 0, s * 32, hp * 8 + j * 4 + w * 2, fb);
                    }
                    if (++slot == NSTAGE) { slot = 0; ph ^= 1; }
                }
                int lim = NSTAGE;
                for (int i = 0; i < 34; i++) {
                    const int u = (i >= 17), r = i - 17 * u;
                    const uint32_t fb = bars + 8 * slot;
                    mbar_wait(bars + 8 * (NSTAGE + slot), ph);
                    const uint32_t dst = smS + slot * STAGE_BYTES;
                    mbar_expect_tx(fb, STAGE_BYTES);
                    if (r < 8) {
                        const int row = (b * kHkv + hp * 2 + u) * kSk + (r >> 1) * 128;
                        tma_3d(dst, (r & 1) ? &P.v[blk] : &P.k[blk], 0, row, 0, fb);
                    } else {
                        const int q = r - 8, row = hp * 512 + u * 256;
                        if (q < 8) {
                            tma_3d(dst, &P.wo[blk], 0, row + (q & 3) * 64, (q >> 2) * 4, fb);
                            tma_3d(dst + 16384, &P.wo[blk], 0, row + ((q & 3) ^ 2) * 64, (q >> 2) * 4 + 2, fb);
                        } else {
                            tma_2d(dst, &P.wo8[blk], 512, row, fb);
                            tma_2d(dst + 16384, &P.wo8[blk], 512, row + 128, fb);
                        }
                    }
                    asm volatile("st.volatile.shared.u32 [%0], %1;" ::"r"(prog), "r"(i + 1) : "memory");
                    if (i == 7) lim = 3;
                    if (++slot == lim) { slot = 0; ph ^= 1; }
                }
            }
            __syncwarp();
            publish(1, 1);
        } else if (wid == 11) {
            if (PF_DIST > 0) {
                uint32_t sink = 0;
                mbar_wait(bars, 0);
                if (PF_WQ) {
                    const char* wqs = (const char*)(P.wqp[blk] + hp * 512) + (size_t)(160 + b * 52) * 8192;
#pragma unroll
                    for (int h = 0; h < 2; h++) {
#pragma unroll
                        for (int j = 0; j < 4; j++) {
                            const int e = (h * 4 + j) * 32 + lane;
                            if (e < 208) sink |= l2_touch(wqs + (size_t)(e >> 2) * 8192 + (e & 3) * 256);
                        }
                        if (sink == 0x9E3779B9u) asm volatile("st.volatile.shared.u32 [%0], %1;" ::"r"(prog + 4), "r"(sink) : "memory");
                    }
                }
                const char* kbase = (const char*)(P.kp[blk] + (size_t)(b * kHkv + hp * 2) * kSk * kDh);
                const char* vbase = (const char*)(P.vp[blk] + (size_t)(b * kHkv + hp * 2) * kSk * kDh);
                const char* wos = (const char*)(P.wop[blk] + (size_t)hp * 512 * kD) + (size_t)b * 36864;
                for (int i = 0; i < 18; i++) {
                    const int u = (i >= 9), r = i - 9 * u;
                    const int pos = u ? (PF_POS1 + r) : r;
                    if (pos >= PF_DIST) {
                        uint32_t pr, n = 0;
                        while (true) {
                            asm volatile("ld.volatile.shared.u32 %0, [%1];" : "=r"(pr) : "r"(prog) : "memory");
                            const int prk = ((int)pr <= 8) ? (int)pr : (((int)pr <= 17) ? 8 + (((int)pr - 8) * (PF_POS1 - 8)) / 9 : (int)pr - 17 + PF_POS1);
                            if (prk + PF_DIST >= pos) break;
                            if (++n > (1u << 22)) break;
                            __nanosleep(100);
                        }
                    }
                    if (r < 8) {
                        const char* p = ((r & 1) ? vbase : kbase) + (size_t)(u * 4 + (r >> 1)) * 32768 + lane * 256;
#pragma unroll
                        for (int j = 0; j < 4; j++) sink |= l2_touch(p + j * 8192);
                    } else {
                        const char* p = wos + (size_t)u * 294912 + lane * 256;
#pragma unroll
                        for (int j = 0; j < 5; j++) if (j * 32 + lane < 144) sink |= l2_touch(p + j * 8192);
                    }
                    if (sink == 0x9E3779B9u) asm volatile("st.volatile.shared.u32 [%0], %1;" ::"r"(prog + 4), "r"(sink) : "memory");
                }
            }
            publish(0, 1);
        } else {
            const int hw = wid - 9;
            publish(hw, 0);
            publish(hw, 2);
        }
    } else {
        asm volatile("setmaxnreg.inc.sync.aligned.u32 232;");
        const int w = wid >> 2;
        const int t = tid & 127;
        int slot = 0, ph = 0, lim = NSTAGE;
        uint32_t qf[8][4];
        const uint32_t stash = smR + (1 + w) * 16384 + t * 16;
        {
            float acc[128];
            int pslot = 0;
            for (int s = 0; s < N_WQ; s++) {
                mbar_wait(bars + 8 * slot, ph);
                if (tid == 0 && s == 0) TS(20);
                if (tid == 0 && s == 5) TS(21);
                if (tid == 0 && s == 10) TS(22);
                const uint64_t da = mk_desc(smR + ((s >> 1) & 7) * 8192 + (s & 1) * 64, 16, 1024);
                const uint64_t db = mk_desc(smS + slot * STAGE_BYTES + w * 16384, 4096, 1024);
                wg_fence();
                wgmma_ss_n256_tb(acc, da, db, s != 0);
                wgmma_ss_n256_tb(acc, da + 2, db + 128, 1);
                wg_commit();
                wg_wait<0>();
                if (lane == 0) mbar_arrive(bars + 8 * (NSTAGE + slot));
                pslot = slot;
                if (++slot == NSTAGE) { slot = 0; ph ^= 1; }
            }
            fence_regs(acc);
            if (tid == 0) TS(1);
#pragma unroll
            for (int kk = 0; kk < 8; kk++) {
#pragma unroll
                for (int i = 0; i < 4; i++) qf[kk][i] = pack_bf16(acc[8 * kk + 2 * i], acc[8 * kk + 2 * i + 1]);
                sts128(stash + kk * 2048,
                       pack_bf16(acc[64 + 8 * kk + 0], acc[64 + 8 * kk + 1]), pack_bf16(acc[64 + 8 * kk + 2], acc[64 + 8 * kk + 3]),
                       pack_bf16(acc[64 + 8 * kk + 4], acc[64 + 8 * kk + 5]), pack_bf16(acc[64 + 8 * kk + 6], acc[64 + 8 * kk + 7]));
            }
        }
        if (w == 1) bar_arrive<5, 256>();
        const float sc = 0.08838834764831845f * 1.4426950408889634f;
#pragma unroll
        for (int u = 0; u < 2; u++) {
            uint32_t af[16][4];
            {
                float o[64], s[64];
                float m0 = -INFINITY, m1 = -INFINITY, l0 = 0.f, l1 = 0.f;
                uint32_t pf[8][4];
#pragma unroll
                for (int i = 0; i < 64; i++) { o[i] = 0.f; s[i] = 0.f; }
#pragma unroll
                for (int i = 0; i < 32; i++) pf[i >> 2][i & 3] = 0u;
#pragma unroll 1
                for (int tt = 0; tt <= 4; tt++) {
                    int vslot = slot;
                    if (tt > 0) {
                        mbar_wait(bars + 8 * slot, ph);
                        if (++slot == lim) { slot = 0; ph ^= 1; }
                    }
                    if (tt < 4) mbar_wait(bars + 8 * slot, ph);
                    if (tid == 0) TS(32 + u * 20 + tt * 4);
                    if (w == 0) bar_sync<5, 256>(); else bar_sync<6, 256>();
                    wg_fence();
                    if (tt > 0) {
                        const uint64_t db = mk_desc(smS + vslot * STAGE_BYTES, 16384, 1024);
#pragma unroll
                        for (int kk = 0; kk < 8; kk++)
                            wgmma_rs_n128_tb(o, pf[kk][0], pf[kk][1], pf[kk][2], pf[kk][3], db + kk * 128, (tt > 1) || (kk != 0));
                        wg_commit();
                    }
                    if (tt < 4) {
                        const uint64_t db = mk_desc(smS + slot * STAGE_BYTES, 16, 1024);
#pragma unroll
                        for (int kk = 0; kk < 8; kk++)
                            wgmma_rs_n128(s, qf[kk][0], qf[kk][1], qf[kk][2], qf[kk][3], db + (kk >> 2) * 1024 + (kk & 3) * 2, kk != 0);
                        wg_commit();
                    }
                    if (w == 0) bar_arrive<6, 256>(); else if (!(u == 1 && tt == 4)) bar_arrive<5, 256>();
                    if (tid == 0) TS(32 + u * 20 + tt * 4 + 1);
                    wg_wait<0>();
                    fence_regs(o);
                    fence_regs(s);
                    if (tid == 0) TS(32 + u * 20 + tt * 4 + 2);
                    if (tt > 0 && lane == 0) mbar_arrive(bars + 8 * (NSTAGE + vslot));
                    if (tt == 4) break;
                    if (lane == 0) mbar_arrive(bars + 8 * (NSTAGE + slot));
                    if (++slot == lim) { slot = 0; ph ^= 1; }
                    float mx0 = s[0], mx1 = s[2];
#pragma unroll
                    for (int j = 0; j < 16; j++) {
                        mx0 = fmaxf(mx0, fmaxf(s[4 * j], s[4 * j + 1]));
                        mx1 = fmaxf(mx1, fmaxf(s[4 * j + 2], s[4 * j + 3]));
                    }
                    mx0 = fmaxf(mx0, __shfl_xor_sync(0xffffffffu, mx0, 1));
                    mx1 = fmaxf(mx1, __shfl_xor_sync(0xffffffffu, mx1, 1));
                    mx0 = fmaxf(mx0, __shfl_xor_sync(0xffffffffu, mx0, 2));
                    mx1 = fmaxf(mx1, __shfl_xor_sync(0xffffffffu, mx1, 2));
                    const float mn0 = fmaxf(m0, mx0), mn1 = fmaxf(m1, mx1);
                    const float al0 = ex2((m0 - mn0) * sc), al1 = ex2((m1 - mn1) * sc);
                    m0 = mn0; m1 = mn1;
                    const float ms0 = mn0 * sc, ms1 = mn1 * sc;
                    float rs0 = 0.f, rs1 = 0.f;
#pragma unroll
                    for (int j = 0; j < 16; j++) {
                        const float p0 = ex2(fmaf(s[4 * j], sc, -ms0)), p1 = ex2(fmaf(s[4 * j + 1], sc, -ms0));
                        const float p2 = ex2(fmaf(s[4 * j + 2], sc, -ms1)), p3 = ex2(fmaf(s[4 * j + 3], sc, -ms1));
                        rs0 += p0 + p1; rs1 += p2 + p3;
                        pf[j >> 1][(j & 1) * 2] = pack_bf16(p0, p1);
                        pf[j >> 1][(j & 1) * 2 + 1] = pack_bf16(p2, p3);
                    }
                    l0 = l0 * al0 + rs0; l1 = l1 * al1 + rs1;
                    if (tt > 0) {
#pragma unroll
                        for (int j = 0; j < 16; j++) { o[4 * j] *= al0; o[4 * j + 1] *= al0; o[4 * j + 2] *= al1; o[4 * j + 3] *= al1; }
                    }
                    if (tid == 0) TS(32 + u * 20 + tt * 4 + 3);
                }
                if (tid == 0) TS(2 + u);
                l0 += __shfl_xor_sync(0xffffffffu, l0, 1);
                l1 += __shfl_xor_sync(0xffffffffu, l1, 1);
                l0 += __shfl_xor_sync(0xffffffffu, l0, 2);
                l1 += __shfl_xor_sync(0xffffffffu, l1, 2);
                const float i0 = 1.f / l0, i1 = 1.f / l1;
                const uint32_t zown = smR + (w ? 3 : 0) * 16384 + t * 16;
#pragma unroll
                for (int kk = 0; kk < 8; kk++) {
                    af[kk][0] = pack_bf16(o[8 * kk + 0] * i0, o[8 * kk + 1] * i0);
                    af[kk][1] = pack_bf16(o[8 * kk + 2] * i1, o[8 * kk + 3] * i1);
                    af[kk][2] = pack_bf16(o[8 * kk + 4] * i0, o[8 * kk + 5] * i0);
                    af[kk][3] = pack_bf16(o[8 * kk + 6] * i1, o[8 * kk + 7] * i1);
                    sts128(zown + kk * 2048, af[kk][0], af[kk][1], af[kk][2], af[kk][3]);
                }
            }
            if (w == 0) bar_arrive<7, 256>(); else bar_arrive<8, 256>();
            lim = 3;
            if (u == 0) {
#pragma unroll
                for (int kk = 0; kk < 8; kk++) lds128(stash + kk * 2048, qf[kk]);
            }
#pragma unroll
            for (int ps = 0; ps < 2; ps++) {
                float acc[64];
                const uint32_t keep = smS + (3 + ps) * STAGE_BYTES + w * 16384 + t * 16;
                if (u == 0) {
#pragma unroll
                    for (int i = 0; i < 64; i++) acc[i] = 0.f;
                } else {
#pragma unroll
                    for (int j = 0; j < 8; j++) {
                        uint32_t r[4];
                        lds128(keep + j * 2048, r);
#pragma unroll
                        for (int i = 0; i < 4; i++) { acc[8 * j + 2 * i] = __uint_as_float(r[i] << 16); acc[8 * j + 2 * i + 1] = __uint_as_float(r[i] & 0xffff0000u); }
                    }
                }
#pragma unroll
                for (int st = 0; st < 4; st++) {
                    if (ps == 0 && st == 2) {
                        if (w == 0) bar_sync<8, 256>(); else bar_sync<7, 256>();
#pragma unroll
                        for (int kk = 0; kk < 8; kk++) lds128(smR + (w ? 0 : 3) * 16384 + kk * 2048 + t * 16, af[8 + kk]);
                    }
                    mbar_wait(bars + 8 * slot, ph);
                    const uint64_t db = mk_desc(smS + slot * STAGE_BYTES + w * 16384, 8192, 1024);
                    wg_fence();
#pragma unroll
                    for (int kk = 0; kk < 4; kk++)
                        wgmma_rs_n128_tb(acc, af[st * 4 + kk][0], af[st * 4 + kk][1], af[st * 4 + kk][2], af[st * 4 + kk][3], db + kk * 128, 1);
                    wg_commit();
                    wg_wait<0>();
                    if (lane == 0) mbar_arrive(bars + 8 * (NSTAGE + slot));
                    if (++slot == 3) { slot = 0; ph ^= 1; }
                }
                fence_regs(acc);
                if (u == 0) {
#pragma unroll
                    for (int j = 0; j < 8; j++)
                        sts128(keep + j * 2048, pack_bf16(acc[8 * j], acc[8 * j + 1]), pack_bf16(acc[8 * j + 2], acc[8 * j + 3]),
                               pack_bf16(acc[8 * j + 4], acc[8 * j + 5]), pack_bf16(acc[8 * j + 6], acc[8 * j + 7]));
                } else {
                    const uint32_t stg = smS + (3 + ps) * STAGE_BYTES + w * 16384 + t * 8;
#pragma unroll
                    for (int j = 0; j < 16; j++) sts64(stg + j * 1024, pack_bf16(acc[4 * j], acc[4 * j + 1]), pack_bf16(acc[4 * j + 2], acc[4 * j + 3]));
                    asm volatile("fence.proxy.async.shared::cta;" ::: "memory");
                    __syncwarp();
                    if (lane == 0) mbar_arrive(bars + 8 * (2 * NSTAGE + w * 5 + ps));
                }
                if (tid == 0) TS(4 + u * 8 + ps);
            }
            {
                float acc[32];
                if (u == 0) {
#pragma unroll
                    for (int i = 0; i < 32; i++) acc[i] = 0.f;
                } else {
#pragma unroll
                    for (int j = 0; j < 4; j++) {
                        uint32_t r[4];
                        lds128(stash + j * 2048, r);
#pragma unroll
                        for (int i = 0; i < 4; i++) { acc[8 * j + 2 * i] = __uint_as_float(r[i] << 16); acc[8 * j + 2 * i + 1] = __uint_as_float(r[i] & 0xffff0000u); }
                    }
                }
                mbar_wait(bars + 8 * slot, ph);
                const uint64_t db = mk_desc(smS + slot * STAGE_BYTES + w * 16384, 8192, 1024);
                wg_fence();
#pragma unroll
                for (int kk = 0; kk < 8; kk++)
                    wgmma_rs_n64_tb(acc, af[kk][0], af[kk][1], af[kk][2], af[kk][3], db + kk * 128, 1);
                wg_commit();
                wg_wait<0>();
                if (lane == 0) mbar_arrive(bars + 8 * (NSTAGE + slot));
                if (++slot == 3) { slot = 0; ph ^= 1; }
                fence_regs(acc);
                if (u == 0) {
#pragma unroll
                    for (int j = 0; j < 4; j++)
                        sts128(stash + j * 2048, pack_bf16(acc[8 * j], acc[8 * j + 1]), pack_bf16(acc[8 * j + 2], acc[8 * j + 3]),
                               pack_bf16(acc[8 * j + 4], acc[8 * j + 5]), pack_bf16(acc[8 * j + 6], acc[8 * j + 7]));
                } else {
                    const uint32_t stg = smR + (1 + w) * 16384 + t * 8;
#pragma unroll
                    for (int j = 0; j < 8; j++) sts64(stg + j * 1024, pack_bf16(acc[4 * j], acc[4 * j + 1]), pack_bf16(acc[4 * j + 2], acc[4 * j + 3]));
                    asm volatile("fence.proxy.async.shared::cta;" ::: "memory");
                    __syncwarp();
                    if (lane == 0) mbar_arrive(bars + 8 * (2 * NSTAGE + w * 5 + 2));
                }
                if (tid == 0) TS(6 + u * 8);
            }
        }
        {
            const int nch = (w == 0) ? 3 : 2;
            if (lane < nch) {
                const int c = (lane < 2) ? (2 * lane + w) : 4;
                const unsigned need = (lane < 2) ? 8u : 16u;
                unsigned* cp = &g_cnt[(grp * 9 + c) * 32 + hp * 4 + (wid & 3)];
                unsigned v, n = 0;
                while (true) {
                    asm volatile("ld.acquire.gpu.global.u32 %0, [%1];" : "=r"(v) : "l"(cp) : "memory");
                    if (v >= need) break;
                    if (++n > (1u << 21)) break;
                }
                *cp = 0;
            }
            __syncwarp();
            if (tid == 0) TS(18);
            __nv_bfloat16* orow = P.out + (size_t)(b * 64 + (t >> 5) * 16 + (lane >> 2)) * (2 * kD) + blk * kD + hp * 8 + (lane & 3) * 2;
            const uint2* src = g_part + ((size_t)(grp * 80 + 2 * w * 8) * 8 + hp) * 128 + t;
            uint2 v[4][8];
#pragma unroll
            for (int k = 0; k < 4; k++)
#pragma unroll
                for (int i = 0; i < 8; i++) v[k][i] = __ldcg(src + (size_t)((k >> 1) * 32 + (k & 1) * 8 + i) * 1024);
            if (w == 0) {
                const uint2* src8 = g_part + ((size_t)(grp * 80 + 64) * 8 + hp) * 128 + t;
                uint2 u[16];
#pragma unroll
                for (int i = 0; i < 16; i++) u[i] = __ldcg(src8 + (size_t)i * 1024);
                float a0 = 0.f, a1 = 0.f, a2 = 0.f, a3 = 0.f;
#pragma unroll
                for (int i = 0; i < 16; i++) {
                    a0 += __uint_as_float(u[i].x << 16); a1 += __uint_as_float(u[i].x & 0xffff0000u);
                    a2 += __uint_as_float(u[i].y << 16); a3 += __uint_as_float(u[i].y & 0xffff0000u);
                }
                *(uint32_t*)(orow + 512) = pack_bf16(a0, a1);
                *(uint32_t*)(orow + 512 + 8 * 2 * kD) = pack_bf16(a2, a3);
            }
#pragma unroll
            for (int k = 0; k < 4; k++) {
                float a0 = 0.f, a1 = 0.f, a2 = 0.f, a3 = 0.f;
#pragma unroll
                for (int i = 0; i < 8; i++) {
                    a0 += __uint_as_float(v[k][i].x << 16); a1 += __uint_as_float(v[k][i].x & 0xffff0000u);
                    a2 += __uint_as_float(v[k][i].y << 16); a3 += __uint_as_float(v[k][i].y & 0xffff0000u);
                }
                *(uint32_t*)(orow + ((k >> 1) * 4 + 2 * w + (k & 1)) * 64) = pack_bf16(a0, a1);
                *(uint32_t*)(orow + ((k >> 1) * 4 + 2 * w + (k & 1)) * 64 + 8 * 2 * kD) = pack_bf16(a2, a3);
            }
            if (tid == 0) TS(19);
        }
    }
}

typedef CUresult (*EncodeFn)(CUtensorMap*, CUtensorMapDataType, cuuint32_t, void*, const cuuint64_t*, const cuuint64_t*,
                             const cuuint32_t*, const cuuint32_t*, CUtensorMapInterleave, CUtensorMapSwizzle,
                             CUtensorMapL2promotion, CUtensorMapFloatOOBfill);

void make_map(EncodeFn fn, CUtensorMap* m, const void* ptr, uint64_t cols, uint64_t rows, uint32_t box_rows) {
    cuuint64_t dims[2] = {cols, rows};
    cuuint64_t strides[1] = {cols * 2};
    cuuint32_t box[2] = {64, box_rows};
    cuuint32_t es[2] = {1, 1};
    fn(m, CU_TENSOR_MAP_DATA_TYPE_BFLOAT16, 2, const_cast<void*>(ptr), dims, strides, box, es, CU_TENSOR_MAP_INTERLEAVE_NONE,
       CU_TENSOR_MAP_SWIZZLE_128B, CU_TENSOR_MAP_L2_PROMOTION_L2_256B, CU_TENSOR_MAP_FLOAT_OOB_FILL_NONE);
}

void make_map3(EncodeFn fn, CUtensorMap* m, const void* ptr, uint64_t cols, uint64_t rows, uint32_t box_rows, uint32_t box_groups) {
    cuuint64_t dims[3] = {64, rows, cols / 64};
    cuuint64_t strides[2] = {cols * 2, 128};
    cuuint32_t box[3] = {64, box_rows, box_groups};
    cuuint32_t es[3] = {1, 1, 1};
    fn(m, CU_TENSOR_MAP_DATA_TYPE_BFLOAT16, 3, const_cast<void*>(ptr), dims, strides, box, es, CU_TENSOR_MAP_INTERLEAVE_NONE,
       CU_TENSOR_MAP_SWIZZLE_128B, CU_TENSOR_MAP_L2_PROMOTION_L2_256B, CU_TENSOR_MAP_FLOAT_OOB_FILL_NONE);
}

}

extern "C" void kernel_launch(void* const* d_in, const int* in_sizes, int n_in, void* d_out, int out_size) {
    static EncodeFn enc = nullptr;
    if (!enc) {
        void* fn = nullptr;
        cudaDriverEntryPointQueryResult st;
        cudaGetDriverEntryPoint("cuTensorMapEncodeTiled", &fn, cudaEnableDefault, &st);
        enc = (EncodeFn)fn;
        cudaFuncSetAttribute(fused_gqa_kernel, cudaFuncAttributeMaxDynamicSharedMemorySize, SMEM_BYTES);
    }
    Params P;
    for (int blk = 0; blk < 2; blk++) {
        const void* x = d_in[blk * 5 + 0];
        const void* k = d_in[blk * 5 + 1];
        const void* v = d_in[blk * 5 + 2];
        const void* wq = d_in[blk * 5 + 3];
        const void* wo = d_in[blk * 5 + 4];
        make_map(enc, &P.x[blk], x, kD, kB * kSq, 64);
        make_map3(enc, &P.wq[blk], wq, kHq * kDh, kD, 32, 2);
        make_map3(enc, &P.k[blk], k, kDh, (uint64_t)kB * kHkv * kSk, 128, 2);
        make_map3(enc, &P.v[blk], v, kDh, (uint64_t)kB * kHkv * kSk, 128, 2);
        make_map3(enc, &P.wo[blk], wo, kD, kHq * kDh, 64, 2);
        make_map(enc, &P.wo8[blk], wo, kD, kHq * kDh, 128);
        P.wqp[blk] = (const __nv_bfloat16*)wq;
        P.kp[blk] = (const __nv_bfloat16*)k;
        P.vp[blk] = (const __nv_bfloat16*)v;
        P.wop[blk] = (const __nv_bfloat16*)wo;
    }
    P.out = (__nv_bfloat16*)d_out;
    fused_gqa_kernel<<<128, 384, SMEM_BYTES>>>(P);
}
```

```cpp
#include <cuda_runtime.h>
#include <cuda_bf16.h>
#include <cuda.h>
#include <stdint.h>

namespace {

constexpr int kB = 8, kSq = 64, kD = 576, kHq = 32, kHkv = 16, kSk = 512, kDh = 128;
constexpr int NSTAGE = 5;
constexpr int STAGE_BYTES = 32768;
constexpr int R_BYTES = 65536;
constexpr int SMEM_BYTES = R_BYTES + NSTAGE * STAGE_BYTES + 1024   + 256  ;
constexpr int N_WQ = 18;
#define PF_DIST_V 6
#define OP_WAIT0 1
#define QP_WAIT0 1
#define PF_POS1 9
#define PF_START 1
#define PF_WQ 0
#define PF_SLEEP 1000
constexpr int PF_DIST = PF_DIST_V;

struct __align__(64) Params {
    CUtensorMap x[2], wq[2], k[2], v[2], wo[2], wo8[2];
    const __nv_bfloat16* wqp[2];
    const __nv_bfloat16* kp[2];
    const __nv_bfloat16* vp[2];
    const __nv_bfloat16* wop[2];
    __nv_bfloat16* out;
};

__device__ uint2 g_part[16 * 80 * 8 * 128];
__device__ unsigned int g_cnt[16 * 9 * 32];
#define TS(k) do {} while (0)

__device__ __forceinline__ uint32_t smem_u32(const void* p) { return (uint32_t)__cvta_generic_to_shared(p); }
__device__ __forceinline__ void mbar_init(uint32_t bar, int cnt) {
    asm volatile("mbarrier.init.shared::cta.b64 [%0], %1;" ::"r"(bar), "r"(cnt));
}
__device__ __forceinline__ void mbar_expect_tx(uint32_t bar, uint32_t bytes) {
    asm volatile("mbarrier.arrive.expect_tx.shared::cta.b64 _, [%0], %1;" ::"r"(bar), "r"(bytes) : "memory");
}
__device__ __forceinline__ void mbar_arrive(uint32_t bar) {
    asm volatile("mbarrier.arrive.shared::cta.b64 _, [%0];" ::"r"(bar) : "memory");
}
__device__ __forceinline__ bool mbar_try(uint32_t bar, uint32_t parity) {
    uint32_t ok;
    asm volatile("{\n.reg .pred p;\nmbarrier.try_wait.parity.shared::cta.b64 p, [%1], %2;\nselp.u32 %0, 1, 0, p;\n}\n"
                 : "=r"(ok) : "r"(bar), "r"(parity) : "memory");
    return ok != 0;
}
__device__ __forceinline__ void mbar_wait(uint32_t bar, uint32_t parity) {
    if (mbar_try(bar, parity)) return;
    uint32_t n = 0;
    while (!mbar_try(bar, parity)) {
        if (++n > (1u << 20)) break;
    }
}
__device__ __forceinline__ void tma_2d(uint32_t dst, const CUtensorMap* tm, int c0, int c1, uint32_t bar) {
    asm volatile("cp.async.bulk.tensor.2d.shared::cluster.global.mbarrier::complete_tx::bytes [%0], [%1, {%3, %4}], [%2];"
                 ::"r"(dst), "l"(tm), "r"(bar), "r"(c0), "r"(c1) : "memory");
}
__device__ __forceinline__ void tma_3d(uint32_t dst, const CUtensorMap* tm, int c0, int c1, int c2, uint32_t bar) {
    asm volatile("cp.async.bulk.tensor.3d.shared::cluster.global.mbarrier::complete_tx::bytes [%0], [%1, {%3, %4, %5}], [%2];"
                 ::"r"(dst), "l"(tm), "r"(bar), "r"(c0), "r"(c1), "r"(c2) : "memory");
}
__device__ __forceinline__ void l2_prefetch(const void* p, uint32_t bytes) {
    asm volatile("cp.async.bulk.prefetch.L2.global [%0], %1;" ::"l"(p), "r"(bytes) : "memory");
}
__device__ __forceinline__ uint32_t l2_touch(const void* p) {
    uint32_t v;
    asm volatile("ld.global.L2::256B.b32 %0, [%1];" : "=r"(v) : "l"(p) : "memory");
    return v;
}
__device__ __forceinline__ void wg_fence() { asm volatile("wgmma.fence.sync.aligned;" ::: "memory"); }
__device__ __forceinline__ void wg_commit() { asm volatile("wgmma.commit_group.sync.aligned;" ::: "memory"); }
template <int N> __device__ __forceinline__ void wg_wait() { asm volatile("wgmma.wait_group.sync.aligned %0;" ::"n"(N) : "memory"); }
template <int N> __device__ __forceinline__ void fence_regs(float (&d)[N]) {
#pragma unroll
    for (int i = 0; i < N; i++) asm volatile("" : "+f"(d[i])::"memory");
}
__device__ __forceinline__ uint64_t mk_desc(uint32_t addr, uint32_t lbo, uint32_t sbo) {
    return (uint64_t)((addr & 0x3FFFF) >> 4) | ((uint64_t)(lbo >> 4) << 16) | ((uint64_t)(sbo >> 4) << 32) | (1ull << 62);
}
__device__ __forceinline__ uint32_t pack_bf16(float a, float b) {
    uint32_t r;
    asm("cvt.rn.bf16x2.f32 %0, %1, %2;" : "=r"(r) : "f"(b), "f"(a));
    return r;
}
__device__ __forceinline__ float ex2(float x) {
    float y;
    asm("ex2.approx.ftz.f32 %0, %1;" : "=f"(y) : "f"(x));
    return y;
}
template <int ID, int N> __device__ __forceinline__ void bar_sync() { asm volatile("bar.sync %0, %1;" ::"n"(ID), "n"(N) : "memory"); }
template <int ID, int N> __device__ __forceinline__ void bar_arrive() { asm volatile("bar.arrive %0, %1;" ::"n"(ID), "n"(N) : "memory"); }
__device__ __forceinline__ void sts128(uint32_t addr, uint32_t a, uint32_t b, uint32_t c, uint32_t d) {
    asm volatile("st.shared.v4.b32 [%0], {%1,%2,%3,%4};" ::"r"(addr), "r"(a), "r"(b), "r"(c), "r"(d) : "memory");
}
__device__ __forceinline__ void sts64(uint32_t addr, uint32_t a, uint32_t b) {
    asm volatile("st.shared.v2.b32 [%0], {%1,%2};" ::"r"(addr), "r"(a), "r"(b) : "memory");
}
__device__ __forceinline__ void bulk_store(void* dst, uint32_t src, uint32_t bytes) {
    asm volatile("cp.async.bulk.global.shared::cta.bulk_group [%0], [%1], %2;" ::"l"(dst), "r"(src), "r"(bytes) : "memory");
}
__device__ __forceinline__ void lds128(uint32_t addr, uint32_t (&r)[4]) {
    asm volatile("ld.shared.v4.b32 {%0,%1,%2,%3}, [%4];" : "=r"(r[0]), "=r"(r[1]), "=r"(r[2]), "=r"(r[3]) : "r"(addr) : "memory");
}

__device__ __forceinline__ void wgmma_ss_n256_tb(float (&d)[128], uint64_t da, uint64_t db, int sd) {
    asm volatile("{\n.reg .pred p;\nsetp.ne.b32 p, %130, 0;\n"
        "wgmma.mma_async.sync.aligned.m64n256k16.f32.bf16.bf16 "
        "{%0, %1, %2, %3, %4, %5, %6, %7, %8, %9, %10, %11, %12, %13, %14, %15, %16, %17, %18, %19, %20, %21, %22, %23, %24, %25, %26, %27, %28, %29, %30, %31, %32, %33, %34, %35, %36, %37, %38, %39, %40, %41, %42, %43, %44, %45, %46, %47, %48, %49, %50, %51, %52, %53, %54, %55, %56, %57, %58, %59, %60, %61, %62, %63, %64, %65, %66, %67, %68, %69, %70, %71, %72, %73, %74, %75, %76, %77, %78, %79, %80, %81, %82, %83, %84, %85, %86, %87, %88, %89, %90, %91, %92, %93, %94, %95, %96, %97, %98, %99, %100, %101, %102, %103, %104, %105, %106, %107, %108, %109, %110, %111, %112, %113, %114, %115, %116, %117, %118, %119, %120, %121, %122, %123, %124, %125, %126, %127}, "
        "%128, %129, p, 1, 1, 0, 1;\n}\n"
        : "+f"(d[0]), "+f"(d[1]), "+f"(d[2]), "+f"(d[3]), "+f"(d[4]), "+f"(d[5]), "+f"(d[6]), "+f"(d[7]), "+f"(d[8]), "+f"(d[9]), "+f"(d[10]), "+f"(d[11]), "+f"(d[12]), "+f"(d[13]), "+f"(d[14]), "+f"(d[15]), "+f"(d[16]), "+f"(d[17]), "+f"(d[18]), "+f"(d[19]), "+f"(d[20]), "+f"(d[21]), "+f"(d[22]), "+f"(d[23]), "+f"(d[24]), "+f"(d[25]), "+f"(d[26]), "+f"(d[27]), "+f"(d[28]), "+f"(d[29]), "+f"(d[30]), "+f"(d[31]), "+f"(d[32]), "+f"(d[33]), "+f"(d[34]), "+f"(d[35]), "+f"(d[36]), "+f"(d[37]), "+f"(d[38]), "+f"(d[39]), "+f"(d[40]), "+f"(d[41]), "+f"(d[42]), "+f"(d[43]), "+f"(d[44]), "+f"(d[45]), "+f"(d[46]), "+f"(d[47]), "+f"(d[48]), "+f"(d[49]), "+f"(d[50]), "+f"(d[51]), "+f"(d[52]), "+f"(d[53]), "+f"(d[54]), "+f"(d[55]), "+f"(d[56]), "+f"(d[57]), "+f"(d[58]), "+f"(d[59]), "+f"(d[60]), "+f"(d[61]), "+f"(d[62]), "+f"(d[63]), "+f"(d[64]), "+f"(d[65]), "+f"(d[66]), "+f"(d[67]), "+f"(d[68]), "+f"(d[69]), "+f"(d[70]), "+f"(d[71]), "+f"(d[72]), "+f"(d[73]), "+f"(d[74]), "+f"(d[75]), "+f"(d[76]), "+f"(d[77]), "+f"(d[78]), "+f"(d[79]), "+f"(d[80]), "+f"(d[81]), "+f"(d[82]), "+f"(d[83]), "+f"(d[84]), "+f"(d[85]), "+f"(d[86]), "+f"(d[87]), "+f"(d[88]), "+f"(d[89]), "+f"(d[90]), "+f"(d[91]), "+f"(d[92]), "+f"(d[93]), "+f"(d[94]), "+f"(d[95]), "+f"(d[96]), "+f"(d[97]), "+f"(d[98]), "+f"(d[99]), "+f"(d[100]), "+f"(d[101]), "+f"(d[102]), "+f"(d[103]), "+f"(d[104]), "+f"(d[105]), "+f"(d[106]), "+f"(d[107]), "+f"(d[108]), "+f"(d[109]), "+f"(d[110]), "+f"(d[111]), "+f"(d[112]), "+f"(d[113]), "+f"(d[114]), "+f"(d[115]), "+f"(d[116]), "+f"(d[117]), "+f"(d[118]), "+f"(d[119]), "+f"(d[120]), "+f"(d[121]), "+f"(d[122]), "+f"(d[123]), "+f"(d[124]), "+f"(d[125]), "+f"(d[126]), "+f"(d[127])
        : "l"(da), "l"(db), "r"(sd));
}
__device__ __forceinline__ void wgmma_rs_n128(float (&d)[64], uint32_t a0, uint32_t a1, uint32_t a2, uint32_t a3, uint64_t db, int sd) {
    asm volatile("{\n.reg .pred p;\nsetp.ne.b32 p, %69, 0;\n"
        "wgmma.mma_async.sync.aligned.m64n128k16.f32.bf16.bf16 "
        "{%0, %1, %2, %3, %4, %5, %6, %7, %8, %9, %10, %11, %12, %13, %14, %15, %16, %17, %18, %19, %20, %21, %22, %23, %24, %25, %26, %27, %28, %29, %30, %31, %32, %33, %34, %35, %36, %37, %38, %39, %40, %41, %42, %43, %44, %45, %46, %47, %48, %49, %50, %51, %52, %53, %54, %55, %56, %57, %58, %59, %60, %61, %62, %63}, "
        "{%64, %65, %66, %67}, %68, p, 1, 1, 0;\n}\n"
        : "+f"(d[0]), "+f"(d[1]), "+f"(d[2]), "+f"(d[3]), "+f"(d[4]), "+f"(d[5]), "+f"(d[6]), "+f"(d[7]), "+f"(d[8]), "+f"(d[9]), "+f"(d[10]), "+f"(d[11]), "+f"(d[12]), "+f"(d[13]), "+f"(d[14]), "+f"(d[15]), "+f"(d[16]), "+f"(d[17]), "+f"(d[18]), "+f"(d[19]), "+f"(d[20]), "+f"(d[21]), "+f"(d[22]), "+f"(d[23]), "+f"(d[24]), "+f"(d[25]), "+f"(d[26]), "+f"(d[27]), "+f"(d[28]), "+f"(d[29]), "+f"(d[30]), "+f"(d[31]), "+f"(d[32]), "+f"(d[33]), "+f"(d[34]), "+f"(d[35]), "+f"(d[36]), "+f"(d[37]), "+f"(d[38]), "+f"(d[39]), "+f"(d[40]), "+f"(d[41]), "+f"(d[42]), "+f"(d[43]), "+f"(d[44]), "+f"(d[45]), "+f"(d[46]), "+f"(d[47]), "+f"(d[48]), "+f"(d[49]), "+f"(d[50]), "+f"(d[51]), "+f"(d[52]), "+f"(d[53]), "+f"(d[54]), "+f"(d[55]), "+f"(d[56]), "+f"(d[57]), "+f"(d[58]), "+f"(d[59]), "+f"(d[60]), "+f"(d[61]), "+f"(d[62]), "+f"(d[63])
        : "r"(a0), "r"(a1), "r"(a2), "r"(a3), "l"(db), "r"(sd));
}
__device__ __forceinline__ void wgmma_rs_n128_tb(float (&d)[64], uint32_t a0, uint32_t a1, uint32_t a2, uint32_t a3, uint64_t db, int sd) {
    asm volatile("{\n.reg .pred p;\nsetp.ne.b32 p, %69, 0;\n"
        "wgmma.mma_async.sync.aligned.m64n128k16.f32.bf16.bf16 "
        "{%0, %1, %2, %3, %4, %5, %6, %7, %8, %9, %10, %11, %12, %13, %14, %15, %16, %17, %18, %19, %20, %21, %22, %23, %24, %25, %26, %27, %28, %29, %30, %31, %32, %33, %34, %35, %36, %37, %38, %39, %40, %41, %42, %43, %44, %45, %46, %47, %48, %49, %50, %51, %52, %53, %54, %55, %56, %57, %58, %59, %60, %61, %62, %63}, "
        "{%64, %65, %66, %67}, %68, p, 1, 1, 1;\n}\n"
        : "+f"(d[0]), "+f"(d[1]), "+f"(d[2]), "+f"(d[3]), "+f"(d[4]), "+f"(d[5]), "+f"(d[6]), "+f"(d[7]), "+f"(d[8]), "+f"(d[9]), "+f"(d[10]), "+f"(d[11]), "+f"(d[12]), "+f"(d[13]), "+f"(d[14]), "+f"(d[15]), "+f"(d[16]), "+f"(d[17]), "+f"(d[18]), "+f"(d[19]), "+f"(d[20]), "+f"(d[21]), "+f"(d[22]), "+f"(d[23]), "+f"(d[24]), "+f"(d[25]), "+f"(d[26]), "+f"(d[27]), "+f"(d[28]), "+f"(d[29]), "+f"(d[30]), "+f"(d[31]), "+f"(d[32]), "+f"(d[33]), "+f"(d[34]), "+f"(d[35]), "+f"(d[36]), "+f"(d[37]), "+f"(d[38]), "+f"(d[39]), "+f"(d[40]), "+f"(d[41]), "+f"(d[42]), "+f"(d[43]), "+f"(d[44]), "+f"(d[45]), "+f"(d[46]), "+f"(d[47]), "+f"(d[48]), "+f"(d[49]), "+f"(d[50]), "+f"(d[51]), "+f"(d[52]), "+f"(d[53]), "+f"(d[54]), "+f"(d[55]), "+f"(d[56]), "+f"(d[57]), "+f"(d[58]), "+f"(d[59]), "+f"(d[60]), "+f"(d[61]), "+f"(d[62]), "+f"(d[63])
        : "r"(a0), "r"(a1), "r"(a2), "r"(a3), "l"(db), "r"(sd));
}
__device__ __forceinline__ void wgmma_rs_n64_tb(float (&d)[32], uint32_t a0, uint32_t a1, uint32_t a2, uint32_t a3, uint64_t db, int sd) {
    asm volatile("{\n.reg .pred p;\nsetp.ne.b32 p, %37, 0;\n"
        "wgmma.mma_async.sync.aligned.m64n64k16.f32.bf16.bf16 "
        "{%0, %1, %2, %3, %4, %5, %6, %7, %8, %9, %10, %11, %12, %13, %14, %15, %16, %17, %18, %19, %20, %21, %22, %23, %24, %25, %26, %27, %28, %29, %30, %31}, "
        "{%32, %33, %34, %35}, %36, p, 1, 1, 1;\n}\n"
        : "+f"(d[0]), "+f"(d[1]), "+f"(d[2]), "+f"(d[3]), "+f"(d[4]), "+f"(d[5]), "+f"(d[6]), "+f"(d[7]), "+f"(d[8]), "+f"(d[9]), "+f"(d[10]), "+f"(d[11]), "+f"(d[12]), "+f"(d[13]), "+f"(d[14]), "+f"(d[15]), "+f"(d[16]), "+f"(d[17]), "+f"(d[18]), "+f"(d[19]), "+f"(d[20]), "+f"(d[21]), "+f"(d[22]), "+f"(d[23]), "+f"(d[24]), "+f"(d[25]), "+f"(d[26]), "+f"(d[27]), "+f"(d[28]), "+f"(d[29]), "+f"(d[30]), "+f"(d[31])
        : "r"(a0), "r"(a1), "r"(a2), "r"(a3), "l"(db), "r"(sd));
}

__global__ void __launch_bounds__(384, 1) fused_gqa_kernel(const __grid_constant__ Params P) {
    extern __shared__ uint8_t smem_raw[];
    const uint32_t base = (smem_u32(smem_raw) + 1023u) & ~1023u;
    const uint32_t smR = base;
    const uint32_t smS = base + R_BYTES;
    const uint32_t bars = smS + NSTAGE * STAGE_BYTES;
    const uint32_t prog = bars + 8 * (2 * NSTAGE + 10);
    const int tid = threadIdx.x;
    const int wid = __shfl_sync(0xffffffffu, tid >> 5, 0);
    const int lane = tid & 31;

    const int cta = blockIdx.x;
    const int blk = cta >> 6;
    const int hp = (cta >> 3) & 7;
    const int b = cta & 7;
    const int grp = blk * 8 + b;

    if (tid == 0) {
        TS(0);
        for (int i = 0; i < NSTAGE; i++) {
            mbar_init(bars + 8 * i, 1);
            mbar_init(bars + 8 * (NSTAGE + i), 8);
        }
        for (int i = 0; i < 10; i++) mbar_init(bars + 8 * (2 * NSTAGE + i), 4);
        asm volatile("st.volatile.shared.u32 [%0], %1;" ::"r"(prog), "r"(0) : "memory");
        asm volatile("fence.mbarrier_init.release.cluster;" ::: "memory");
        asm volatile("fence.proxy.async.shared::cta;" ::: "memory");
    }
    __syncthreads();

    if (wid >= 8) {
        asm volatile("setmaxnreg.dec.sync.aligned.u32 40;");
        auto publish = [&](int hw, int k) {
            mbar_wait(bars + 8 * (2 * NSTAGE + hw * 5 + k), 0);
            const int c = (k < 2) ? (2 * k + hw) : 4;
            if (lane == 0) {
                if (k < 2) {
                    uint2* dst = g_part + (size_t)(grp * 80 + (4 * k + 2 * hw) * 8 + hp) * 1024;
                    const uint32_t src = k ? (smS + 3 * STAGE_BYTES + hw * 16384) : (smR + (hw ? 3 : 0) * 16384);
                    bulk_store(dst, src, 8192);
                    bulk_store(dst + 8192, src + 8192, 8192);
                } else {
                    bulk_store(g_part + (size_t)(grp * 80 + 64 + hp * 2 + hw) * 1024, smR + (1 + hw) * 16384, 8192);
                }
                asm volatile("cp.async.bulk.commit_group;" ::: "memory");
                asm volatile("cp.async.bulk.wait_group 0;" ::: "memory");
                asm volatile("fence.acq_rel.gpu;" ::: "memory");
            }
            __syncwarp();
            asm volatile("red.relaxed.gpu.global.add.u32 [%0], 1;" ::"l"(&g_cnt[(grp * 9 + c) * 32 + lane]) : "memory");
        };
        if (wid == 8) {
            if (lane == 0) {
                int slot = 0, ph = 1;
                for (int s = 0; s < N_WQ; s++) {
                    const uint32_t fb = bars + 8 * slot;
                    mbar_wait(bars + 8 * (NSTAGE + slot), ph);
                    const uint32_t dst = smS + slot * STAGE_BYTES;
                    mbar_expect_tx(fb, (s & 1) ? STAGE_BYTES : STAGE_BYTES + 8192);
                    if (!(s & 1)) tma_2d(smR + ((s >> 1) & 7) * 8192, &P.x[blk], (s >> 1) * 64, b * 64, fb);
#pragma unroll
                    for (int p = 0; p < 4; p++) {
                        const int w = p >> 1, j = p & 1;
                        tma_3d(dst + p * 8192, &P.wq[blk], 0, s * 32, hp * 8 + j * 4 + w * 2, fb);
                    }
                    if (++slot == NSTAGE) { slot = 0; ph ^= 1; }
                }
                int lim = NSTAGE;
                for (int i = 0; i < 34; i++) {
                    const int u = (i >= 17), r = i - 17 * u;
                    const bool extra = (i == 28) || (i == 31);
                    const int sl = extra ? ((i == 28) ? 3 : 4) : slot;
                    const uint32_t fb = bars + 8 * sl;
                    mbar_wait(bars + 8 * (NSTAGE + sl), extra ? 1 : ph);
                    const uint32_t dst = smS + sl * STAGE_BYTES;
                    mbar_expect_tx(fb, STAGE_BYTES);
                    if (r < 8) {
                        const int row = (b * kHkv + hp * 2 + u) * kSk + (r >> 1) * 128;
                        tma_3d(dst, (r & 1) ? &P.v[blk] : &P.k[blk], 0, row, 0, fb);
                    } else {
                        const int q = r - 8, row = hp * 512 + u * 256;
                        if (q < 8) {
                            tma_3d(dst, &P.wo[blk], 0, row + (q & 3) * 64, (q >> 2) * 4, fb);
                            tma_3d(dst + 16384, &P.wo[blk], 0, row + ((q & 3) ^ 2) * 64, (q >> 2) * 4 + 2, fb);
                        } else {
                            tma_2d(dst, &P.wo8[blk], 512, row, fb);
                            tma_2d(dst + 16384, &P.wo8[blk], 512, row + 128, fb);
                        }
                    }
                    asm volatile("st.volatile.shared.u32 [%0], %1;" ::"r"(prog), "r"(i + 1) : "memory");
                    if (i == 7) lim = 3;
                    if (!extra && ++slot == lim) { slot = 0; ph ^= 1; }
                }
            }
            __syncwarp();
            publish(1, 1);
        } else if (wid == 11) {
            if (PF_DIST > 0) {
                uint32_t sink = 0;
                mbar_wait(bars, 0);
                if (PF_WQ) {
                    const char* wqs = (const char*)(P.wqp[blk] + hp * 512) + (size_t)(160 + b * 52) * 8192;
#pragma unroll
                    for (int h = 0; h < 2; h++) {
#pragma unroll
                        for (int j = 0; j < 4; j++) {
                            const int e = (h * 4 + j) * 32 + lane;
                            if (e < 208) sink |= l2_touch(wqs + (size_t)(e >> 2) * 8192 + (e & 3) * 256);
                        }
                        if (sink == 0x9E3779B9u) asm volatile("st.volatile.shared.u32 [%0], %1;" ::"r"(prog + 4), "r"(sink) : "memory");
                    }
                }
                const char* kbase = (const char*)(P.kp[blk] + (size_t)(b * kHkv + hp * 2) * kSk * kDh);
                const char* vbase = (const char*)(P.vp[blk] + (size_t)(b * kHkv + hp * 2) * kSk * kDh);
                const char* wos = (const char*)(P.wop[blk] + (size_t)hp * 512 * kD) + (size_t)b * 36864;
                for (int i = 0; i < 18; i++) {
                    const int u = (i >= 9), r = i - 9 * u;
                    const int pos = u ? (PF_POS1 + r) : r;
                    if (pos >= PF_DIST) {
                        uint32_t pr, n = 0;
                        while (true) {
                            asm volatile("ld.volatile.shared.u32 %0, [%1];" : "=r"(pr) : "r"(prog) : "memory");
                            const int prk = ((int)pr <= 8) ? (int)pr : (((int)pr <= 17) ? 8 + (((int)pr - 8) * (PF_POS1 - 8)) / 9 : (int)pr - 17 + PF_POS1);
                            if (prk + PF_DIST >= pos) break;
                            if (++n > (1u << 22)) break;
                            __nanosleep(100);
                        }
                    }
                    if (r < 8) {
                        const char* p = ((r & 1) ? vbase : kbase) + (size_t)(u * 4 + (r >> 1)) * 32768 + lane * 256;
#pragma unroll
                        for (int j = 0; j < 4; j++) sink |= l2_touch(p + j * 8192);
                    } else {
                        const char* p = wos + (size_t)u * 294912 + lane * 256;
#pragma unroll
                        for (int j = 0; j < 5; j++) if (j * 32 + lane < 144) sink |= l2_touch(p + j * 8192);
                    }
                    if (sink == 0x9E3779B9u) asm volatile("st.volatile.shared.u32 [%0], %1;" ::"r"(prog + 4), "r"(sink) : "memory");
                }
            }
            publish(0, 1);
        } else {
            const int hw = wid - 9;
            publish(hw, 0);
            publish(hw, 2);
        }
    } else {
        asm volatile("setmaxnreg.inc.sync.aligned.u32 232;");
        const int w = wid >> 2;
        const int t = tid & 127;
        int slot = 0, ph = 0, lim = NSTAGE;
        uint32_t qf[8][4];
        const uint32_t stash = smR + (1 + w) * 16384 + t * 16;
        {
            float acc[128];
            int pslot = 0;
            for (int s = 0; s < N_WQ; s++) {
                mbar_wait(bars + 8 * slot, ph);
                if (tid == 0 && s == 0) TS(20);
                if (tid == 0 && s == 5) TS(21);
                if (tid == 0 && s == 10) TS(22);
                const uint64_t da = mk_desc(smR + ((s >> 1) & 7) * 8192 + (s & 1) * 64, 16, 1024);
                const uint64_t db = mk_desc(smS + slot * STAGE_BYTES + w * 16384, 4096, 1024);
                wg_fence();
                wgmma_ss_n256_tb(acc, da, db, s != 0);
                wgmma_ss_n256_tb(acc, da + 2, db + 128, 1);
                wg_commit();
                wg_wait<0>();
                if (lane == 0) mbar_arrive(bars + 8 * (NSTAGE + slot));
                pslot = slot;
                if (++slot == NSTAGE) { slot = 0; ph ^= 1; }
            }
            fence_regs(acc);
            if (tid == 0) TS(1);
#pragma unroll
            for (int kk = 0; kk < 8; kk++) {
#pragma unroll
                for (int i = 0; i < 4; i++) qf[kk][i] = pack_bf16(acc[8 * kk + 2 * i], acc[8 * kk + 2 * i + 1]);
                sts128(stash + kk * 2048,
                       pack_bf16(acc[64 + 8 * kk + 0], acc[64 + 8 * kk + 1]), pack_bf16(acc[64 + 8 * kk + 2], acc[64 + 8 * kk + 3]),
                       pack_bf16(acc[64 + 8 * kk + 4], acc[64 + 8 * kk + 5]), pack_bf16(acc[64 + 8 * kk + 6], acc[64 + 8 * kk + 7]));
            }
        }
        if (w == 1) bar_arrive<5, 256>();
        const float sc = 0.08838834764831845f * 1.4426950408889634f;
#pragma unroll
        for (int u = 0; u < 2; u++) {
            uint32_t af[16][4];
            {
                float o[64], s[64];
                float m0 = -INFINITY, m1 = -INFINITY, l0 = 0.f, l1 = 0.f;
                uint32_t pf[8][4];
#pragma unroll
                for (int i = 0; i < 64; i++) { o[i] = 0.f; s[i] = 0.f; }
#pragma unroll
                for (int i = 0; i < 32; i++) pf[i >> 2][i & 3] = 0u;
#pragma unroll 1
                for (int tt = 0; tt <= 4; tt++) {
                    int vslot = slot;
                    if (tt > 0) {
                        mbar_wait(bars + 8 * slot, ph);
                        if (++slot == lim) { slot = 0; ph ^= 1; }
                    }
                    if (tt < 4) mbar_wait(bars + 8 * slot, ph);
                    if (tid == 0) TS(32 + u * 20 + tt * 4);
                    if (w == 0) bar_sync<5, 256>(); else bar_sync<6, 256>();
                    wg_fence();
                    if (tt > 0) {
                        const uint64_t db = mk_desc(smS + vslot * STAGE_BYTES, 16384, 1024);
#pragma unroll
                        for (int kk = 0; kk < 8; kk++)
                            wgmma_rs_n128_tb(o, pf[kk][0], pf[kk][1], pf[kk][2], pf[kk][3], db + kk * 128, (tt > 1) || (kk != 0));
                        wg_commit();
                    }
                    if (tt < 4) {
                        const uint64_t db = mk_desc(smS + slot * STAGE_BYTES, 16, 1024);
#pragma unroll
                        for (int kk = 0; kk < 8; kk++)
                            wgmma_rs_n128(s, qf[kk][0], qf[kk][1], qf[kk][2], qf[kk][3], db + (kk >> 2) * 1024 + (kk & 3) * 2, kk != 0);
                        wg_commit();
                    }
                    if (w == 0) bar_arrive<6, 256>(); else if (!(u == 1 && tt == 4)) bar_arrive<5, 256>();
                    if (tid == 0) TS(32 + u * 20 + tt * 4 + 1);
                    wg_wait<0>();
                    fence_regs(o);
                    fence_regs(s);
                    if (tid == 0) TS(32 + u * 20 + tt * 4 + 2);
                    if (tt > 0 && lane == 0) mbar_arrive(bars + 8 * (NSTAGE + vslot));
                    if (tt == 4) break;
                    if (lane == 0) mbar_arrive(bars + 8 * (NSTAGE + slot));
                    if (++slot == lim) { slot = 0; ph ^= 1; }
                    float mx0 = s[0], mx1 = s[2];
#pragma unroll
                    for (int j = 0; j < 16; j++) {
                        mx0 = fmaxf(mx0, fmaxf(s[4 * j], s[4 * j + 1]));
                        mx1 = fmaxf(mx1, fmaxf(s[4 * j + 2], s[4 * j + 3]));
                    }
                    mx0 = fmaxf(mx0, __shfl_xor_sync(0xffffffffu, mx0, 1));
                    mx1 = fmaxf(mx1, __shfl_xor_sync(0xffffffffu, mx1, 1));
                    mx0 = fmaxf(mx0, __shfl_xor_sync(0xffffffffu, mx0, 2));
                    mx1 = fmaxf(mx1, __shfl_xor_sync(0xffffffffu, mx1, 2));
                    const float mn0 = fmaxf(m0, mx0), mn1 = fmaxf(m1, mx1);
                    const float al0 = ex2((m0 - mn0) * sc), al1 = ex2((m1 - mn1) * sc);
                    m0 = mn0; m1 = mn1;
                    const float ms0 = mn0 * sc, ms1 = mn1 * sc;
                    float rs0 = 0.f, rs1 = 0.f;
#pragma unroll
                    for (int j = 0; j < 16; j++) {
                        const float p0 = ex2(fmaf(s[4 * j], sc, -ms0)), p1 = ex2(fmaf(s[4 * j + 1], sc, -ms0));
                        const float p2 = ex2(fmaf(s[4 * j + 2], sc, -ms1)), p3 = ex2(fmaf(s[4 * j + 3], sc, -ms1));
                        rs0 += p0 + p1; rs1 += p2 + p3;
                        pf[j >> 1][(j & 1) * 2] = pack_bf16(p0, p1);
                        pf[j >> 1][(j & 1) * 2 + 1] = pack_bf16(p2, p3);
                    }
                    l0 = l0 * al0 + rs0; l1 = l1 * al1 + rs1;
                    if (tt > 0) {
#pragma unroll
                        for (int j = 0; j < 16; j++) { o[4 * j] *= al0; o[4 * j + 1] *= al0; o[4 * j + 2] *= al1; o[4 * j + 3] *= al1; }
                    }
                    if (tid == 0) TS(32 + u * 20 + tt * 4 + 3);
                }
                if (tid == 0) TS(2 + u);
                l0 += __shfl_xor_sync(0xffffffffu, l0, 1);
                l1 += __shfl_xor_sync(0xffffffffu, l1, 1);
                l0 += __shfl_xor_sync(0xffffffffu, l0, 2);
                l1 += __shfl_xor_sync(0xffffffffu, l1, 2);
                const float i0 = 1.f / l0, i1 = 1.f / l1;
                const uint32_t zown = smR + (w ? 3 : 0) * 16384 + t * 16;
#pragma unroll
                for (int kk = 0; kk < 8; kk++) {
                    af[kk][0] = pack_bf16(o[8 * kk + 0] * i0, o[8 * kk + 1] * i0);
                    af[kk][1] = pack_bf16(o[8 * kk + 2] * i1, o[8 * kk + 3] * i1);
                    af[kk][2] = pack_bf16(o[8 * kk + 4] * i0, o[8 * kk + 5] * i0);
                    af[kk][3] = pack_bf16(o[8 * kk + 6] * i1, o[8 * kk + 7] * i1);
                    sts128(zown + kk * 2048, af[kk][0], af[kk][1], af[kk][2], af[kk][3]);
                }
            }
            if (w == 0) bar_arrive<7, 256>(); else bar_arrive<8, 256>();
            lim = 3;
            if (u == 0) {
#pragma unroll
                for (int kk = 0; kk < 8; kk++) lds128(stash + kk * 2048, qf[kk]);
            }
#pragma unroll
            for (int ps = 0; ps < 2; ps++) {
                float acc[64];
                const uint32_t keep = smS + (3 + ps) * STAGE_BYTES + w * 16384 + t * 16;
                if (u == 0) {
#pragma unroll
                    for (int i = 0; i < 64; i++) acc[i] = 0.f;
                } else {
#pragma unroll
                    for (int j = 0; j < 8; j++) {
                        uint32_t r[4];
                        lds128(keep + j * 2048, r);
#pragma unroll
                        for (int i = 0; i < 4; i++) { acc[8 * j + 2 * i] = __uint_as_float(r[i] << 16); acc[8 * j + 2 * i + 1] = __uint_as_float(r[i] & 0xffff0000u); }
                    }
                    asm volatile("fence.proxy.async.shared::cta;" ::: "memory");
                    __syncwarp();
                    if (lane == 0) mbar_arrive(bars + 8 * (NSTAGE + 3 + ps));
                }
#pragma unroll
                for (int st = 0; st < 4; st++) {
                    if (ps == 0 && st == 2) {
                        if (w == 0) bar_sync<8, 256>(); else bar_sync<7, 256>();
#pragma unroll
                        for (int kk = 0; kk < 8; kk++) lds128(smR + (w ? 0 : 3) * 16384 + kk * 2048 + t * 16, af[8 + kk]);
                        if (u == 1) { if (w == 0) bar_arrive<9, 256>(); else bar_arrive<10, 256>(); }
                    }
                    const bool extra = (u == 1) && ((ps == 0 && st == 3) || (ps == 1 && st == 2));
                    const int sl = extra ? (3 + ps) : slot;
                    mbar_wait(bars + 8 * sl, extra ? 1 : ph);
                    const uint64_t db = mk_desc(smS + sl * STAGE_BYTES + w * 16384, 8192, 1024);
                    wg_fence();
#pragma unroll
                    for (int kk = 0; kk < 4; kk++)
                        wgmma_rs_n128_tb(acc, af[st * 4 + kk][0], af[st * 4 + kk][1], af[st * 4 + kk][2], af[st * 4 + kk][3], db + kk * 128, 1);
                    wg_commit();
                    wg_wait<0>();
                    if (!extra) {
                        if (lane == 0) mbar_arrive(bars + 8 * (NSTAGE + slot));
                        if (++slot == 3) { slot = 0; ph ^= 1; }
                    }
                }
                fence_regs(acc);
                if (u == 0) {
#pragma unroll
                    for (int j = 0; j < 8; j++)
                        sts128(keep + j * 2048, pack_bf16(acc[8 * j], acc[8 * j + 1]), pack_bf16(acc[8 * j + 2], acc[8 * j + 3]),
                               pack_bf16(acc[8 * j + 4], acc[8 * j + 5]), pack_bf16(acc[8 * j + 6], acc[8 * j + 7]));
                } else {
                    if (ps == 0) { if (w == 0) bar_sync<10, 256>(); else bar_sync<9, 256>(); }
                    const uint32_t stg = (ps ? (smS + 3 * STAGE_BYTES + w * 16384) : (smR + (w ? 3 : 0) * 16384)) + t * 8;
#pragma unroll
                    for (int j = 0; j < 16; j++) sts64(stg + j * 1024, pack_bf16(acc[4 * j], acc[4 * j + 1]), pack_bf16(acc[4 * j + 2], acc[4 * j + 3]));
                    asm volatile("fence.proxy.async.shared::cta;" ::: "memory");
                    __syncwarp();
                    if (lane == 0) mbar_arrive(bars + 8 * (2 * NSTAGE + w * 5 + ps));
                }
                if (tid == 0) TS(4 + u * 8 + ps);
            }
            {
                float acc[32];
                if (u == 0) {
#pragma unroll
                    for (int i = 0; i < 32; i++) acc[i] = 0.f;
                } else {
#pragma unroll
                    for (int j = 0; j < 4; j++) {
                        uint32_t r[4];
                        lds128(stash + j * 2048, r);
#pragma unroll
                        for (int i = 0; i < 4; i++) { acc[8 * j + 2 * i] = __uint_as_float(r[i] << 16); acc[8 * j + 2 * i + 1] = __uint_as_float(r[i] & 0xffff0000u); }
                    }
                }
                mbar_wait(bars + 8 * slot, ph);
                const uint64_t db = mk_desc(smS + slot * STAGE_BYTES + w * 16384, 8192, 1024);
                wg_fence();
#pragma unroll
                for (int kk = 0; kk < 8; kk++)
                    wgmma_rs_n64_tb(acc, af[kk][0], af[kk][1], af[kk][2], af[kk][3], db + kk * 128, 1);
                wg_commit();
                wg_wait<0>();
                if (lane == 0) mbar_arrive(bars + 8 * (NSTAGE + slot));
                if (++slot == 3) { slot = 0; ph ^= 1; }
                fence_regs(acc);
                if (u == 0) {
#pragma unroll
                    for (int j = 0; j < 4; j++)
                        sts128(stash + j * 2048, pack_bf16(acc[8 * j], acc[8 * j + 1]), pack_bf16(acc[8 * j + 2], acc[8 * j + 3]),
                               pack_bf16(acc[8 * j + 4], acc[8 * j + 5]), pack_bf16(acc[8 * j + 6], acc[8 * j + 7]));
                } else {
                    const uint32_t stg = smR + (1 + w) * 16384 + t * 8;
#pragma unroll
                    for (int j = 0; j < 8; j++) sts64(stg + j * 1024, pack_bf16(acc[4 * j], acc[4 * j + 1]), pack_bf16(acc[4 * j + 2], acc[4 * j + 3]));
                    asm volatile("fence.proxy.async.shared::cta;" ::: "memory");
                    __syncwarp();
                    if (lane == 0) mbar_arrive(bars + 8 * (2 * NSTAGE + w * 5 + 2));
                }
                if (tid == 0) TS(6 + u * 8);
            }
        }
        {
            const int nch = (w == 0) ? 3 : 2;
            if (lane < nch) {
                const int c = (lane < 2) ? (2 * lane + w) : 4;
                const unsigned need = (lane < 2) ? 8u : 16u;
                unsigned* cp = &g_cnt[(grp * 9 + c) * 32 + hp * 4 + (wid & 3)];
                unsigned v, n = 0;
                while (true) {
                    asm volatile("ld.acquire.gpu.global.u32 %0, [%1];" : "=r"(v) : "l"(cp) : "memory");
                    if (v >= need) break;
                    if (++n > (1u << 21)) break;
                }
                *cp = 0;
            }
            __syncwarp();
            if (tid == 0) TS(18);
            __nv_bfloat16* orow = P.out + (size_t)(b * 64 + (t >> 5) * 16 + (lane >> 2)) * (2 * kD) + blk * kD + hp * 8 + (lane & 3) * 2;
            const uint2* src = g_part + ((size_t)(grp * 80 + 2 * w * 8) * 8 + hp) * 128 + t;
            uint2 v[4][8];
#pragma unroll
            for (int k = 0; k < 4; k++)
#pragma unroll
                for (int i = 0; i < 8; i++) v[k][i] = __ldcg(src + (size_t)((k >> 1) * 32 + (k & 1) * 8 + i) * 1024);
            if (w == 0) {
                const uint2* src8 = g_part + ((size_t)(grp * 80 + 64) * 8 + hp) * 128 + t;
                uint2 u[16];
#pragma unroll
                for (int i = 0; i < 16; i++) u[i] = __ldcg(src8 + (size_t)i * 1024);
                float a0 = 0.f, a1 = 0.f, a2 = 0.f, a3 = 0.f;
#pragma unroll
                for (int i = 0; i < 16; i++) {
                    a0 += __uint_as_float(u[i].x << 16); a1 += __uint_as_float(u[i].x & 0xffff0000u);
                    a2 += __uint_as_float(u[i].y << 16); a3 += __uint_as_float(u[i].y & 0xffff0000u);
                }
                *(uint32_t*)(orow + 512) = pack_bf16(a0, a1);
                *(uint32_t*)(orow + 512 + 8 * 2 * kD) = pack_bf16(a2, a3);
            }
#pragma unroll
            for (int k = 0; k < 4; k++) {
                float a0 = 0.f, a1 = 0.f, a2 = 0.f, a3 = 0.f;
#pragma unroll
                for (int i = 0; i < 8; i++) {
                    a0 += __uint_as_float(v[k][i].x << 16); a1 += __uint_as_float(v[k][i].x & 0xffff0000u);
                    a2 += __uint_as_float(v[k][i].y << 16); a3 += __uint_as_float(v[k][i].y & 0xffff0000u);
                }
                *(uint32_t*)(orow + ((k >> 1) * 4 + 2 * w + (k & 1)) * 64) = pack_bf16(a0, a1);
                *(uint32_t*)(orow + ((k >> 1) * 4 + 2 * w + (k & 1)) * 64 + 8 * 2 * kD) = pack_bf16(a2, a3);
            }
            if (tid == 0) TS(19);
        }
    }
}

typedef CUresult (*EncodeFn)(CUtensorMap*, CUtensorMapDataType, cuuint32_t, void*, const cuuint64_t*, const cuuint64_t*,
                             const cuuint32_t*, const cuuint32_t*, CUtensorMapInterleave, CUtensorMapSwizzle,
                             CUtensorMapL2promotion, CUtensorMapFloatOOBfill);

void make_map(EncodeFn fn, CUtensorMap* m, const void* ptr, uint64_t cols, uint64_t rows, uint32_t box_rows) {
    cuuint64_t dims[2] = {cols, rows};
    cuuint64_t strides[1] = {cols * 2};
    cuuint32_t box[2] = {64, box_rows};
    cuuint32_t es[2] = {1, 1};
    fn(m, CU_TENSOR_MAP_DATA_TYPE_BFLOAT16, 2, const_cast<void*>(ptr), dims, strides, box, es, CU_TENSOR_MAP_INTERLEAVE_NONE,
       CU_TENSOR_MAP_SWIZZLE_128B, CU_TENSOR_MAP_L2_PROMOTION_L2_256B, CU_TENSOR_MAP_FLOAT_OOB_FILL_NONE);
}

void make_map3(EncodeFn fn, CUtensorMap* m, const void* ptr, uint64_t cols, uint64_t rows, uint32_t box_rows, uint32_t box_groups) {
    cuuint64_t dims[3] = {64, rows, cols / 64};
    cuuint64_t strides[2] = {cols * 2, 128};
    cuuint32_t box[3] = {64, box_rows, box_groups};
    cuuint32_t es[3] = {1, 1, 1};
    fn(m, CU_TENSOR_MAP_DATA_TYPE_BFLOAT16, 3, const_cast<void*>(ptr), dims, strides, box, es, CU_TENSOR_MAP_INTERLEAVE_NONE,
       CU_TENSOR_MAP_SWIZZLE_128B, CU_TENSOR_MAP_L2_PROMOTION_L2_256B, CU_TENSOR_MAP_FLOAT_OOB_FILL_NONE);
}

}

extern "C" void kernel_launch(void* const* d_in, const int* in_sizes, int n_in, void* d_out, int out_size) {
    static EncodeFn enc = nullptr;
    if (!enc) {
        void* fn = nullptr;
        cudaDriverEntryPointQueryResult st;
        cudaGetDriverEntryPoint("cuTensorMapEncodeTiled", &fn, cudaEnableDefault, &st);
        enc = (EncodeFn)fn;
        cudaFuncSetAttribute(fused_gqa_kernel, cudaFuncAttributeMaxDynamicSharedMemorySize, SMEM_BYTES);
    }
    Params P;
    for (int blk = 0; blk < 2; blk++) {
        const void* x = d_in[blk * 5 + 0];
        const void* k = d_in[blk * 5 + 1];
        const void* v = d_in[blk * 5 + 2];
        const void* wq = d_in[blk * 5 + 3];
        const void* wo = d_in[blk * 5 + 4];
        make_map(enc, &P.x[blk], x, kD, kB * kSq, 64);
        make_map3(enc, &P.wq[blk], wq, kHq * kDh, kD, 32, 2);
        make_map3(enc, &P.k[blk], k, kDh, (uint64_t)kB * kHkv * kSk, 128, 2);
        make_map3(enc, &P.v[blk], v, kDh, (uint64_t)kB * kHkv * kSk, 128, 2);
        make_map3(enc, &P.wo[blk], wo, kD, kHq * kDh, 64, 2);
        make_map(enc, &P.wo8[blk], wo, kD, kHq * kDh, 128);
        P.wqp[blk] = (const __nv_bfloat16*)wq;
        P.kp[blk] = (const __nv_bfloat16*)k;
        P.vp[blk] = (const __nv_bfloat16*)v;
        P.wop[blk] = (const __nv_bfloat16*)wo;
    }
    P.out = (__nv_bfloat16*)d_out;
    fused_gqa_kernel<<<128, 384, SMEM_BYTES>>>(P);
}
```

```cpp
#include <cuda_runtime.h>
#include <cuda_bf16.h>
#include <cuda.h>
#include <stdint.h>

namespace {

constexpr int kB = 8, kSq = 64, kD = 576, kHq = 32, kHkv = 16, kSk = 512, kDh = 128;
constexpr int NSTAGE = 5;
constexpr int STAGE_BYTES = 32768;
constexpr int R_BYTES = 65536;
constexpr int SMEM_BYTES = R_BYTES + NSTAGE * STAGE_BYTES + 1024   + 256  ;
constexpr int N_WQ = 18;
#define PF_DIST_V 6
#define OP_WAIT0 1
#define QP_WAIT0 1
#define PF_POS1 9
#define PF_START 1
#define PF_WQ 0
#define PF_SLEEP 1000
constexpr int PF_DIST = PF_DIST_V;

struct __align__(64) Params {
    CUtensorMap x[2], wq[2], k[2], v[2], wo[2], wo8[2];
    const __nv_bfloat16* wqp[2];
    const __nv_bfloat16* kp[2];
    const __nv_bfloat16* vp[2];
    const __nv_bfloat16* wop[2];
    __nv_bfloat16* out;
};

__device__ uint2 g_part[16 * 80 * 8 * 128];
__device__ unsigned int g_cnt[16 * 9 * 32];
#define TS(k) do {} while (0)

__device__ __forceinline__ uint32_t smem_u32(const void* p) { return (uint32_t)__cvta_generic_to_shared(p); }
__device__ __forceinline__ void mbar_init(uint32_t bar, int cnt) {
    asm volatile("mbarrier.init.shared::cta.b64 [%0], %1;" ::"r"(bar), "r"(cnt));
}
__device__ __forceinline__ void mbar_expect_tx(uint32_t bar, uint32_t bytes) {
    asm volatile("mbarrier.arrive.expect_tx.shared::cta.b64 _, [%0], %1;" ::"r"(bar), "r"(bytes) : "memory");
}
__device__ __forceinline__ void mbar_arrive(uint32_t bar) {
    asm volatile("mbarrier.arrive.shared::cta.b64 _, [%0];" ::"r"(bar) : "memory");
}
__device__ __forceinline__ bool mbar_try(uint32_t bar, uint32_t parity) {
    uint32_t ok;
    asm volatile("{\n.reg .pred p;\nmbarrier.try_wait.parity.shared::cta.b64 p, [%1], %2;\nselp.u32 %0, 1, 0, p;\n}\n"
                 : "=r"(ok) : "r"(bar), "r"(parity) : "memory");
    return ok != 0;
}
__device__ __forceinline__ void mbar_wait(uint32_t bar, uint32_t parity) {
    if (mbar_try(bar, parity)) return;
    uint32_t n = 0;
    while (!mbar_try(bar, parity)) {
        if (++n > (1u << 20)) break;
    }
}
__device__ __forceinline__ void tma_2d(uint32_t dst, const CUtensorMap* tm, int c0, int c1, uint32_t bar) {
    asm volatile("cp.async.bulk.tensor.2d.shared::cluster.global.mbarrier::complete_tx::bytes [%0], [%1, {%3, %4}], [%2];"
                 ::"r"(dst), "l"(tm), "r"(bar), "r"(c0), "r"(c1) : "memory");
}
__device__ __forceinline__ void tma_3d(uint32_t dst, const CUtensorMap* tm, int c0, int c1, int c2, uint32_t bar) {
    asm volatile("cp.async.bulk.tensor.3d.shared::cluster.global.mbarrier::complete_tx::bytes [%0], [%1, {%3, %4, %5}], [%2];"
                 ::"r"(dst), "l"(tm), "r"(bar), "r"(c0), "r"(c1), "r"(c2) : "memory");
}
__device__ __forceinline__ void l2_prefetch(const void* p, uint32_t bytes) {
    asm volatile("cp.async.bulk.prefetch.L2.global [%0], %1;" ::"l"(p), "r"(bytes) : "memory");
}
__device__ __forceinline__ uint32_t l2_touch(const void* p) {
    uint32_t v;
    asm volatile("ld.global.L2::256B.b32 %0, [%1];" : "=r"(v) : "l"(p) : "memory");
    return v;
}
__device__ __forceinline__ void wg_fence() { asm volatile("wgmma.fence.sync.aligned;" ::: "memory"); }
__device__ __forceinline__ void wg_commit() { asm volatile("wgmma.commit_group.sync.aligned;" ::: "memory"); }
template <int N> __device__ __forceinline__ void wg_wait() { asm volatile("wgmma.wait_group.sync.aligned %0;" ::"n"(N) : "memory"); }
template <int N> __device__ __forceinline__ void fence_regs(float (&d)[N]) {
#pragma unroll
    for (int i = 0; i < N; i++) asm volatile("" : "+f"(d[i])::"memory");
}
__device__ __forceinline__ uint64_t mk_desc(uint32_t addr, uint32_t lbo, uint32_t sbo) {
    return (uint64_t)((addr & 0x3FFFF) >> 4) | ((uint64_t)(lbo >> 4) << 16) | ((uint64_t)(sbo >> 4) << 32) | (1ull << 62);
}
__device__ __forceinline__ uint32_t pack_bf16(float a, float b) {
    uint32_t r;
    asm("cvt.rn.bf16x2.f32 %0, %1, %2;" : "=r"(r) : "f"(b), "f"(a));
    return r;
}
__device__ __forceinline__ float ex2(float x) {
    float y;
    asm("ex2.approx.ftz.f32 %0, %1;" : "=f"(y) : "f"(x));
    return y;
}
template <int ID, int N> __device__ __forceinline__ void bar_sync() { asm volatile("bar.sync %0, %1;" ::"n"(ID), "n"(N) : "memory"); }
template <int ID, int N> __device__ __forceinline__ void bar_arrive() { asm volatile("bar.arrive %0, %1;" ::"n"(ID), "n"(N) : "memory"); }
__device__ __forceinline__ void sts128(uint32_t addr, uint32_t a, uint32_t b, uint32_t c, uint32_t d) {
    asm volatile("st.shared.v4.b32 [%0], {%1,%2,%3,%4};" ::"r"(addr), "r"(a), "r"(b), "r"(c), "r"(d) : "memory");
}
__device__ __forceinline__ void lds128(uint32_t addr, uint32_t (&r)[4]) {
    asm volatile("ld.shared.v4.b32 {%0,%1,%2,%3}, [%4];" : "=r"(r[0]), "=r"(r[1]), "=r"(r[2]), "=r"(r[3]) : "r"(addr) : "memory");
}

__device__ __forceinline__ void wgmma_ss_n256_tb(float (&d)[128], uint64_t da, uint64_t db, int sd) {
    asm volatile("{\n.reg .pred p;\nsetp.ne.b32 p, %130, 0;\n"
        "wgmma.mma_async.sync.aligned.m64n256k16.f32.bf16.bf16 "
        "{%0, %1, %2, %3, %4, %5, %6, %7, %8, %9, %10, %11, %12, %13, %14, %15, %16, %17, %18, %19, %20, %21, %22, %23, %24, %25, %26, %27, %28, %29, %30, %31, %32, %33, %34, %35, %36, %37, %38, %39, %40, %41, %42, %43, %44, %45, %46, %47, %48, %49, %50, %51, %52, %53, %54, %55, %56, %57, %58, %59, %60, %61, %62, %63, %64, %65, %66, %67, %68, %69, %70, %71, %72, %73, %74, %75, %76, %77, %78, %79, %80, %81, %82, %83, %84, %85, %86, %87, %88, %89, %90, %91, %92, %93, %94, %95, %96, %97, %98, %99, %100, %101, %102, %103, %104, %105, %106, %107, %108, %109, %110, %111, %112, %113, %114, %115, %116, %117, %118, %119, %120, %121, %122, %123, %124, %125, %126, %127}, "
        "%128, %129, p, 1, 1, 0, 1;\n}\n"
        : "+f"(d[0]), "+f"(d[1]), "+f"(d[2]), "+f"(d[3]), "+f"(d[4]), "+f"(d[5]), "+f"(d[6]), "+f"(d[7]), "+f"(d[8]), "+f"(d[9]), "+f"(d[10]), "+f"(d[11]), "+f"(d[12]), "+f"(d[13]), "+f"(d[14]), "+f"(d[15]), "+f"(d[16]), "+f"(d[17]), "+f"(d[18]), "+f"(d[19]), "+f"(d[20]), "+f"(d[21]), "+f"(d[22]), "+f"(d[23]), "+f"(d[24]), "+f"(d[25]), "+f"(d[26]), "+f"(d[27]), "+f"(d[28]), "+f"(d[29]), "+f"(d[30]), "+f"(d[31]), "+f"(d[32]), "+f"(d[33]), "+f"(d[34]), "+f"(d[35]), "+f"(d[36]), "+f"(d[37]), "+f"(d[38]), "+f"(d[39]), "+f"(d[40]), "+f"(d[41]), "+f"(d[42]), "+f"(d[43]), "+f"(d[44]), "+f"(d[45]), "+f"(d[46]), "+f"(d[47]), "+f"(d[48]), "+f"(d[49]), "+f"(d[50]), "+f"(d[51]), "+f"(d[52]), "+f"(d[53]), "+f"(d[54]), "+f"(d[55]), "+f"(d[56]), "+f"(d[57]), "+f"(d[58]), "+f"(d[59]), "+f"(d[60]), "+f"(d[61]), "+f"(d[62]), "+f"(d[63]), "+f"(d[64]), "+f"(d[65]), "+f"(d[66]), "+f"(d[67]), "+f"(d[68]), "+f"(d[69]), "+f"(d[70]), "+f"(d[71]), "+f"(d[72]), "+f"(d[73]), "+f"(d[74]), "+f"(d[75]), "+f"(d[76]), "+f"(d[77]), "+f"(d[78]), "+f"(d[79]), "+f"(d[80]), "+f"(d[81]), "+f"(d[82]), "+f"(d[83]), "+f"(d[84]), "+f"(d[85]), "+f"(d[86]), "+f"(d[87]), "+f"(d[88]), "+f"(d[89]), "+f"(d[90]), "+f"(d[91]), "+f"(d[92]), "+f"(d[93]), "+f"(d[94]), "+f"(d[95]), "+f"(d[96]), "+f"(d[97]), "+f"(d[98]), "+f"(d[99]), "+f"(d[100]), "+f"(d[101]), "+f"(d[102]), "+f"(d[103]), "+f"(d[104]), "+f"(d[105]), "+f"(d[106]), "+f"(d[107]), "+f"(d[108]), "+f"(d[109]), "+f"(d[110]), "+f"(d[111]), "+f"(d[112]), "+f"(d[113]), "+f"(d[114]), "+f"(d[115]), "+f"(d[116]), "+f"(d[117]), "+f"(d[118]), "+f"(d[119]), "+f"(d[120]), "+f"(d[121]), "+f"(d[122]), "+f"(d[123]), "+f"(d[124]), "+f"(d[125]), "+f"(d[126]), "+f"(d[127])
        : "l"(da), "l"(db), "r"(sd));
}
__device__ __forceinline__ void wgmma_rs_n128(float (&d)[64], uint32_t a0, uint32_t a1, uint32_t a2, uint32_t a3, uint64_t db, int sd) {
    asm volatile("{\n.reg .pred p;\nsetp.ne.b32 p, %69, 0;\n"
        "wgmma.mma_async.sync.aligned.m64n128k16.f32.bf16.bf16 "
        "{%0, %1, %2, %3, %4, %5, %6, %7, %8, %9, %10, %11, %12, %13, %14, %15, %16, %17, %18, %19, %20, %21, %22, %23, %24, %25, %26, %27, %28, %29, %30, %31, %32, %33, %34, %35, %36, %37, %38, %39, %40, %41, %42, %43, %44, %45, %46, %47, %48, %49, %50, %51, %52, %53, %54, %55, %56, %57, %58, %59, %60, %61, %62, %63}, "
        "{%64, %65, %66, %67}, %68, p, 1, 1, 0;\n}\n"
        : "+f"(d[0]), "+f"(d[1]), "+f"(d[2]), "+f"(d[3]), "+f"(d[4]), "+f"(d[5]), "+f"(d[6]), "+f"(d[7]), "+f"(d[8]), "+f"(d[9]), "+f"(d[10]), "+f"(d[11]), "+f"(d[12]), "+f"(d[13]), "+f"(d[14]), "+f"(d[15]), "+f"(d[16]), "+f"(d[17]), "+f"(d[18]), "+f"(d[19]), "+f"(d[20]), "+f"(d[21]), "+f"(d[22]), "+f"(d[23]), "+f"(d[24]), "+f"(d[25]), "+f"(d[26]), "+f"(d[27]), "+f"(d[28]), "+f"(d[29]), "+f"(d[30]), "+f"(d[31]), "+f"(d[32]), "+f"(d[33]), "+f"(d[34]), "+f"(d[35]), "+f"(d[36]), "+f"(d[37]), "+f"(d[38]), "+f"(d[39]), "+f"(d[40]), "+f"(d[41]), "+f"(d[42]), "+f"(d[43]), "+f"(d[44]), "+f"(d[45]), "+f"(d[46]), "+f"(d[47]), "+f"(d[48]), "+f"(d[49]), "+f"(d[50]), "+f"(d[51]), "+f"(d[52]), "+f"(d[53]), "+f"(d[54]), "+f"(d[55]), "+f"(d[56]), "+f"(d[57]), "+f"(d[58]), "+f"(d[59]), "+f"(d[60]), "+f"(d[61]), "+f"(d[62]), "+f"(d[63])
        : "r"(a0), "r"(a1), "r"(a2), "r"(a3), "l"(db), "r"(sd));
}
__device__ __forceinline__ void wgmma_rs_n128_tb(float (&d)[64], uint32_t a0, uint32_t a1, uint32_t a2, uint32_t a3, uint64_t db, int sd) {
    asm volatile("{\n.reg .pred p;\nsetp.ne.b32 p, %69, 0;\n"
        "wgmma.mma_async.sync.aligned.m64n128k16.f32.bf16.bf16 "
        "{%0, %1, %2, %3, %4, %5, %6, %7, %8, %9, %10, %11, %12, %13, %14, %15, %16, %17, %18, %19, %20, %21, %22, %23, %24, %25, %26, %27, %28, %29, %30, %31, %32, %33, %34, %35, %36, %37, %38, %39, %40, %41, %42, %43, %44, %45, %46, %47, %48, %49, %50, %51, %52, %53, %54, %55, %56, %57, %58, %59, %60, %61, %62, %63}, "
        "{%64, %65, %66, %67}, %68, p, 1, 1, 1;\n}\n"
        : "+f"(d[0]), "+f"(d[1]), "+f"(d[2]), "+f"(d[3]), "+f"(d[4]), "+f"(d[5]), "+f"(d[6]), "+f"(d[7]), "+f"(d[8]), "+f"(d[9]), "+f"(d[10]), "+f"(d[11]), "+f"(d[12]), "+f"(d[13]), "+f"(d[14]), "+f"(d[15]), "+f"(d[16]), "+f"(d[17]), "+f"(d[18]), "+f"(d[19]), "+f"(d[20]), "+f"(d[21]), "+f"(d[22]), "+f"(d[23]), "+f"(d[24]), "+f"(d[25]), "+f"(d[26]), "+f"(d[27]), "+f"(d[28]), "+f"(d[29]), "+f"(d[30]), "+f"(d[31]), "+f"(d[32]), "+f"(d[33]), "+f"(d[34]), "+f"(d[35]), "+f"(d[36]), "+f"(d[37]), "+f"(d[38]), "+f"(d[39]), "+f"(d[40]), "+f"(d[41]), "+f"(d[42]), "+f"(d[43]), "+f"(d[44]), "+f"(d[45]), "+f"(d[46]), "+f"(d[47]), "+f"(d[48]), "+f"(d[49]), "+f"(d[50]), "+f"(d[51]), "+f"(d[52]), "+f"(d[53]), "+f"(d[54]), "+f"(d[55]), "+f"(d[56]), "+f"(d[57]), "+f"(d[58]), "+f"(d[59]), "+f"(d[60]), "+f"(d[61]), "+f"(d[62]), "+f"(d[63])
        : "r"(a0), "r"(a1), "r"(a2), "r"(a3), "l"(db), "r"(sd));
}
__device__ __forceinline__ void wgmma_rs_n64_tb(float (&d)[32], uint32_t a0, uint32_t a1, uint32_t a2, uint32_t a3, uint64_t db, int sd) {
    asm volatile("{\n.reg .pred p;\nsetp.ne.b32 p, %37, 0;\n"
        "wgmma.mma_async.sync.aligned.m64n64k16.f32.bf16.bf16 "
        "{%0, %1, %2, %3, %4, %5, %6, %7, %8, %9, %10, %11, %12, %13, %14, %15, %16, %17, %18, %19, %20, %21, %22, %23, %24, %25, %26, %27, %28, %29, %30, %31}, "
        "{%32, %33, %34, %35}, %36, p, 1, 1, 1;\n}\n"
        : "+f"(d[0]), "+f"(d[1]), "+f"(d[2]), "+f"(d[3]), "+f"(d[4]), "+f"(d[5]), "+f"(d[6]), "+f"(d[7]), "+f"(d[8]), "+f"(d[9]), "+f"(d[10]), "+f"(d[11]), "+f"(d[12]), "+f"(d[13]), "+f"(d[14]), "+f"(d[15]), "+f"(d[16]), "+f"(d[17]), "+f"(d[18]), "+f"(d[19]), "+f"(d[20]), "+f"(d[21]), "+f"(d[22]), "+f"(d[23]), "+f"(d[24]), "+f"(d[25]), "+f"(d[26]), "+f"(d[27]), "+f"(d[28]), "+f"(d[29]), "+f"(d[30]), "+f"(d[31])
        : "r"(a0), "r"(a1), "r"(a2), "r"(a3), "l"(db), "r"(sd));
}

__global__ void __launch_bounds__(384, 1) fused_gqa_kernel(const __grid_constant__ Params P) {
    extern __shared__ uint8_t smem_raw[];
    const uint32_t base = (smem_u32(smem_raw) + 1023u) & ~1023u;
    const uint32_t smR = base;
    const uint32_t smS = base + R_BYTES;
    const uint32_t bars = smS + NSTAGE * STAGE_BYTES;
    const uint32_t prog = bars + 8 * (2 * NSTAGE + 10);
    const int tid = threadIdx.x;
    const int wid = __shfl_sync(0xffffffffu, tid >> 5, 0);
    const int lane = tid & 31;

    const int cta = blockIdx.x;
    const int blk = cta >> 6;
    const int hp = (cta >> 3) & 7;
    const int b = cta & 7;
    const int grp = blk * 8 + b;

    if (tid == 0) {
        TS(0);
        for (int i = 0; i < NSTAGE; i++) {
            mbar_init(bars + 8 * i, 1);
            mbar_init(bars + 8 * (NSTAGE + i), 8);
        }
        for (int i = 0; i < 10; i++) mbar_init(bars + 8 * (2 * NSTAGE + i), 4);
        asm volatile("st.volatile.shared.u32 [%0], %1;" ::"r"(prog), "r"(0) : "memory");
        asm volatile("fence.mbarrier_init.release.cluster;" ::: "memory");
        asm volatile("fence.proxy.async.shared::cta;" ::: "memory");
    }
    __syncthreads();

    if (wid >= 8) {
        asm volatile("setmaxnreg.dec.sync.aligned.u32 40;");
        if (wid == 8) {
            if (lane == 0) {
                int slot = 0, ph = 1;
                for (int s = 0; s < N_WQ; s++) {
                    const uint32_t fb = bars + 8 * slot;
                    mbar_wait(bars + 8 * (NSTAGE + slot), ph);
                    const uint32_t dst = smS + slot * STAGE_BYTES;
                    mbar_expect_tx(fb, (s & 1) ? STAGE_BYTES : STAGE_BYTES + 8192);
                    if (!(s & 1)) tma_2d(smR + ((s >> 1) & 7) * 8192, &P.x[blk], (s >> 1) * 64, b * 64, fb);
#pragma unroll
                    for (int p = 0; p < 4; p++) {
                        const int w = p >> 1, j = p & 1;
                        tma_3d(dst + p * 8192, &P.wq[blk], 0, s * 32, hp * 8 + j * 4 + w * 2, fb);
                    }
                    if (++slot == NSTAGE) { slot = 0; ph ^= 1; }
                }
                int lim = NSTAGE;
                for (int i = 0; i < 34; i++) {
                    const int u = (i >= 17), r = i - 17 * u;
                    const bool extra = (i == 28) || (i == 33);
                    const int sl = extra ? ((i == 28) ? 3 : 4) : slot;
                    const uint32_t fb = bars + 8 * sl;
                    mbar_wait(bars + 8 * (NSTAGE + sl), extra ? 1 : ph);
                    const uint32_t dst = smS + sl * STAGE_BYTES;
                    mbar_expect_tx(fb, STAGE_BYTES);
                    if (r < 8) {
                        const int row = (b * kHkv + hp * 2 + u) * kSk + (r >> 1) * 128;
                        tma_3d(dst, (r & 1) ? &P.v[blk] : &P.k[blk], 0, row, 0, fb);
                    } else {
                        const int q = r - 8, row = hp * 512 + u * 256;
                        if (q < 8) {
                            tma_3d(dst, &P.wo[blk], 0, row + (q & 3) * 64, (q >> 2) * 4, fb);
                            tma_3d(dst + 16384, &P.wo[blk], 0, row + ((q & 3) ^ 2) * 64, (q >> 2) * 4 + 2, fb);
                        } else {
                            tma_2d(dst, &P.wo8[blk], 512, row, fb);
                            tma_2d(dst + 16384, &P.wo8[blk], 512, row + 128, fb);
                        }
                    }
                    asm volatile("st.volatile.shared.u32 [%0], %1;" ::"r"(prog), "r"(i + 1) : "memory");
                    if (i == 7) lim = 3;
                    if (!extra && ++slot == lim) { slot = 0; ph ^= 1; }
                }
            }
        } else if (wid == 11) {
            if (PF_DIST > 0) {
                uint32_t sink = 0;
                mbar_wait(bars, 0);
                if (PF_WQ) {
                    const char* wqs = (const char*)(P.wqp[blk] + hp * 512) + (size_t)(160 + b * 52) * 8192;
#pragma unroll
                    for (int h = 0; h < 2; h++) {
#pragma unroll
                        for (int j = 0; j < 4; j++) {
                            const int e = (h * 4 + j) * 32 + lane;
                            if (e < 208) sink |= l2_touch(wqs + (size_t)(e >> 2) * 8192 + (e & 3) * 256);
                        }
                        if (sink == 0x9E3779B9u) asm volatile("st.volatile.shared.u32 [%0], %1;" ::"r"(prog + 4), "r"(sink) : "memory");
                    }
                }
                const char* kbase = (const char*)(P.kp[blk] + (size_t)(b * kHkv + hp * 2) * kSk * kDh);
                const char* vbase = (const char*)(P.vp[blk] + (size_t)(b * kHkv + hp * 2) * kSk * kDh);
                const char* wos = (const char*)(P.wop[blk] + (size_t)hp * 512 * kD) + (size_t)b * 36864;
                for (int i = 0; i < 18; i++) {
                    const int u = (i >= 9), r = i - 9 * u;
                    const int pos = u ? (PF_POS1 + r) : r;
                    if (pos >= PF_DIST) {
                        uint32_t pr, n = 0;
                        while (true) {
                            asm volatile("ld.volatile.shared.u32 %0, [%1];" : "=r"(pr) : "r"(prog) : "memory");
                            const int prk = ((int)pr <= 8) ? (int)pr : (((int)pr <= 17) ? 8 + (((int)pr - 8) * (PF_POS1 - 8)) / 9 : (int)pr - 17 + PF_POS1);
                            if (prk + PF_DIST >= pos) break;
                            if (++n > (1u << 22)) break;
                            __nanosleep(100);
                        }
                    }
                    if (r < 8) {
                        const char* p = ((r & 1) ? vbase : kbase) + (size_t)(u * 4 + (r >> 1)) * 32768 + lane * 256;
#pragma unroll
                        for (int j = 0; j < 4; j++) sink |= l2_touch(p + j * 8192);
                    } else {
                        const char* p = wos + (size_t)u * 294912 + lane * 256;
#pragma unroll
                        for (int j = 0; j < 5; j++) if (j * 32 + lane < 144) sink |= l2_touch(p + j * 8192);
                    }
                    if (sink == 0x9E3779B9u) asm volatile("st.volatile.shared.u32 [%0], %1;" ::"r"(prog + 4), "r"(sink) : "memory");
                }
            }
        } else {
            const int hw = wid - 9;
            for (int k = 0; k < 3; k++) {
                mbar_wait(bars + 8 * (2 * NSTAGE + hw * 5 + k), 0);
                const int c = (k < 2) ? (2 * k + hw) : 4;
                asm volatile("fence.acq_rel.gpu;" ::: "memory");
                asm volatile("red.relaxed.gpu.global.add.u32 [%0], 1;" ::"l"(&g_cnt[(grp * 9 + c) * 32 + lane]) : "memory");
            }
        }
    } else {
        asm volatile("setmaxnreg.inc.sync.aligned.u32 232;");
        const int w = wid >> 2;
        const int t = tid & 127;
        int slot = 0, ph = 0, lim = NSTAGE;
        uint32_t qf[8][4];
        const uint32_t stash = smR + (1 + w) * 16384 + t * 16;
        {
            float acc[128];
            int pslot = 0;
            for (int s = 0; s < N_WQ; s++) {
                mbar_wait(bars + 8 * slot, ph);
                if (tid == 0 && s == 0) TS(20);
                if (tid == 0 && s == 5) TS(21);
                if (tid == 0 && s == 10) TS(22);
                const uint64_t da = mk_desc(smR + ((s >> 1) & 7) * 8192 + (s & 1) * 64, 16, 1024);
                const uint64_t db = mk_desc(smS + slot * STAGE_BYTES + w * 16384, 4096, 1024);
                wg_fence();
                wgmma_ss_n256_tb(acc, da, db, s != 0);
                wgmma_ss_n256_tb(acc, da + 2, db + 128, 1);
                wg_commit();
                wg_wait<0>();
                if (lane == 0) mbar_arrive(bars + 8 * (NSTAGE + slot));
                pslot = slot;
                if (++slot == NSTAGE) { slot = 0; ph ^= 1; }
            }
            fence_regs(acc);
            if (tid == 0) TS(1);
#pragma unroll
            for (int kk = 0; kk < 8; kk++) {
#pragma unroll
                for (int i = 0; i < 4; i++) qf[kk][i] = pack_bf16(acc[8 * kk + 2 * i], acc[8 * kk + 2 * i + 1]);
                sts128(stash + kk * 2048,
                       pack_bf16(acc[64 + 8 * kk + 0], acc[64 + 8 * kk + 1]), pack_bf16(acc[64 + 8 * kk + 2], acc[64 + 8 * kk + 3]),
                       pack_bf16(acc[64 + 8 * kk + 4], acc[64 + 8 * kk + 5]), pack_bf16(acc[64 + 8 * kk + 6], acc[64 + 8 * kk + 7]));
            }
        }
        if (w == 1) bar_arrive<5, 256>();
        const float sc = 0.08838834764831845f * 1.4426950408889634f;
        uint2* dst0 = g_part + (size_t)(grp * 80 + 2 * w * 8 + hp) * 1024 + t;
        uint2* dst8 = g_part + (size_t)(grp * 80 + 64 + hp * 2 + w) * 1024 + t;
#pragma unroll
        for (int u = 0; u < 2; u++) {
            uint32_t af[16][4];
            {
                float o[64], s[64];
                float m0 = -INFINITY, m1 = -INFINITY, l0 = 0.f, l1 = 0.f;
                uint32_t pf[8][4];
#pragma unroll
                for (int i = 0; i < 64; i++) { o[i] = 0.f; s[i] = 0.f; }
#pragma unroll
                for (int i = 0; i < 32; i++) pf[i >> 2][i & 3] = 0u;
#pragma unroll 1
                for (int tt = 0; tt <= 4; tt++) {
                    int vslot = slot;
                    if (tt > 0) {
                        mbar_wait(bars + 8 * slot, ph);
                        if (++slot == lim) { slot = 0; ph ^= 1; }
                    }
                    if (tt < 4) mbar_wait(bars + 8 * slot, ph);
                    if (tid == 0) TS(32 + u * 20 + tt * 4);
                    if (w == 0) bar_sync<5, 256>(); else bar_sync<6, 256>();
                    wg_fence();
                    if (tt > 0) {
                        const uint64_t db = mk_desc(smS + vslot * STAGE_BYTES, 16384, 1024);
#pragma unroll
                        for (int kk = 0; kk < 8; kk++)
                            wgmma_rs_n128_tb(o, pf[kk][0], pf[kk][1], pf[kk][2], pf[kk][3], db + kk * 128, (tt > 1) || (kk != 0));
                        wg_commit();
                    }
                    if (tt < 4) {
                        const uint64_t db = mk_desc(smS + slot * STAGE_BYTES, 16, 1024);
#pragma unroll
                        for (int kk = 0; kk < 8; kk++)
                            wgmma_rs_n128(s, qf[kk][0], qf[kk][1], qf[kk][2], qf[kk][3], db + (kk >> 2) * 1024 + (kk & 3) * 2, kk != 0);
                        wg_commit();
                    }
                    if (w == 0) bar_arrive<6, 256>(); else if (!(u == 1 && tt == 4)) bar_arrive<5, 256>();
                    if (tid == 0) TS(32 + u * 20 + tt * 4 + 1);
                    wg_wait<0>();
                    fence_regs(o);
                    fence_regs(s);
                    if (tid == 0) TS(32 + u * 20 + tt * 4 + 2);
                    if (tt > 0 && lane == 0) mbar_arrive(bars + 8 * (NSTAGE + vslot));
                    if (tt == 4) break;
                    if (lane == 0) mbar_arrive(bars + 8 * (NSTAGE + slot));
                    if (++slot == lim) { slot = 0; ph ^= 1; }
                    float mx0 = s[0], mx1 = s[2];
#pragma unroll
                    for (int j = 0; j < 16; j++) {
                        mx0 = fmaxf(mx0, fmaxf(s[4 * j], s[4 * j + 1]));
                        mx1 = fmaxf(mx1, fmaxf(s[4 * j + 2], s[4 * j + 3]));
                    }
                    mx0 = fmaxf(mx0, __shfl_xor_sync(0xffffffffu, mx0, 1));
                    mx1 = fmaxf(mx1, __shfl_xor_sync(0xffffffffu, mx1, 1));
                    mx0 = fmaxf(mx0, __shfl_xor_sync(0xffffffffu, mx0, 2));
                    mx1 = fmaxf(mx1, __shfl_xor_sync(0xffffffffu, mx1, 2));
                    const float mn0 = fmaxf(m0, mx0), mn1 = fmaxf(m1, mx1);
                    const float al0 = ex2((m0 - mn0) * sc), al1 = ex2((m1 - mn1) * sc);
                    m0 = mn0; m1 = mn1;
                    const float ms0 = mn0 * sc, ms1 = mn1 * sc;
                    float rs0 = 0.f, rs1 = 0.f;
#pragma unroll
                    for (int j = 0; j < 16; j++) {
                        const float p0 = ex2(fmaf(s[4 * j], sc, -ms0)), p1 = ex2(fmaf(s[4 * j + 1], sc, -ms0));
                        const float p2 = ex2(fmaf(s[4 * j + 2], sc, -ms1)), p3 = ex2(fmaf(s[4 * j + 3], sc, -ms1));
                        rs0 += p0 + p1; rs1 += p2 + p3;
                        pf[j >> 1][(j & 1) * 2] = pack_bf16(p0, p1);
                        pf[j >> 1][(j & 1) * 2 + 1] = pack_bf16(p2, p3);
                    }
                    l0 = l0 * al0 + rs0; l1 = l1 * al1 + rs1;
                    if (tt > 0) {
#pragma unroll
                        for (int j = 0; j < 16; j++) { o[4 * j] *= al0; o[4 * j + 1] *= al0; o[4 * j + 2] *= al1; o[4 * j + 3] *= al1; }
                    }
                    if (tid == 0) TS(32 + u * 20 + tt * 4 + 3);
                }
                if (tid == 0) TS(2 + u);
                l0 += __shfl_xor_sync(0xffffffffu, l0, 1);
                l1 += __shfl_xor_sync(0xffffffffu, l1, 1);
                l0 += __shfl_xor_sync(0xffffffffu, l0, 2);
                l1 += __shfl_xor_sync(0xffffffffu, l1, 2);
                const float i0 = 1.f / l0, i1 = 1.f / l1;
                const uint32_t zown = smR + (w ? 3 : 0) * 16384 + t * 16;
#pragma unroll
                for (int kk = 0; kk < 8; kk++) {
                    af[kk][0] = pack_bf16(o[8 * kk + 0] * i0, o[8 * kk + 1] * i0);
                    af[kk][1] = pack_bf16(o[8 * kk + 2] * i1, o[8 * kk + 3] * i1);
                    af[kk][2] = pack_bf16(o[8 * kk + 4] * i0, o[8 * kk + 5] * i0);
                    af[kk][3] = pack_bf16(o[8 * kk + 6] * i1, o[8 * kk + 7] * i1);
                    sts128(zown + kk * 2048, af[kk][0], af[kk][1], af[kk][2], af[kk][3]);
                }
            }
            if (w == 0) bar_arrive<7, 256>(); else bar_arrive<8, 256>();
            lim = 3;
            if (u == 0) {
#pragma unroll
                for (int kk = 0; kk < 8; kk++) lds128(stash + kk * 2048, qf[kk]);
            }
            uint32_t nx[8][4];
#pragma unroll
            for (int ps = 0; ps < 2; ps++) {
                float acc[64];
                const uint32_t keep = smS + (3 + ps) * STAGE_BYTES + w * 16384 + t * 16;
                if (u == 0) {
#pragma unroll
                    for (int i = 0; i < 64; i++) acc[i] = 0.f;
                } else {
                    if (ps == 0) {
#pragma unroll
                        for (int j = 0; j < 8; j++) lds128(keep + j * 2048, nx[j]);
                        asm volatile("fence.proxy.async.shared::cta;" ::: "memory");
                        __syncwarp();
                        if (lane == 0) mbar_arrive(bars + 8 * (NSTAGE + 3));
                    }
#pragma unroll
                    for (int j = 0; j < 8; j++)
#pragma unroll
                        for (int i = 0; i < 4; i++) { acc[8 * j + 2 * i] = __uint_as_float(nx[j][i] << 16); acc[8 * j + 2 * i + 1] = __uint_as_float(nx[j][i] & 0xffff0000u); }
                }
#pragma unroll
                for (int st = 0; st < 4; st++) {
                    if (ps == 0 && st == 2) {
                        if (w == 0) bar_sync<8, 256>(); else bar_sync<7, 256>();
#pragma unroll
                        for (int kk = 0; kk < 8; kk++) lds128(smR + (w ? 0 : 3) * 16384 + kk * 2048 + t * 16, af[8 + kk]);
                    }
                    const bool extra = (u == 1) && (ps == 0 && st == 3);
                    const int sl = extra ? (3 + ps) : slot;
                    if (tid == 0) TS(80 + u * 24 + (ps * 4 + st) * 3);
                    mbar_wait(bars + 8 * sl, extra ? 1 : ph);
                    if (tid == 0) TS(80 + u * 24 + (ps * 4 + st) * 3 + 1);
                    const uint64_t db = mk_desc(smS + sl * STAGE_BYTES + w * 16384, 8192, 1024);
                    wg_fence();
#pragma unroll
                    for (int kk = 0; kk < 4; kk++)
                        wgmma_rs_n128_tb(acc, af[st * 4 + kk][0], af[st * 4 + kk][1], af[st * 4 + kk][2], af[st * 4 + kk][3], db + kk * 128, 1);
                    wg_commit();
                    if (u == 1 && st == 1) {
                        if (ps == 0) {
#pragma unroll
                            for (int j = 0; j < 8; j++) lds128(keep + STAGE_BYTES + j * 2048, nx[j]);
                            asm volatile("fence.proxy.async.shared::cta;" ::: "memory");
                            __syncwarp();
                            if (lane == 0) mbar_arrive(bars + 8 * (NSTAGE + 4));
                        } else {
#pragma unroll
                            for (int j = 0; j < 4; j++) lds128(stash + j * 2048, nx[j]);
                        }
                    }
                    wg_wait<0>();
                    if (tid == 0) TS(80 + u * 24 + (ps * 4 + st) * 3 + 2);
                    if (!extra) {
                        if (lane == 0) mbar_arrive(bars + 8 * (NSTAGE + slot));
                        if (++slot == 3) { slot = 0; ph ^= 1; }
                    }
                }
                fence_regs(acc);
                if (u == 0) {
#pragma unroll
                    for (int j = 0; j < 8; j++)
                        sts128(keep + j * 2048, pack_bf16(acc[8 * j], acc[8 * j + 1]), pack_bf16(acc[8 * j + 2], acc[8 * j + 3]),
                               pack_bf16(acc[8 * j + 4], acc[8 * j + 5]), pack_bf16(acc[8 * j + 6], acc[8 * j + 7]));
                } else {
                    uint2* dst = dst0 + (size_t)ps * 32 * 1024;
#pragma unroll
                    for (int j = 0; j < 16; j++)
                        __stcg(dst + (j >> 3) * 8192 + (j & 7) * 128, make_uint2(pack_bf16(acc[4 * j], acc[4 * j + 1]), pack_bf16(acc[4 * j + 2], acc[4 * j + 3])));
                    __syncwarp();
                    if (lane == 0) mbar_arrive(bars + 8 * (2 * NSTAGE + w * 5 + ps));
                }
                if (tid == 0) TS(4 + u * 8 + ps);
            }
            {
                float acc[32];
                if (u == 0) {
#pragma unroll
                    for (int i = 0; i < 32; i++) acc[i] = 0.f;
                } else {
#pragma unroll
                    for (int j = 0; j < 4; j++)
#pragma unroll
                        for (int i = 0; i < 4; i++) { acc[8 * j + 2 * i] = __uint_as_float(nx[j][i] << 16); acc[8 * j + 2 * i + 1] = __uint_as_float(nx[j][i] & 0xffff0000u); }
                }
                const int sl = u ? 4 : slot;
                mbar_wait(bars + 8 * sl, u ? 1 : ph);
                const uint64_t db = mk_desc(smS + sl * STAGE_BYTES + w * 16384, 8192, 1024);
                wg_fence();
#pragma unroll
                for (int kk = 0; kk < 8; kk++)
                    wgmma_rs_n64_tb(acc, af[kk][0], af[kk][1], af[kk][2], af[kk][3], db + kk * 128, 1);
                wg_commit();
                wg_wait<0>();
                if (u == 0) {
                    if (lane == 0) mbar_arrive(bars + 8 * (NSTAGE + slot));
                    if (++slot == 3) { slot = 0; ph ^= 1; }
                }
                fence_regs(acc);
                if (u == 0) {
#pragma unroll
                    for (int j = 0; j < 4; j++)
                        sts128(stash + j * 2048, pack_bf16(acc[8 * j], acc[8 * j + 1]), pack_bf16(acc[8 * j + 2], acc[8 * j + 3]),
                               pack_bf16(acc[8 * j + 4], acc[8 * j + 5]), pack_bf16(acc[8 * j + 6], acc[8 * j + 7]));
                } else {
#pragma unroll
                    for (int j = 0; j < 8; j++)
                        __stcg(dst8 + j * 128, make_uint2(pack_bf16(acc[4 * j], acc[4 * j + 1]), pack_bf16(acc[4 * j + 2], acc[4 * j + 3])));
                    __syncwarp();
                    if (lane == 0) mbar_arrive(bars + 8 * (2 * NSTAGE + w * 5 + 2));
                }
                if (tid == 0) TS(6 + u * 8);
            }
        }
        {
            const int nch = (w == 0) ? 3 : 2;
            if (lane < nch) {
                const int c = (lane < 2) ? (2 * lane + w) : 4;
                const unsigned need = (lane < 2) ? 8u : 16u;
                unsigned* cp = &g_cnt[(grp * 9 + c) * 32 + hp * 4 + (wid & 3)];
                unsigned v, n = 0;
                while (true) {
                    asm volatile("ld.acquire.gpu.global.u32 %0, [%1];" : "=r"(v) : "l"(cp) : "memory");
                    if (v >= need) break;
                    if (++n > (1u << 21)) break;
                }
                *cp = 0;
            }
            __syncwarp();
            if (tid == 0) TS(18);
            __nv_bfloat16* orow = P.out + (size_t)(b * 64 + (t >> 5) * 16 + (lane >> 2)) * (2 * kD) + blk * kD + hp * 8 + (lane & 3) * 2;
            const uint2* src = g_part + ((size_t)(grp * 80 + 2 * w * 8) * 8 + hp) * 128 + t;
            uint2 v[4][8];
#pragma unroll
            for (int k = 0; k < 4; k++)
#pragma unroll
                for (int i = 0; i < 8; i++) v[k][i] = __ldcg(src + (size_t)((k >> 1) * 32 + (k & 1) * 8 + i) * 1024);
            if (w == 0) {
                const uint2* src8 = g_part + ((size_t)(grp * 80 + 64) * 8 + hp) * 128 + t;
                uint2 u[16];
#pragma unroll
                for (int i = 0; i < 16; i++) u[i] = __ldcg(src8 + (size_t)i * 1024);
                float a0 = 0.f, a1 = 0.f, a2 = 0.f, a3 = 0.f;
#pragma unroll
                for (int i = 0; i < 16; i++) {
                    a0 += __uint_as_float(u[i].x << 16); a1 += __uint_as_float(u[i].x & 0xffff0000u);
                    a2 += __uint_as_float(u[i].y << 16); a3 += __uint_as_float(u[i].y & 0xffff0000u);
                }
                *(uint32_t*)(orow + 512) = pack_bf16(a0, a1);
                *(uint32_t*)(orow + 512 + 8 * 2 * kD) = pack_bf16(a2, a3);
            }
#pragma unroll
            for (int k = 0; k < 4; k++) {
                float a0 = 0.f, a1 = 0.f, a2 = 0.f, a3 = 0.f;
#pragma unroll
                for (int i = 0; i < 8; i++) {
                    a0 += __uint_as_float(v[k][i].x << 16); a1 += __uint_as_float(v[k][i].x & 0xffff0000u);
                    a2 += __uint_as_float(v[k][i].y << 16); a3 += __uint_as_float(v[k][i].y & 0xffff0000u);
                }
                *(uint32_t*)(orow + ((k >> 1) * 4 + 2 * w + (k & 1)) * 64) = pack_bf16(a0, a1);
                *(uint32_t*)(orow + ((k >> 1) * 4 + 2 * w + (k & 1)) * 64 + 8 * 2 * kD) = pack_bf16(a2, a3);
            }
            if (tid == 0) TS(19);
        }
    }
}

typedef CUresult (*EncodeFn)(CUtensorMap*, CUtensorMapDataType, cuuint32_t, void*, const cuuint64_t*, const cuuint64_t*,
                             const cuuint32_t*, const cuuint32_t*, CUtensorMapInterleave, CUtensorMapSwizzle,
                             CUtensorMapL2promotion, CUtensorMapFloatOOBfill);

void make_map(EncodeFn fn, CUtensorMap* m, const void* ptr, uint64_t cols, uint64_t rows, uint32_t box_rows) {
    cuuint64_t dims[2] = {cols, rows};
    cuuint64_t strides[1] = {cols * 2};
    cuuint32_t box[2] = {64, box_rows};
    cuuint32_t es[2] = {1, 1};
    fn(m, CU_TENSOR_MAP_DATA_TYPE_BFLOAT16, 2, const_cast<void*>(ptr), dims, strides, box, es, CU_TENSOR_MAP_INTERLEAVE_NONE,
       CU_TENSOR_MAP_SWIZZLE_128B, CU_TENSOR_MAP_L2_PROMOTION_L2_256B, CU_TENSOR_MAP_FLOAT_OOB_FILL_NONE);
}

void make_map3(EncodeFn fn, CUtensorMap* m, const void* ptr, uint64_t cols, uint64_t rows, uint32_t box_rows, uint32_t box_groups) {
    cuuint64_t dims[3] = {64, rows, cols / 64};
    cuuint64_t strides[2] = {cols * 2, 128};
    cuuint32_t box[3] = {64, box_rows, box_groups};
    cuuint32_t es[3] = {1, 1, 1};
    fn(m, CU_TENSOR_MAP_DATA_TYPE_BFLOAT16, 3, const_cast<void*>(ptr), dims, strides, box, es, CU_TENSOR_MAP_INTERLEAVE_NONE,
       CU_TENSOR_MAP_SWIZZLE_128B, CU_TENSOR_MAP_L2_PROMOTION_L2_256B, CU_TENSOR_MAP_FLOAT_OOB_FILL_NONE);
}

}

extern "C" void kernel_launch(void* const* d_in, const int* in_sizes, int n_in, void* d_out, int out_size) {
    static EncodeFn enc = nullptr;
    if (!enc) {
        void* fn = nullptr;
        cudaDriverEntryPointQueryResult st;
        cudaGetDriverEntryPoint("cuTensorMapEncodeTiled", &fn, cudaEnableDefault, &st);
        enc = (EncodeFn)fn;
        cudaFuncSetAttribute(fused_gqa_kernel, cudaFuncAttributeMaxDynamicSharedMemorySize, SMEM_BYTES);
    }
    Params P;
    for (int blk = 0; blk < 2; blk++) {
        const void* x = d_in[blk * 5 + 0];
        const void* k = d_in[blk * 5 + 1];
        const void* v = d_in[blk * 5 + 2];
        const void* wq = d_in[blk * 5 + 3];
        const void* wo = d_in[blk * 5 + 4];
        make_map(enc, &P.x[blk], x, kD, kB * kSq, 64);
        make_map3(enc, &P.wq[blk], wq, kHq * kDh, kD, 32, 2);
        make_map3(enc, &P.k[blk], k, kDh, (uint64_t)kB * kHkv * kSk, 128, 2);
        make_map3(enc, &P.v[blk], v, kDh, (uint64_t)kB * kHkv * kSk, 128, 2);
        make_map3(enc, &P.wo[blk], wo, kD, kHq * kDh, 64, 2);
        make_map(enc, &P.wo8[blk], wo, kD, kHq * kDh, 128);
        P.wqp[blk] = (const __nv_bfloat16*)wq;
        P.kp[blk] = (const __nv_bfloat16*)k;
        P.vp[blk] = (const __nv_bfloat16*)v;
        P.wop[blk] = (const __nv_bfloat16*)wo;
    }
    P.out = (__nv_bfloat16*)d_out;
    fused_gqa_kernel<<<128, 384, SMEM_BYTES>>>(P);
}
```

```cpp
#include <cuda_runtime.h>
#include <cuda_bf16.h>
#include <cuda.h>
#include <stdint.h>

namespace {

constexpr int kB = 8, kSq = 64, kD = 576, kHq = 32, kHkv = 16, kSk = 512, kDh = 128;
constexpr int NSTAGE = 5;
constexpr int STAGE_BYTES = 32768;
constexpr int R_BYTES = 65536;
constexpr int SMEM_BYTES = R_BYTES + NSTAGE * STAGE_BYTES + 1024   + 256  ;
constexpr int N_WQ = 18;
#define PF_DIST_V 6
#define OP_WAIT0 1
#define QP_WAIT0 1
#define PF_POS1 9
#define PF_START 1
#define PF_WQ 0
#define PF_SLEEP 1000
constexpr int PF_DIST = PF_DIST_V;

struct __align__(64) Params {
    CUtensorMap x[2], wq[2], k[2], v[2], wo[2], wo8[2];
    const __nv_bfloat16* wqp[2];
    const __nv_bfloat16* kp[2];
    const __nv_bfloat16* vp[2];
    const __nv_bfloat16* wop[2];
    __nv_bfloat16* out;
};

__device__ uint2 g_part[16 * 80 * 8 * 128];
__device__ unsigned int g_cnt[16 * 9 * 32];
#define TS(k) do {} while (0)

__device__ __forceinline__ uint32_t smem_u32(const void* p) { return (uint32_t)__cvta_generic_to_shared(p); }
__device__ __forceinline__ void mbar_init(uint32_t bar, int cnt) {
    asm volatile("mbarrier.init.shared::cta.b64 [%0], %1;" ::"r"(bar), "r"(cnt));
}
__device__ __forceinline__ void mbar_expect_tx(uint32_t bar, uint32_t bytes) {
    asm volatile("mbarrier.arrive.expect_tx.shared::cta.b64 _, [%0], %1;" ::"r"(bar), "r"(bytes) : "memory");
}
__device__ __forceinline__ void mbar_arrive(uint32_t bar) {
    asm volatile("mbarrier.arrive.shared::cta.b64 _, [%0];" ::"r"(bar) : "memory");
}
__device__ __forceinline__ bool mbar_try(uint32_t bar, uint32_t parity) {
    uint32_t ok;
    asm volatile("{\n.reg .pred p;\nmbarrier.try_wait.parity.shared::cta.b64 p, [%1], %2;\nselp.u32 %0, 1, 0, p;\n}\n"
                 : "=r"(ok) : "r"(bar), "r"(parity) : "memory");
    return ok != 0;
}
__device__ __forceinline__ void mbar_wait(uint32_t bar, uint32_t parity) {
    if (mbar_try(bar, parity)) return;
    uint32_t n = 0;
    while (!mbar_try(bar, parity)) {
        if (++n > (1u << 20)) break;
    }
}
__device__ __forceinline__ void tma_2d(uint32_t dst, const CUtensorMap* tm, int c0, int c1, uint32_t bar) {
    asm volatile("cp.async.bulk.tensor.2d.shared::cluster.global.mbarrier::complete_tx::bytes [%0], [%1, {%3, %4}], [%2];"
                 ::"r"(dst), "l"(tm), "r"(bar), "r"(c0), "r"(c1) : "memory");
}
__device__ __forceinline__ void tma_3d(uint32_t dst, const CUtensorMap* tm, int c0, int c1, int c2, uint32_t bar) {
    asm volatile("cp.async.bulk.tensor.3d.shared::cluster.global.mbarrier::complete_tx::bytes [%0], [%1, {%3, %4, %5}], [%2];"
                 ::"r"(dst), "l"(tm), "r"(bar), "r"(c0), "r"(c1), "r"(c2) : "memory");
}
__device__ __forceinline__ void l2_prefetch(const void* p, uint32_t bytes) {
    asm volatile("cp.async.bulk.prefetch.L2.global [%0], %1;" ::"l"(p), "r"(bytes) : "memory");
}
__device__ __forceinline__ uint32_t l2_touch(const void* p) {
    uint32_t v;
    asm volatile("ld.global.L2::256B.b32 %0, [%1];" : "=r"(v) : "l"(p) : "memory");
    return v;
}
__device__ __forceinline__ void wg_fence() { asm volatile("wgmma.fence.sync.aligned;" ::: "memory"); }
__device__ __forceinline__ void wg_commit() { asm volatile("wgmma.commit_group.sync.aligned;" ::: "memory"); }
template <int N> __device__ __forceinline__ void wg_wait() { asm volatile("wgmma.wait_group.sync.aligned %0;" ::"n"(N) : "memory"); }
template <int N> __device__ __forceinline__ void fence_regs(float (&d)[N]) {
#pragma unroll
    for (int i = 0; i < N; i++) asm volatile("" : "+f"(d[i])::"memory");
}
__device__ __forceinline__ uint64_t mk_desc(uint32_t addr, uint32_t lbo, uint32_t sbo) {
    return (uint64_t)((addr & 0x3FFFF) >> 4) | ((uint64_t)(lbo >> 4) << 16) | ((uint64_t)(sbo >> 4) << 32) | (1ull << 62);
}
__device__ __forceinline__ uint32_t pack_bf16(float a, float b) {
    uint32_t r;
    asm("cvt.rn.bf16x2.f32 %0, %1, %2;" : "=r"(r) : "f"(b), "f"(a));
    return r;
}
__device__ __forceinline__ float ex2(float x) {
    float y;
    asm("ex2.approx.ftz.f32 %0, %1;" : "=f"(y) : "f"(x));
    return y;
}
template <int ID, int N> __device__ __forceinline__ void bar_sync() { asm volatile("bar.sync %0, %1;" ::"n"(ID), "n"(N) : "memory"); }
template <int ID, int N> __device__ __forceinline__ void bar_arrive() { asm volatile("bar.arrive %0, %1;" ::"n"(ID), "n"(N) : "memory"); }
__device__ __forceinline__ void sts128(uint32_t addr, uint32_t a, uint32_t b, uint32_t c, uint32_t d) {
    asm volatile("st.shared.v4.b32 [%0], {%1,%2,%3,%4};" ::"r"(addr), "r"(a), "r"(b), "r"(c), "r"(d) : "memory");
}
__device__ __forceinline__ void lds128(uint32_t addr, uint32_t (&r)[4]) {
    asm volatile("ld.shared.v4.b32 {%0,%1,%2,%3}, [%4];" : "=r"(r[0]), "=r"(r[1]), "=r"(r[2]), "=r"(r[3]) : "r"(addr) : "memory");
}

__device__ __forceinline__ void wgmma_ss_n256_tb(float (&d)[128], uint64_t da, uint64_t db, int sd) {
    asm volatile("{\n.reg .pred p;\nsetp.ne.b32 p, %130, 0;\n"
        "wgmma.mma_async.sync.aligned.m64n256k16.f32.bf16.bf16 "
        "{%0, %1, %2, %3, %4, %5, %6, %7, %8, %9, %10, %11, %12, %13, %14, %15, %16, %17, %18, %19, %20, %21, %22, %23, %24, %25, %26, %27, %28, %29, %30, %31, %32, %33, %34, %35, %36, %37, %38, %39, %40, %41, %42, %43, %44, %45, %46, %47, %48, %49, %50, %51, %52, %53, %54, %55, %56, %57, %58, %59, %60, %61, %62, %63, %64, %65, %66, %67, %68, %69, %70, %71, %72, %73, %74, %75, %76, %77, %78, %79, %80, %81, %82, %83, %84, %85, %86, %87, %88, %89, %90, %91, %92, %93, %94, %95, %96, %97, %98, %99, %100, %101, %102, %103, %104, %105, %106, %107, %108, %109, %110, %111, %112, %113, %114, %115, %116, %117, %118, %119, %120, %121, %122, %123, %124, %125, %126, %127}, "
        "%128, %129, p, 1, 1, 0, 1;\n}\n"
        : "+f"(d[0]), "+f"(d[1]), "+f"(d[2]), "+f"(d[3]), "+f"(d[4]), "+f"(d[5]), "+f"(d[6]), "+f"(d[7]), "+f"(d[8]), "+f"(d[9]), "+f"(d[10]), "+f"(d[11]), "+f"(d[12]), "+f"(d[13]), "+f"(d[14]), "+f"(d[15]), "+f"(d[16]), "+f"(d[17]), "+f"(d[18]), "+f"(d[19]), "+f"(d[20]), "+f"(d[21]), "+f"(d[22]), "+f"(d[23]), "+f"(d[24]), "+f"(d[25]), "+f"(d[26]), "+f"(d[27]), "+f"(d[28]), "+f"(d[29]), "+f"(d[30]), "+f"(d[31]), "+f"(d[32]), "+f"(d[33]), "+f"(d[34]), "+f"(d[35]), "+f"(d[36]), "+f"(d[37]), "+f"(d[38]), "+f"(d[39]), "+f"(d[40]), "+f"(d[41]), "+f"(d[42]), "+f"(d[43]), "+f"(d[44]), "+f"(d[45]), "+f"(d[46]), "+f"(d[47]), "+f"(d[48]), "+f"(d[49]), "+f"(d[50]), "+f"(d[51]), "+f"(d[52]), "+f"(d[53]), "+f"(d[54]), "+f"(d[55]), "+f"(d[56]), "+f"(d[57]), "+f"(d[58]), "+f"(d[59]), "+f"(d[60]), "+f"(d[61]), "+f"(d[62]), "+f"(d[63]), "+f"(d[64]), "+f"(d[65]), "+f"(d[66]), "+f"(d[67]), "+f"(d[68]), "+f"(d[69]), "+f"(d[70]), "+f"(d[71]), "+f"(d[72]), "+f"(d[73]), "+f"(d[74]), "+f"(d[75]), "+f"(d[76]), "+f"(d[77]), "+f"(d[78]), "+f"(d[79]), "+f"(d[80]), "+f"(d[81]), "+f"(d[82]), "+f"(d[83]), "+f"(d[84]), "+f"(d[85]), "+f"(d[86]), "+f"(d[87]), "+f"(d[88]), "+f"(d[89]), "+f"(d[90]), "+f"(d[91]), "+f"(d[92]), "+f"(d[93]), "+f"(d[94]), "+f"(d[95]), "+f"(d[96]), "+f"(d[97]), "+f"(d[98]), "+f"(d[99]), "+f"(d[100]), "+f"(d[101]), "+f"(d[102]), "+f"(d[103]), "+f"(d[104]), "+f"(d[105]), "+f"(d[106]), "+f"(d[107]), "+f"(d[108]), "+f"(d[109]), "+f"(d[110]), "+f"(d[111]), "+f"(d[112]), "+f"(d[113]), "+f"(d[114]), "+f"(d[115]), "+f"(d[116]), "+f"(d[117]), "+f"(d[118]), "+f"(d[119]), "+f"(d[120]), "+f"(d[121]), "+f"(d[122]), "+f"(d[123]), "+f"(d[124]), "+f"(d[125]), "+f"(d[126]), "+f"(d[127])
        : "l"(da), "l"(db), "r"(sd));
}
__device__ __forceinline__ void wgmma_rs_n128(float (&d)[64], uint32_t a0, uint32_t a1, uint32_t a2, uint32_t a3, uint64_t db, int sd) {
    asm volatile("{\n.reg .pred p;\nsetp.ne.b32 p, %69, 0;\n"
        "wgmma.mma_async.sync.aligned.m64n128k16.f32.bf16.bf16 "
        "{%0, %1, %2, %3, %4, %5, %6, %7, %8, %9, %10, %11, %12, %13, %14, %15, %16, %17, %18, %19, %20, %21, %22, %23, %24, %25, %26, %27, %28, %29, %30, %31, %32, %33, %34, %35, %36, %37, %38, %39, %40, %41, %42, %43, %44, %45, %46, %47, %48, %49, %50, %51, %52, %53, %54, %55, %56, %57, %58, %59, %60, %61, %62, %63}, "
        "{%64, %65, %66, %67}, %68, p, 1, 1, 0;\n}\n"
        : "+f"(d[0]), "+f"(d[1]), "+f"(d[2]), "+f"(d[3]), "+f"(d[4]), "+f"(d[5]), "+f"(d[6]), "+f"(d[7]), "+f"(d[8]), "+f"(d[9]), "+f"(d[10]), "+f"(d[11]), "+f"(d[12]), "+f"(d[13]), "+f"(d[14]), "+f"(d[15]), "+f"(d[16]), "+f"(d[17]), "+f"(d[18]), "+f"(d[19]), "+f"(d[20]), "+f"(d[21]), "+f"(d[22]), "+f"(d[23]), "+f"(d[24]), "+f"(d[25]), "+f"(d[26]), "+f"(d[27]), "+f"(d[28]), "+f"(d[29]), "+f"(d[30]), "+f"(d[31]), "+f"(d[32]), "+f"(d[33]), "+f"(d[34]), "+f"(d[35]), "+f"(d[36]), "+f"(d[37]), "+f"(d[38]), "+f"(d[39]), "+f"(d[40]), "+f"(d[41]), "+f"(d[42]), "+f"(d[43]), "+f"(d[44]), "+f"(d[45]), "+f"(d[46]), "+f"(d[47]), "+f"(d[48]), "+f"(d[49]), "+f"(d[50]), "+f"(d[51]), "+f"(d[52]), "+f"(d[53]), "+f"(d[54]), "+f"(d[55]), "+f"(d[56]), "+f"(d[57]), "+f"(d[58]), "+f"(d[59]), "+f"(d[60]), "+f"(d[61]), "+f"(d[62]), "+f"(d[63])
        : "r"(a0), "r"(a1), "r"(a2), "r"(a3), "l"(db), "r"(sd));
}
__device__ __forceinline__ void wgmma_rs_n128_tb(float (&d)[64], uint32_t a0, uint32_t a1, uint32_t a2, uint32_t a3, uint64_t db, int sd) {
    asm volatile("{\n.reg .pred p;\nsetp.ne.b32 p, %69, 0;\n"
        "wgmma.mma_async.sync.aligned.m64n128k16.f32.bf16.bf16 "
        "{%0, %1, %2, %3, %4, %5, %6, %7, %8, %9, %10, %11, %12, %13, %14, %15, %16, %17, %18, %19, %20, %21, %22, %23, %24, %25, %26, %27, %28, %29, %30, %31, %32, %33, %34, %35, %36, %37, %38, %39, %40, %41, %42, %43, %44, %45, %46, %47, %48, %49, %50, %51, %52, %53, %54, %55, %56, %57, %58, %59, %60, %61, %62, %63}, "
        "{%64, %65, %66, %67}, %68, p, 1, 1, 1;\n}\n"
        : "+f"(d[0]), "+f"(d[1]), "+f"(d[2]), "+f"(d[3]), "+f"(d[4]), "+f"(d[5]), "+f"(d[6]), "+f"(d[7]), "+f"(d[8]), "+f"(d[9]), "+f"(d[10]), "+f"(d[11]), "+f"(d[12]), "+f"(d[13]), "+f"(d[14]), "+f"(d[15]), "+f"(d[16]), "+f"(d[17]), "+f"(d[18]), "+f"(d[19]), "+f"(d[20]), "+f"(d[21]), "+f"(d[22]), "+f"(d[23]), "+f"(d[24]), "+f"(d[25]), "+f"(d[26]), "+f"(d[27]), "+f"(d[28]), "+f"(d[29]), "+f"(d[30]), "+f"(d[31]), "+f"(d[32]), "+f"(d[33]), "+f"(d[34]), "+f"(d[35]), "+f"(d[36]), "+f"(d[37]), "+f"(d[38]), "+f"(d[39]), "+f"(d[40]), "+f"(d[41]), "+f"(d[42]), "+f"(d[43]), "+f"(d[44]), "+f"(d[45]), "+f"(d[46]), "+f"(d[47]), "+f"(d[48]), "+f"(d[49]), "+f"(d[50]), "+f"(d[51]), "+f"(d[52]), "+f"(d[53]), "+f"(d[54]), "+f"(d[55]), "+f"(d[56]), "+f"(d[57]), "+f"(d[58]), "+f"(d[59]), "+f"(d[60]), "+f"(d[61]), "+f"(d[62]), "+f"(d[63])
        : "r"(a0), "r"(a1), "r"(a2), "r"(a3), "l"(db), "r"(sd));
}
__device__ __forceinline__ void wgmma_rs_n64_tb(float (&d)[32], uint32_t a0, uint32_t a1, uint32_t a2, uint32_t a3, uint64_t db, int sd) {
    asm volatile("{\n.reg .pred p;\nsetp.ne.b32 p, %37, 0;\n"
        "wgmma.mma_async.sync.aligned.m64n64k16.f32.bf16.bf16 "
        "{%0, %1, %2, %3, %4, %5, %6, %7, %8, %9, %10, %11, %12, %13, %14, %15, %16, %17, %18, %19, %20, %21, %22, %23, %24, %25, %26, %27, %28, %29, %30, %31}, "
        "{%32, %33, %34, %35}, %36, p, 1, 1, 1;\n}\n"
        : "+f"(d[0]), "+f"(d[1]), "+f"(d[2]), "+f"(d[3]), "+f"(d[4]), "+f"(d[5]), "+f"(d[6]), "+f"(d[7]), "+f"(d[8]), "+f"(d[9]), "+f"(d[10]), "+f"(d[11]), "+f"(d[12]), "+f"(d[13]), "+f"(d[14]), "+f"(d[15]), "+f"(d[16]), "+f"(d[17]), "+f"(d[18]), "+f"(d[19]), "+f"(d[20]), "+f"(d[21]), "+f"(d[22]), "+f"(d[23]), "+f"(d[24]), "+f"(d[25]), "+f"(d[26]), "+f"(d[27]), "+f"(d[28]), "+f"(d[29]), "+f"(d[30]), "+f"(d[31])
        : "r"(a0), "r"(a1), "r"(a2), "r"(a3), "l"(db), "r"(sd));
}

__global__ void __launch_bounds__(384, 1) fused_gqa_kernel(const __grid_constant__ Params P) {
    extern __shared__ uint8_t smem_raw[];
    const uint32_t base = (smem_u32(smem_raw) + 1023u) & ~1023u;
    const uint32_t smR = base;
    const uint32_t smS = base + R_BYTES;
    const uint32_t bars = smS + NSTAGE * STAGE_BYTES;
    const uint32_t prog = bars + 8 * (2 * NSTAGE + 10);
    const int tid = threadIdx.x;
    const int wid = __shfl_sync(0xffffffffu, tid >> 5, 0);
    const int lane = tid & 31;

    const int cta = blockIdx.x;
    const int blk = cta >> 6;
    const int hp = (cta >> 3) & 7;
    const int b = cta & 7;
    const int grp = blk * 8 + b;

    if (tid == 256) {
        TS(0);
        asm volatile("prefetch.tensormap [%0];" ::"l"(&P.x[blk]) : "memory");
        asm volatile("prefetch.tensormap [%0];" ::"l"(&P.wq[blk]) : "memory");
        for (int i = 0; i < NSTAGE; i++) {
            mbar_init(bars + 8 * i, 1);
            mbar_init(bars + 8 * (NSTAGE + i), 8);
        }
        for (int i = 0; i < 10; i++) mbar_init(bars + 8 * (2 * NSTAGE + i), 4);
        asm volatile("st.volatile.shared.u32 [%0], %1;" ::"r"(prog), "r"(0) : "memory");
        asm volatile("fence.mbarrier_init.release.cluster;" ::: "memory");
        asm volatile("fence.proxy.async.shared::cta;" ::: "memory");
#pragma unroll
        for (int s = 0; s < NSTAGE; s++) {
            const uint32_t fb = bars + 8 * s;
            const uint32_t dst = smS + s * STAGE_BYTES;
            mbar_expect_tx(fb, (s & 1) ? STAGE_BYTES : STAGE_BYTES + 8192);
            if (!(s & 1)) tma_2d(smR + (s >> 1) * 8192, &P.x[blk], (s >> 1) * 64, b * 64, fb);
#pragma unroll
            for (int p = 0; p < 4; p++) tma_3d(dst + p * 8192, &P.wq[blk], 0, s * 32, hp * 8 + (p & 1) * 4 + (p >> 1) * 2, fb);
        }
        asm volatile("prefetch.tensormap [%0];" ::"l"(&P.k[blk]) : "memory");
        asm volatile("prefetch.tensormap [%0];" ::"l"(&P.v[blk]) : "memory");
        asm volatile("prefetch.tensormap [%0];" ::"l"(&P.wo[blk]) : "memory");
        asm volatile("prefetch.tensormap [%0];" ::"l"(&P.wo8[blk]) : "memory");
    }
    __syncthreads();

    if (wid >= 8) {
        asm volatile("setmaxnreg.dec.sync.aligned.u32 40;");
        if (wid == 8) {
            if (lane == 0) {
                int slot = 0, ph = 0;
                for (int s = NSTAGE; s < N_WQ; s++) {
                    const uint32_t fb = bars + 8 * slot;
                    mbar_wait(bars + 8 * (NSTAGE + slot), ph);
                    const uint32_t dst = smS + slot * STAGE_BYTES;
                    mbar_expect_tx(fb, (s & 1) ? STAGE_BYTES : STAGE_BYTES + 8192);
                    if (!(s & 1)) tma_2d(smR + ((s >> 1) & 7) * 8192, &P.x[blk], (s >> 1) * 64, b * 64, fb);
#pragma unroll
                    for (int p = 0; p < 4; p++) {
                        const int w = p >> 1, j = p & 1;
                        tma_3d(dst + p * 8192, &P.wq[blk], 0, s * 32, hp * 8 + j * 4 + w * 2, fb);
                    }
                    if (++slot == NSTAGE) { slot = 0; ph ^= 1; }
                }
                int lim = NSTAGE;
                for (int i = 0; i < 34; i++) {
                    const int u = (i >= 17), r = i - 17 * u;
                    const bool extra = (i == 28) || (i == 33);
                    const int sl = extra ? ((i == 28) ? 3 : 4) : slot;
                    const uint32_t fb = bars + 8 * sl;
                    mbar_wait(bars + 8 * (NSTAGE + sl), extra ? 1 : ph);
                    const uint32_t dst = smS + sl * STAGE_BYTES;
                    mbar_expect_tx(fb, STAGE_BYTES);
                    if (r < 8) {
                        const int row = (b * kHkv + hp * 2 + u) * kSk + (r >> 1) * 128;
                        tma_3d(dst, (r & 1) ? &P.v[blk] : &P.k[blk], 0, row, 0, fb);
                    } else {
                        const int q = r - 8, row = hp * 512 + u * 256;
                        if (q < 8) {
                            tma_3d(dst, &P.wo[blk], 0, row + (q & 3) * 64, (q >> 2) * 4, fb);
                            tma_3d(dst + 16384, &P.wo[blk], 0, row + ((q & 3) ^ 2) * 64, (q >> 2) * 4 + 2, fb);
                        } else {
                            tma_2d(dst, &P.wo8[blk], 512, row, fb);
                            tma_2d(dst + 16384, &P.wo8[blk], 512, row + 128, fb);
                        }
                    }
                    asm volatile("st.volatile.shared.u32 [%0], %1;" ::"r"(prog), "r"(i + 1) : "memory");
                    if (i == 7) lim = 3;
                    if (!extra && ++slot == lim) { slot = 0; ph ^= 1; }
                }
            }
        } else if (wid == 11) {
            if (PF_DIST > 0) {
                uint32_t sink = 0;
                mbar_wait(bars, 0);
                if (PF_WQ) {
                    const char* wqs = (const char*)(P.wqp[blk] + hp * 512) + (size_t)(160 + b * 52) * 8192;
#pragma unroll
                    for (int h = 0; h < 2; h++) {
#pragma unroll
                        for (int j = 0; j < 4; j++) {
                            const int e = (h * 4 + j) * 32 + lane;
                            if (e < 208) sink |= l2_touch(wqs + (size_t)(e >> 2) * 8192 + (e & 3) * 256);
                        }
                        if (sink == 0x9E3779B9u) asm volatile("st.volatile.shared.u32 [%0], %1;" ::"r"(prog + 4), "r"(sink) : "memory");
                    }
                }
                const char* kbase = (const char*)(P.kp[blk] + (size_t)(b * kHkv + hp * 2) * kSk * kDh);
                const char* vbase = (const char*)(P.vp[blk] + (size_t)(b * kHkv + hp * 2) * kSk * kDh);
                const char* wos = (const char*)(P.wop[blk] + (size_t)hp * 512 * kD) + (size_t)b * 36864;
                for (int i = 0; i < 18; i++) {
                    const int u = (i >= 9), r = i - 9 * u;
                    const int pos = u ? (PF_POS1 + r) : r;
                    if (pos >= PF_DIST) {
                        uint32_t pr, n = 0;
                        while (true) {
                            asm volatile("ld.volatile.shared.u32 %0, [%1];" : "=r"(pr) : "r"(prog) : "memory");
                            const int prk = ((int)pr <= 8) ? (int)pr : (((int)pr <= 17) ? 8 + (((int)pr - 8) * (PF_POS1 - 8)) / 9 : (int)pr - 17 + PF_POS1);
                            if (prk + PF_DIST >= pos) break;
                            if (++n > (1u << 22)) break;
                            __nanosleep(100);
                        }
                    }
                    if (r < 8) {
                        const char* p = ((r & 1) ? vbase : kbase) + (size_t)(u * 4 + (r >> 1)) * 32768 + lane * 256;
#pragma unroll
                        for (int j = 0; j < 4; j++) sink |= l2_touch(p + j * 8192);
                    } else {
                        const char* p = wos + (size_t)u * 294912 + lane * 256;
#pragma unroll
                        for (int j = 0; j < 5; j++) if (j * 32 + lane < 144) sink |= l2_touch(p + j * 8192);
                    }
                    if (sink == 0x9E3779B9u) asm volatile("st.volatile.shared.u32 [%0], %1;" ::"r"(prog + 4), "r"(sink) : "memory");
                }
            }
        } else {
            const int hw = wid - 9;
            for (int k = 0; k < 3; k++) {
                mbar_wait(bars + 8 * (2 * NSTAGE + hw * 5 + k), 0);
                const int c = (k < 2) ? (2 * k + hw) : 4;
                asm volatile("fence.acq_rel.gpu;" ::: "memory");
                asm volatile("red.relaxed.gpu.global.add.u32 [%0], 1;" ::"l"(&g_cnt[(grp * 9 + c) * 32 + lane]) : "memory");
            }
        }
    } else {
        asm volatile("setmaxnreg.inc.sync.aligned.u32 232;");
        const int w = wid >> 2;
        const int t = tid & 127;
        int slot = 0, ph = 0, lim = NSTAGE;
        uint32_t qf[8][4];
        const uint32_t stash = smR + (1 + w) * 16384 + t * 16;
        {
            float acc[128];
            int pslot = 0;
            for (int s = 0; s < N_WQ; s++) {
                mbar_wait(bars + 8 * slot, ph);
                if (tid == 0 && s == 0) TS(20);
                if (tid == 0 && s == 5) TS(21);
                if (tid == 0 && s == 10) TS(22);
                const uint64_t da = mk_desc(smR + ((s >> 1) & 7) * 8192 + (s & 1) * 64, 16, 1024);
                const uint64_t db = mk_desc(smS + slot * STAGE_BYTES + w * 16384, 4096, 1024);
                wg_fence();
                wgmma_ss_n256_tb(acc, da, db, s != 0);
                wgmma_ss_n256_tb(acc, da + 2, db + 128, 1);
                wg_commit();
                wg_wait<0>();
                if (lane == 0) mbar_arrive(bars + 8 * (NSTAGE + slot));
                pslot = slot;
                if (++slot == NSTAGE) { slot = 0; ph ^= 1; }
            }
            fence_regs(acc);
            if (tid == 0) TS(1);
#pragma unroll
            for (int kk = 0; kk < 8; kk++) {
#pragma unroll
                for (int i = 0; i < 4; i++) qf[kk][i] = pack_bf16(acc[8 * kk + 2 * i], acc[8 * kk + 2 * i + 1]);
                sts128(stash + kk * 2048,
                       pack_bf16(acc[64 + 8 * kk + 0], acc[64 + 8 * kk + 1]), pack_bf16(acc[64 + 8 * kk + 2], acc[64 + 8 * kk + 3]),
                       pack_bf16(acc[64 + 8 * kk + 4], acc[64 + 8 * kk + 5]), pack_bf16(acc[64 + 8 * kk + 6], acc[64 + 8 * kk + 7]));
            }
        }
        if (w == 1) bar_arrive<5, 256>();
        const float sc = 0.08838834764831845f * 1.4426950408889634f;
        uint2* dst0 = g_part + (size_t)(grp * 80 + 2 * w * 8 + hp) * 1024 + t;
        uint2* dst8 = g_part + (size_t)(grp * 80 + 64 + hp * 2 + w) * 1024 + t;
#pragma unroll
        for (int u = 0; u < 2; u++) {
            uint32_t af[16][4];
            {
                float o[64], s[64];
                float m0 = -INFINITY, m1 = -INFINITY, l0 = 0.f, l1 = 0.f;
                uint32_t pf[8][4];
#pragma unroll
                for (int i = 0; i < 64; i++) { o[i] = 0.f; s[i] = 0.f; }
#pragma unroll
                for (int i = 0; i < 32; i++) pf[i >> 2][i & 3] = 0u;
#pragma unroll 1
                for (int tt = 0; tt <= 4; tt++) {
                    int vslot = slot;
                    if (tt > 0) {
                        mbar_wait(bars + 8 * slot, ph);
                        if (++slot == lim) { slot = 0; ph ^= 1; }
                    }
                    if (tt < 4) mbar_wait(bars + 8 * slot, ph);
                    if (tid == 0) TS(32 + u * 20 + tt * 4);
                    if (w == 0) bar_sync<5, 256>(); else bar_sync<6, 256>();
                    wg_fence();
                    if (tt > 0) {
                        const uint64_t db = mk_desc(smS + vslot * STAGE_BYTES, 16384, 1024);
#pragma unroll
                        for (int kk = 0; kk < 8; kk++)
                            wgmma_rs_n128_tb(o, pf[kk][0], pf[kk][1], pf[kk][2], pf[kk][3], db + kk * 128, (tt > 1) || (kk != 0));
                        wg_commit();
                    }
                    if (tt < 4) {
                        const uint64_t db = mk_desc(smS + slot * STAGE_BYTES, 16, 1024);
#pragma unroll
                        for (int kk = 0; kk < 8; kk++)
                            wgmma_rs_n128(s, qf[kk][0], qf[kk][1], qf[kk][2], qf[kk][3], db + (kk >> 2) * 1024 + (kk & 3) * 2, kk != 0);
                        wg_commit();
                    }
                    if (w == 0) bar_arrive<6, 256>(); else if (!(u == 1 && tt == 4)) bar_arrive<5, 256>();
                    if (tid == 0) TS(32 + u * 20 + tt * 4 + 1);
                    wg_wait<0>();
                    fence_regs(o);
                    fence_regs(s);
                    if (tid == 0) TS(32 + u * 20 + tt * 4 + 2);
                    if (tt > 0 && lane == 0) mbar_arrive(bars + 8 * (NSTAGE + vslot));
                    if (tt == 4) break;
                    if (lane == 0) mbar_arrive(bars + 8 * (NSTAGE + slot));
                    if (++slot == lim) { slot = 0; ph ^= 1; }
                    float mx0 = s[0], mx1 = s[2];
#pragma unroll
                    for (int j = 0; j < 16; j++) {
                        mx0 = fmaxf(mx0, fmaxf(s[4 * j], s[4 * j + 1]));
                        mx1 = fmaxf(mx1, fmaxf(s[4 * j + 2], s[4 * j + 3]));
                    }
                    mx0 = fmaxf(mx0, __shfl_xor_sync(0xffffffffu, mx0, 1));
                    mx1 = fmaxf(mx1, __shfl_xor_sync(0xffffffffu, mx1, 1));
                    mx0 = fmaxf(mx0, __shfl_xor_sync(0xffffffffu, mx0, 2));
                    mx1 = fmaxf(mx1, __shfl_xor_sync(0xffffffffu, mx1, 2));
                    const float mn0 = fmaxf(m0, mx0), mn1 = fmaxf(m1, mx1);
                    const float al0 = ex2((m0 - mn0) * sc), al1 = ex2((m1 - mn1) * sc);
                    m0 = mn0; m1 = mn1;
                    const float ms0 = mn0 * sc, ms1 = mn1 * sc;
                    float rs0 = 0.f, rs1 = 0.f;
#pragma unroll
                    for (int j = 0; j < 16; j++) {
                        const float p0 = ex2(fmaf(s[4 * j], sc, -ms0)), p1 = ex2(fmaf(s[4 * j + 1], sc, -ms0));
                        const float p2 = ex2(fmaf(s[4 * j + 2], sc, -ms1)), p3 = ex2(fmaf(s[4 * j + 3], sc, -ms1));
                        rs0 += p0 + p1; rs1 += p2 + p3;
                        pf[j >> 1][(j & 1) * 2] = pack_bf16(p0, p1);
                        pf[j >> 1][(j & 1) * 2 + 1] = pack_bf16(p2, p3);
                    }
                    l0 = l0 * al0 + rs0; l1 = l1 * al1 + rs1;
                    if (tt > 0) {
#pragma unroll
                        for (int j = 0; j < 16; j++) { o[4 * j] *= al0; o[4 * j + 1] *= al0; o[4 * j + 2] *= al1; o[4 * j + 3] *= al1; }
                    }
                    if (tid == 0) TS(32 + u * 20 + tt * 4 + 3);
                }
                if (tid == 0) TS(2 + u);
                l0 += __shfl_xor_sync(0xffffffffu, l0, 1);
                l1 += __shfl_xor_sync(0xffffffffu, l1, 1);
                l0 += __shfl_xor_sync(0xffffffffu, l0, 2);
                l1 += __shfl_xor_sync(0xffffffffu, l1, 2);
                const float i0 = 1.f / l0, i1 = 1.f / l1;
                const uint32_t zown = smR + (w ? 3 : 0) * 16384 + t * 16;
#pragma unroll
                for (int kk = 0; kk < 8; kk++) {
                    af[kk][0] = pack_bf16(o[8 * kk + 0] * i0, o[8 * kk + 1] * i0);
                    af[kk][1] = pack_bf16(o[8 * kk + 2] * i1, o[8 * kk + 3] * i1);
                    af[kk][2] = pack_bf16(o[8 * kk + 4] * i0, o[8 * kk + 5] * i0);
                    af[kk][3] = pack_bf16(o[8 * kk + 6] * i1, o[8 * kk + 7] * i1);
                    sts128(zown + kk * 2048, af[kk][0], af[kk][1], af[kk][2], af[kk][3]);
                }
            }
            if (w == 0) bar_arrive<7, 256>(); else bar_arrive<8, 256>();
            lim = 3;
            if (u == 0) {
#pragma unroll
                for (int kk = 0; kk < 8; kk++) lds128(stash + kk * 2048, qf[kk]);
            }
            uint32_t nx[8][4];
#pragma unroll
            for (int ps = 0; ps < 2; ps++) {
                float acc[64];
                const uint32_t keep = smS + (3 + ps) * STAGE_BYTES + w * 16384 + t * 16;
                if (u == 0) {
#pragma unroll
                    for (int i = 0; i < 64; i++) acc[i] = 0.f;
                } else {
                    if (ps == 0) {
#pragma unroll
                        for (int j = 0; j < 8; j++) lds128(keep + j * 2048, nx[j]);
                        asm volatile("fence.proxy.async.shared::cta;" ::: "memory");
                        __syncwarp();
                        if (lane == 0) mbar_arrive(bars + 8 * (NSTAGE + 3));
                    }
#pragma unroll
                    for (int j = 0; j < 8; j++)
#pragma unroll
                        for (int i = 0; i < 4; i++) { acc[8 * j + 2 * i] = __uint_as_float(nx[j][i] << 16); acc[8 * j + 2 * i + 1] = __uint_as_float(nx[j][i] & 0xffff0000u); }
                }
#pragma unroll
                for (int st = 0; st < 4; st++) {
                    if (ps == 0 && st == 2) {
                        if (w == 0) bar_sync<8, 256>(); else bar_sync<7, 256>();
#pragma unroll
                        for (int kk = 0; kk < 8; kk++) lds128(smR + (w ? 0 : 3) * 16384 + kk * 2048 + t * 16, af[8 + kk]);
                    }
                    const bool extra = (u == 1) && (ps == 0 && st == 3);
                    const int sl = extra ? (3 + ps) : slot;
                    if (tid == 0) TS(80 + u * 24 + (ps * 4 + st) * 3);
                    mbar_wait(bars + 8 * sl, extra ? 1 : ph);
                    if (tid == 0) TS(80 + u * 24 + (ps * 4 + st) * 3 + 1);
                    const uint64_t db = mk_desc(smS + sl * STAGE_BYTES + w * 16384, 8192, 1024);
                    wg_fence();
#pragma unroll
                    for (int kk = 0; kk < 4; kk++)
                        wgmma_rs_n128_tb(acc, af[st * 4 + kk][0], af[st * 4 + kk][1], af[st * 4 + kk][2], af[st * 4 + kk][3], db + kk * 128, 1);
                    wg_commit();
                    if (u == 1 && st == 1) {
                        if (ps == 0) {
#pragma unroll
                            for (int j = 0; j < 8; j++) lds128(keep + STAGE_BYTES + j * 2048, nx[j]);
                            asm volatile("fence.proxy.async.shared::cta;" ::: "memory");
                            __syncwarp();
                            if (lane == 0) mbar_arrive(bars + 8 * (NSTAGE + 4));
                        } else {
#pragma unroll
                            for (int j = 0; j < 4; j++) lds128(stash + j * 2048, nx[j]);
                        }
                    }
                    wg_wait<0>();
                    if (tid == 0) TS(80 + u * 24 + (ps * 4 + st) * 3 + 2);
                    if (!extra) {
                        if (lane == 0) mbar_arrive(bars + 8 * (NSTAGE + slot));
                        if (++slot == 3) { slot = 0; ph ^= 1; }
                    }
                }
                fence_regs(acc);
                if (u == 0) {
#pragma unroll
                    for (int j = 0; j < 8; j++)
                        sts128(keep + j * 2048, pack_bf16(acc[8 * j], acc[8 * j + 1]), pack_bf16(acc[8 * j + 2], acc[8 * j + 3]),
                               pack_bf16(acc[8 * j + 4], acc[8 * j + 5]), pack_bf16(acc[8 * j + 6], acc[8 * j + 7]));
                } else {
                    uint2* dst = dst0 + (size_t)ps * 32 * 1024;
#pragma unroll
                    for (int j = 0; j < 16; j++)
                        __stcg(dst + (j >> 3) * 8192 + (j & 7) * 128, make_uint2(pack_bf16(acc[4 * j], acc[4 * j + 1]), pack_bf16(acc[4 * j + 2], acc[4 * j + 3])));
                    __syncwarp();
                    if (lane == 0) mbar_arrive(bars + 8 * (2 * NSTAGE + w * 5 + ps));
                }
                if (tid == 0) TS(4 + u * 8 + ps);
            }
            {
                float acc[32];
                if (u == 0) {
#pragma unroll
                    for (int i = 0; i < 32; i++) acc[i] = 0.f;
                } else {
#pragma unroll
                    for (int j = 0; j < 4; j++)
#pragma unroll
                        for (int i = 0; i < 4; i++) { acc[8 * j + 2 * i] = __uint_as_float(nx[j][i] << 16); acc[8 * j + 2 * i + 1] = __uint_as_float(nx[j][i] & 0xffff0000u); }
                }
                const int sl = u ? 4 : slot;
                mbar_wait(bars + 8 * sl, u ? 1 : ph);
                const uint64_t db = mk_desc(smS + sl * STAGE_BYTES + w * 16384, 8192, 1024);
                wg_fence();
#pragma unroll
                for (int kk = 0; kk < 8; kk++)
                    wgmma_rs_n64_tb(acc, af[kk][0], af[kk][1], af[kk][2], af[kk][3], db + kk * 128, 1);
                wg_commit();
                wg_wait<0>();
                if (u == 0) {
                    if (lane == 0) mbar_arrive(bars + 8 * (NSTAGE + slot));
                    if (++slot == 3) { slot = 0; ph ^= 1; }
                }
                fence_regs(acc);
                if (u == 0) {
#pragma unroll
                    for (int j = 0; j < 4; j++)
                        sts128(stash + j * 2048, pack_bf16(acc[8 * j], acc[8 * j + 1]), pack_bf16(acc[8 * j + 2], acc[8 * j + 3]),
                               pack_bf16(acc[8 * j + 4], acc[8 * j + 5]), pack_bf16(acc[8 * j + 6], acc[8 * j + 7]));
                } else {
#pragma unroll
                    for (int j = 0; j < 8; j++)
                        __stcg(dst8 + j * 128, make_uint2(pack_bf16(acc[4 * j], acc[4 * j + 1]), pack_bf16(acc[4 * j + 2], acc[4 * j + 3])));
                    __syncwarp();
                    if (lane == 0) mbar_arrive(bars + 8 * (2 * NSTAGE + w * 5 + 2));
                }
                if (tid == 0) TS(6 + u * 8);
            }
        }
        {
            const int nch = (w == 0) ? 3 : 2;
            if (lane < nch) {
                const int c = (lane < 2) ? (2 * lane + w) : 4;
                const unsigned need = (lane < 2) ? 8u : 16u;
                unsigned* cp = &g_cnt[(grp * 9 + c) * 32 + hp * 4 + (wid & 3)];
                unsigned v, n = 0;
                while (true) {
                    asm volatile("ld.acquire.gpu.global.u32 %0, [%1];" : "=r"(v) : "l"(cp) : "memory");
                    if (v >= need) break;
                    if (++n > (1u << 21)) break;
                }
                *cp = 0;
            }
            __syncwarp();
            if (tid == 0) TS(18);
            __nv_bfloat16* orow = P.out + (size_t)(b * 64 + (t >> 5) * 16 + (lane >> 2)) * (2 * kD) + blk * kD + hp * 8 + (lane & 3) * 2;
            const uint2* src = g_part + ((size_t)(grp * 80 + 2 * w * 8) * 8 + hp) * 128 + t;
            uint2 v[4][8];
#pragma unroll
            for (int k = 0; k < 4; k++)
#pragma unroll
                for (int i = 0; i < 8; i++) v[k][i] = __ldcg(src + (size_t)((k >> 1) * 32 + (k & 1) * 8 + i) * 1024);
            if (w == 0) {
                const uint2* src8 = g_part + ((size_t)(grp * 80 + 64) * 8 + hp) * 128 + t;
                uint2 u[16];
#pragma unroll
                for (int i = 0; i < 16; i++) u[i] = __ldcg(src8 + (size_t)i * 1024);
                float a0 = 0.f, a1 = 0.f, a2 = 0.f, a3 = 0.f;
#pragma unroll
                for (int i = 0; i < 16; i++) {
                    a0 += __uint_as_float(u[i].x << 16); a1 += __uint_as_float(u[i].x & 0xffff0000u);
                    a2 += __uint_as_float(u[i].y << 16); a3 += __uint_as_float(u[i].y & 0xffff0000u);
                }
                *(uint32_t*)(orow + 512) = pack_bf16(a0, a1);
                *(uint32_t*)(orow + 512 + 8 * 2 * kD) = pack_bf16(a2, a3);
            }
#pragma unroll
            for (int k = 0; k < 4; k++) {
                float a0 = 0.f, a1 = 0.f, a2 = 0.f, a3 = 0.f;
#pragma unroll
                for (int i = 0; i < 8; i++) {
                    a0 += __uint_as_float(v[k][i].x << 16); a1 += __uint_as_float(v[k][i].x & 0xffff0000u);
                    a2 += __uint_as_float(v[k][i].y << 16); a3 += __uint_as_float(v[k][i].y & 0xffff0000u);
                }
                *(uint32_t*)(orow + ((k >> 1) * 4 + 2 * w + (k & 1)) * 64) = pack_bf16(a0, a1);
                *(uint32_t*)(orow + ((k >> 1) * 4 + 2 * w + (k & 1)) * 64 + 8 * 2 * kD) = pack_bf16(a2, a3);
            }
            if (tid == 0) TS(19);
        }
    }
}

typedef CUresult (*EncodeFn)(CUtensorMap*, CUtensorMapDataType, cuuint32_t, void*, const cuuint64_t*, const cuuint64_t*,
                             const cuuint32_t*, const cuuint32_t*, CUtensorMapInterleave, CUtensorMapSwizzle,
                             CUtensorMapL2promotion, CUtensorMapFloatOOBfill);

void make_map(EncodeFn fn, CUtensorMap* m, const void* ptr, uint64_t cols, uint64_t rows, uint32_t box_rows) {
    cuuint64_t dims[2] = {cols, rows};
    cuuint64_t strides[1] = {cols * 2};
    cuuint32_t box[2] = {64, box_rows};
    cuuint32_t es[2] = {1, 1};
    fn(m, CU_TENSOR_MAP_DATA_TYPE_BFLOAT16, 2, const_cast<void*>(ptr), dims, strides, box, es, CU_TENSOR_MAP_INTERLEAVE_NONE,
       CU_TENSOR_MAP_SWIZZLE_128B, CU_TENSOR_MAP_L2_PROMOTION_L2_256B, CU_TENSOR_MAP_FLOAT_OOB_FILL_NONE);
}

void make_map3(EncodeFn fn, CUtensorMap* m, const void* ptr, uint64_t cols, uint64_t rows, uint32_t box_rows, uint32_t box_groups) {
    cuuint64_t dims[3] = {64, rows, cols / 64};
    cuuint64_t strides[2] = {cols * 2, 128};
    cuuint32_t box[3] = {64, box_rows, box_groups};
    cuuint32_t es[3] = {1, 1, 1};
    fn(m, CU_TENSOR_MAP_DATA_TYPE_BFLOAT16, 3, const_cast<void*>(ptr), dims, strides, box, es, CU_TENSOR_MAP_INTERLEAVE_NONE,
       CU_TENSOR_MAP_SWIZZLE_128B, CU_TENSOR_MAP_L2_PROMOTION_L2_256B, CU_TENSOR_MAP_FLOAT_OOB_FILL_NONE);
}

}

extern "C" void kernel_launch(void* const* d_in, const int* in_sizes, int n_in, void* d_out, int out_size) {
    static EncodeFn enc = nullptr;
    if (!enc) {
        void* fn = nullptr;
        cudaDriverEntryPointQueryResult st;
        cudaGetDriverEntryPoint("cuTensorMapEncodeTiled", &fn, cudaEnableDefault, &st);
        enc = (EncodeFn)fn;
        cudaFuncSetAttribute(fused_gqa_kernel, cudaFuncAttributeMaxDynamicSharedMemorySize, SMEM_BYTES);
    }
    Params P;
    for (int blk = 0; blk < 2; blk++) {
        const void* x = d_in[blk * 5 + 0];
        const void* k = d_in[blk * 5 + 1];
        const void* v = d_in[blk * 5 + 2];
        const void* wq = d_in[blk * 5 + 3];
        const void* wo = d_in[blk * 5 + 4];
        make_map(enc, &P.x[blk], x, kD, kB * kSq, 64);
        make_map3(enc, &P.wq[blk], wq, kHq * kDh, kD, 32, 2);
        make_map3(enc, &P.k[blk], k, kDh, (uint64_t)kB * kHkv * kSk, 128, 2);
        make_map3(enc, &P.v[blk], v, kDh, (uint64_t)kB * kHkv * kSk, 128, 2);
        make_map3(enc, &P.wo[blk], wo, kD, kHq * kDh, 64, 2);
        make_map(enc, &P.wo8[blk], wo, kD, kHq * kDh, 128);
        P.wqp[blk] = (const __nv_bfloat16*)wq;
        P.kp[blk] = (const __nv_bfloat16*)k;
        P.vp[blk] = (const __nv_bfloat16*)v;
        P.wop[blk] = (const __nv_bfloat16*)wo;
    }
    P.out = (__nv_bfloat16*)d_out;
    fused_gqa_kernel<<<128, 384, SMEM_BYTES>>>(P);
}
```

```cpp
#include <cuda_runtime.h>
#include <cuda_bf16.h>
#include <cuda.h>
#include <stdint.h>

namespace {

constexpr int kB = 8, kSq = 64, kD = 576, kHq = 32, kHkv = 16, kSk = 512, kDh = 128;
constexpr int NSTAGE = 5;
constexpr int STAGE_BYTES = 32768;
constexpr int R_BYTES = 65536;
constexpr int SMEM_BYTES = R_BYTES + NSTAGE * STAGE_BYTES + 1024   + 256  ;
constexpr int N_WQ = 18;
#define PF_DIST_V 6
#define OP_WAIT0 1
#define QP_WAIT0 1
#define PF_POS1 9
#define PF_START 1
#define PF_WQ 0
#define PF_SLEEP 1000
constexpr int PF_DIST = PF_DIST_V;

struct __align__(64) Params {
    CUtensorMap x[2], wq[2], k[2], v[2], wo[2], wo8[2];
    const __nv_bfloat16* wqp[2];
    const __nv_bfloat16* kp[2];
    const __nv_bfloat16* vp[2];
    const __nv_bfloat16* wop[2];
    __nv_bfloat16* out;
};

__device__ uint2 g_part[16 * 80 * 8 * 128];
__device__ unsigned int g_cnt[16 * 9 * 32];
#define TS(k) do {} while (0)

__device__ __forceinline__ uint32_t smem_u32(const void* p) { return (uint32_t)__cvta_generic_to_shared(p); }
__device__ __forceinline__ void mbar_init(uint32_t bar, int cnt) {
    asm volatile("mbarrier.init.shared::cta.b64 [%0], %1;" ::"r"(bar), "r"(cnt));
}
__device__ __forceinline__ void mbar_expect_tx(uint32_t bar, uint32_t bytes) {
    asm volatile("mbarrier.arrive.expect_tx.shared::cta.b64 _, [%0], %1;" ::"r"(bar), "r"(bytes) : "memory");
}
__device__ __forceinline__ void mbar_arrive(uint32_t bar) {
    asm volatile("mbarrier.arrive.shared::cta.b64 _, [%0];" ::"r"(bar) : "memory");
}
__device__ __forceinline__ bool mbar_try(uint32_t bar, uint32_t parity) {
    uint32_t ok;
    asm volatile("{\n.reg .pred p;\nmbarrier.try_wait.parity.shared::cta.b64 p, [%1], %2;\nselp.u32 %0, 1, 0, p;\n}\n"
                 : "=r"(ok) : "r"(bar), "r"(parity) : "memory");
    return ok != 0;
}
__device__ __forceinline__ void mbar_wait(uint32_t bar, uint32_t parity) {
    if (mbar_try(bar, parity)) return;
    uint32_t n = 0;
    while (!mbar_try(bar, parity)) {
        if (++n > (1u << 20)) break;
    }
}
__device__ __forceinline__ void tma_2d(uint32_t dst, const CUtensorMap* tm, int c0, int c1, uint32_t bar) {
    asm volatile("cp.async.bulk.tensor.2d.shared::cluster.global.mbarrier::complete_tx::bytes [%0], [%1, {%3, %4}], [%2];"
                 ::"r"(dst), "l"(tm), "r"(bar), "r"(c0), "r"(c1) : "memory");
}
__device__ __forceinline__ void tma_3d(uint32_t dst, const CUtensorMap* tm, int c0, int c1, int c2, uint32_t bar) {
    asm volatile("cp.async.bulk.tensor.3d.shared::cluster.global.mbarrier::complete_tx::bytes [%0], [%1, {%3, %4, %5}], [%2];"
                 ::"r"(dst), "l"(tm), "r"(bar), "r"(c0), "r"(c1), "r"(c2) : "memory");
}
__device__ __forceinline__ void l2_prefetch(const void* p, uint32_t bytes) {
    asm volatile("cp.async.bulk.prefetch.L2.global [%0], %1;" ::"l"(p), "r"(bytes) : "memory");
}
__device__ __forceinline__ uint32_t l2_touch(const void* p) {
    uint32_t v;
    asm volatile("ld.global.L2::256B.b32 %0, [%1];" : "=r"(v) : "l"(p) : "memory");
    return v;
}
__device__ __forceinline__ void wg_fence() { asm volatile("wgmma.fence.sync.aligned;" ::: "memory"); }
__device__ __forceinline__ void wg_commit() { asm volatile("wgmma.commit_group.sync.aligned;" ::: "memory"); }
template <int N> __device__ __forceinline__ void wg_wait() { asm volatile("wgmma.wait_group.sync.aligned %0;" ::"n"(N) : "memory"); }
template <int N> __device__ __forceinline__ void fence_regs(float (&d)[N]) {
#pragma unroll
    for (int i = 0; i < N; i++) asm volatile("" : "+f"(d[i])::"memory");
}
__device__ __forceinline__ uint64_t mk_desc(uint32_t addr, uint32_t lbo, uint32_t sbo) {
    return (uint64_t)((addr & 0x3FFFF) >> 4) | ((uint64_t)(lbo >> 4) << 16) | ((uint64_t)(sbo >> 4) << 32) | (1ull << 62);
}
__device__ __forceinline__ uint32_t pack_bf16(float a, float b) {
    uint32_t r;
    asm("cvt.rn.bf16x2.f32 %0, %1, %2;" : "=r"(r) : "f"(b), "f"(a));
    return r;
}
__device__ __forceinline__ float ex2(float x) {
    float y;
    asm("ex2.approx.ftz.f32 %0, %1;" : "=f"(y) : "f"(x));
    return y;
}
template <int ID, int N> __device__ __forceinline__ void bar_sync() { asm volatile("bar.sync %0, %1;" ::"n"(ID), "n"(N) : "memory"); }
template <int ID, int N> __device__ __forceinline__ void bar_arrive() { asm volatile("bar.arrive %0, %1;" ::"n"(ID), "n"(N) : "memory"); }
__device__ __forceinline__ void sts128(uint32_t addr, uint32_t a, uint32_t b, uint32_t c, uint32_t d) {
    asm volatile("st.shared.v4.b32 [%0], {%1,%2,%3,%4};" ::"r"(addr), "r"(a), "r"(b), "r"(c), "r"(d) : "memory");
}
__device__ __forceinline__ void lds128(uint32_t addr, uint32_t (&r)[4]) {
    asm volatile("ld.shared.v4.b32 {%0,%1,%2,%3}, [%4];" : "=r"(r[0]), "=r"(r[1]), "=r"(r[2]), "=r"(r[3]) : "r"(addr) : "memory");
}

__device__ __forceinline__ void wgmma_ss_n256_tb(float (&d)[128], uint64_t da, uint64_t db, int sd) {
    asm volatile("{\n.reg .pred p;\nsetp.ne.b32 p, %130, 0;\n"
        "wgmma.mma_async.sync.aligned.m64n256k16.f32.bf16.bf16 "
        "{%0, %1, %2, %3, %4, %5, %6, %7, %8, %9, %10, %11, %12, %13, %14, %15, %16, %17, %18, %19, %20, %21, %22, %23, %24, %25, %26, %27, %28, %29, %30, %31, %32, %33, %34, %35, %36, %37, %38, %39, %40, %41, %42, %43, %44, %45, %46, %47, %48, %49, %50, %51, %52, %53, %54, %55, %56, %57, %58, %59, %60, %61, %62, %63, %64, %65, %66, %67, %68, %69, %70, %71, %72, %73, %74, %75, %76, %77, %78, %79, %80, %81, %82, %83, %84, %85, %86, %87, %88, %89, %90, %91, %92, %93, %94, %95, %96, %97, %98, %99, %100, %101, %102, %103, %104, %105, %106, %107, %108, %109, %110, %111, %112, %113, %114, %115, %116, %117, %118, %119, %120, %121, %122, %123, %124, %125, %126, %127}, "
        "%128, %129, p, 1, 1, 0, 1;\n}\n"
        : "+f"(d[0]), "+f"(d[1]), "+f"(d[2]), "+f"(d[3]), "+f"(d[4]), "+f"(d[5]), "+f"(d[6]), "+f"(d[7]), "+f"(d[8]), "+f"(d[9]), "+f"(d[10]), "+f"(d[11]), "+f"(d[12]), "+f"(d[13]), "+f"(d[14]), "+f"(d[15]), "+f"(d[16]), "+f"(d[17]), "+f"(d[18]), "+f"(d[19]), "+f"(d[20]), "+f"(d[21]), "+f"(d[22]), "+f"(d[23]), "+f"(d[24]), "+f"(d[25]), "+f"(d[26]), "+f"(d[27]), "+f"(d[28]), "+f"(d[29]), "+f"(d[30]), "+f"(d[31]), "+f"(d[32]), "+f"(d[33]), "+f"(d[34]), "+f"(d[35]), "+f"(d[36]), "+f"(d[37]), "+f"(d[38]), "+f"(d[39]), "+f"(d[40]), "+f"(d[41]), "+f"(d[42]), "+f"(d[43]), "+f"(d[44]), "+f"(d[45]), "+f"(d[46]), "+f"(d[47]), "+f"(d[48]), "+f"(d[49]), "+f"(d[50]), "+f"(d[51]), "+f"(d[52]), "+f"(d[53]), "+f"(d[54]), "+f"(d[55]), "+f"(d[56]), "+f"(d[57]), "+f"(d[58]), "+f"(d[59]), "+f"(d[60]), "+f"(d[61]), "+f"(d[62]), "+f"(d[63]), "+f"(d[64]), "+f"(d[65]), "+f"(d[66]), "+f"(d[67]), "+f"(d[68]), "+f"(d[69]), "+f"(d[70]), "+f"(d[71]), "+f"(d[72]), "+f"(d[73]), "+f"(d[74]), "+f"(d[75]), "+f"(d[76]), "+f"(d[77]), "+f"(d[78]), "+f"(d[79]), "+f"(d[80]), "+f"(d[81]), "+f"(d[82]), "+f"(d[83]), "+f"(d[84]), "+f"(d[85]), "+f"(d[86]), "+f"(d[87]), "+f"(d[88]), "+f"(d[89]), "+f"(d[90]), "+f"(d[91]), "+f"(d[92]), "+f"(d[93]), "+f"(d[94]), "+f"(d[95]), "+f"(d[96]), "+f"(d[97]), "+f"(d[98]), "+f"(d[99]), "+f"(d[100]), "+f"(d[101]), "+f"(d[102]), "+f"(d[103]), "+f"(d[104]), "+f"(d[105]), "+f"(d[106]), "+f"(d[107]), "+f"(d[108]), "+f"(d[109]), "+f"(d[110]), "+f"(d[111]), "+f"(d[112]), "+f"(d[113]), "+f"(d[114]), "+f"(d[115]), "+f"(d[116]), "+f"(d[117]), "+f"(d[118]), "+f"(d[119]), "+f"(d[120]), "+f"(d[121]), "+f"(d[122]), "+f"(d[123]), "+f"(d[124]), "+f"(d[125]), "+f"(d[126]), "+f"(d[127])
        : "l"(da), "l"(db), "r"(sd));
}
__device__ __forceinline__ void wgmma_rs_n128(float (&d)[64], uint32_t a0, uint32_t a1, uint32_t a2, uint32_t a3, uint64_t db, int sd) {
    asm volatile("{\n.reg .pred p;\nsetp.ne.b32 p, %69, 0;\n"
        "wgmma.mma_async.sync.aligned.m64n128k16.f32.bf16.bf16 "
        "{%0, %1, %2, %3, %4, %5, %6, %7, %8, %9, %10, %11, %12, %13, %14, %15, %16, %17, %18, %19, %20, %21, %22, %23, %24, %25, %26, %27, %28, %29, %30, %31, %32, %33, %34, %35, %36, %37, %38, %39, %40, %41, %42, %43, %44, %45, %46, %47, %48, %49, %50, %51, %52, %53, %54, %55, %56, %57, %58, %59, %60, %61, %62, %63}, "
        "{%64, %65, %66, %67}, %68, p, 1, 1, 0;\n}\n"
        : "+f"(d[0]), "+f"(d[1]), "+f"(d[2]), "+f"(d[3]), "+f"(d[4]), "+f"(d[5]), "+f"(d[6]), "+f"(d[7]), "+f"(d[8]), "+f"(d[9]), "+f"(d[10]), "+f"(d[11]), "+f"(d[12]), "+f"(d[13]), "+f"(d[14]), "+f"(d[15]), "+f"(d[16]), "+f"(d[17]), "+f"(d[18]), "+f"(d[19]), "+f"(d[20]), "+f"(d[21]), "+f"(d[22]), "+f"(d[23]), "+f"(d[24]), "+f"(d[25]), "+f"(d[26]), "+f"(d[27]), "+f"(d[28]), "+f"(d[29]), "+f"(d[30]), "+f"(d[31]), "+f"(d[32]), "+f"(d[33]), "+f"(d[34]), "+f"(d[35]), "+f"(d[36]), "+f"(d[37]), "+f"(d[38]), "+f"(d[39]), "+f"(d[40]), "+f"(d[41]), "+f"(d[42]), "+f"(d[43]), "+f"(d[44]), "+f"(d[45]), "+f"(d[46]), "+f"(d[47]), "+f"(d[48]), "+f"(d[49]), "+f"(d[50]), "+f"(d[51]), "+f"(d[52]), "+f"(d[53]), "+f"(d[54]), "+f"(d[55]), "+f"(d[56]), "+f"(d[57]), "+f"(d[58]), "+f"(d[59]), "+f"(d[60]), "+f"(d[61]), "+f"(d[62]), "+f"(d[63])
        : "r"(a0), "r"(a1), "r"(a2), "r"(a3), "l"(db), "r"(sd));
}
__device__ __forceinline__ void wgmma_rs_n128_tb(float (&d)[64], uint32_t a0, uint32_t a1, uint32_t a2, uint32_t a3, uint64_t db, int sd) {
    asm volatile("{\n.reg .pred p;\nsetp.ne.b32 p, %69, 0;\n"
        "wgmma.mma_async.sync.aligned.m64n128k16.f32.bf16.bf16 "
        "{%0, %1, %2, %3, %4, %5, %6, %7, %8, %9, %10, %11, %12, %13, %14, %15, %16, %17, %18, %19, %20, %21, %22, %23, %24, %25, %26, %27, %28, %29, %30, %31, %32, %33, %34, %35, %36, %37, %38, %39, %40, %41, %42, %43, %44, %45, %46, %47, %48, %49, %50, %51, %52, %53, %54, %55, %56, %57, %58, %59, %60, %61, %62, %63}, "
        "{%64, %65, %66, %67}, %68, p, 1, 1, 1;\n}\n"
        : "+f"(d[0]), "+f"(d[1]), "+f"(d[2]), "+f"(d[3]), "+f"(d[4]), "+f"(d[5]), "+f"(d[6]), "+f"(d[7]), "+f"(d[8]), "+f"(d[9]), "+f"(d[10]), "+f"(d[11]), "+f"(d[12]), "+f"(d[13]), "+f"(d[14]), "+f"(d[15]), "+f"(d[16]), "+f"(d[17]), "+f"(d[18]), "+f"(d[19]), "+f"(d[20]), "+f"(d[21]), "+f"(d[22]), "+f"(d[23]), "+f"(d[24]), "+f"(d[25]), "+f"(d[26]), "+f"(d[27]), "+f"(d[28]), "+f"(d[29]), "+f"(d[30]), "+f"(d[31]), "+f"(d[32]), "+f"(d[33]), "+f"(d[34]), "+f"(d[35]), "+f"(d[36]), "+f"(d[37]), "+f"(d[38]), "+f"(d[39]), "+f"(d[40]), "+f"(d[41]), "+f"(d[42]), "+f"(d[43]), "+f"(d[44]), "+f"(d[45]), "+f"(d[46]), "+f"(d[47]), "+f"(d[48]), "+f"(d[49]), "+f"(d[50]), "+f"(d[51]), "+f"(d[52]), "+f"(d[53]), "+f"(d[54]), "+f"(d[55]), "+f"(d[56]), "+f"(d[57]), "+f"(d[58]), "+f"(d[59]), "+f"(d[60]), "+f"(d[61]), "+f"(d[62]), "+f"(d[63])
        : "r"(a0), "r"(a1), "r"(a2), "r"(a3), "l"(db), "r"(sd));
}
__device__ __forceinline__ void wgmma_rs_n64_tb(float (&d)[32], uint32_t a0, uint32_t a1, uint32_t a2, uint32_t a3, uint64_t db, int sd) {
    asm volatile("{\n.reg .pred p;\nsetp.ne.b32 p, %37, 0;\n"
        "wgmma.mma_async.sync.aligned.m64n64k16.f32.bf16.bf16 "
        "{%0, %1, %2, %3, %4, %5, %6, %7, %8, %9, %10, %11, %12, %13, %14, %15, %16, %17, %18, %19, %20, %21, %22, %23, %24, %25, %26, %27, %28, %29, %30, %31}, "
        "{%32, %33, %34, %35}, %36, p, 1, 1, 1;\n}\n"
        : "+f"(d[0]), "+f"(d[1]), "+f"(d[2]), "+f"(d[3]), "+f"(d[4]), "+f"(d[5]), "+f"(d[6]), "+f"(d[7]), "+f"(d[8]), "+f"(d[9]), "+f"(d[10]), "+f"(d[11]), "+f"(d[12]), "+f"(d[13]), "+f"(d[14]), "+f"(d[15]), "+f"(d[16]), "+f"(d[17]), "+f"(d[18]), "+f"(d[19]), "+f"(d[20]), "+f"(d[21]), "+f"(d[22]), "+f"(d[23]), "+f"(d[24]), "+f"(d[25]), "+f"(d[26]), "+f"(d[27]), "+f"(d[28]), "+f"(d[29]), "+f"(d[30]), "+f"(d[31])
        : "r"(a0), "r"(a1), "r"(a2), "r"(a3), "l"(db), "r"(sd));
}

__global__ void __launch_bounds__(384, 1) fused_gqa_kernel(const __grid_constant__ Params P) {
    extern __shared__ uint8_t smem_raw[];
    const uint32_t base = (smem_u32(smem_raw) + 1023u) & ~1023u;
    const uint32_t smR = base;
    const uint32_t smS = base + R_BYTES;
    const uint32_t bars = smS + NSTAGE * STAGE_BYTES;
    const uint32_t prog = bars + 8 * (2 * NSTAGE + 10);
    const int tid = threadIdx.x;
    const int wid = __shfl_sync(0xffffffffu, tid >> 5, 0);
    const int lane = tid & 31;

    const int cta = blockIdx.x;
    const int blk = cta >> 6;
    const int hp = (cta >> 3) & 7;
    const int b = cta & 7;
    const int grp = blk * 8 + b;

    if (tid == 256) {
        TS(0);
        asm volatile("prefetch.tensormap [%0];" ::"l"(&P.x[blk]) : "memory");
        asm volatile("prefetch.tensormap [%0];" ::"l"(&P.wq[blk]) : "memory");
        for (int i = 0; i < NSTAGE; i++) {
            mbar_init(bars + 8 * i, 1);
            mbar_init(bars + 8 * (NSTAGE + i), 8);
        }
        for (int i = 0; i < 10; i++) mbar_init(bars + 8 * (2 * NSTAGE + i), 4);
        asm volatile("st.volatile.shared.u32 [%0], %1;" ::"r"(prog), "r"(0) : "memory");
        asm volatile("fence.mbarrier_init.release.cluster;" ::: "memory");
        asm volatile("fence.proxy.async.shared::cta;" ::: "memory");
#pragma unroll
        for (int s = 0; s < NSTAGE; s++) {
            const uint32_t fb = bars + 8 * s;
            const uint32_t dst = smS + s * STAGE_BYTES;
            mbar_expect_tx(fb, (s & 1) ? STAGE_BYTES : STAGE_BYTES + 8192);
            if (!(s & 1)) tma_2d(smR + (s >> 1) * 8192, &P.x[blk], (s >> 1) * 64, b * 64, fb);
#pragma unroll
            for (int p = 0; p < 4; p++) tma_3d(dst + p * 8192, &P.wq[blk], 0, s * 32, hp * 8 + (p & 1) * 4 + (p >> 1) * 2, fb);
        }
        asm volatile("prefetch.tensormap [%0];" ::"l"(&P.k[blk]) : "memory");
        asm volatile("prefetch.tensormap [%0];" ::"l"(&P.v[blk]) : "memory");
        asm volatile("prefetch.tensormap [%0];" ::"l"(&P.wo[blk]) : "memory");
        asm volatile("prefetch.tensormap [%0];" ::"l"(&P.wo8[blk]) : "memory");
    }
    __syncthreads();

    if (wid >= 8) {
        asm volatile("setmaxnreg.dec.sync.aligned.u32 40;");
        if (wid == 8) {
            if (lane == 0) {
                int slot = 0, ph = 0;
                for (int s = NSTAGE; s < N_WQ; s++) {
                    const uint32_t fb = bars + 8 * slot;
                    mbar_wait(bars + 8 * (NSTAGE + slot), ph);
                    const uint32_t dst = smS + slot * STAGE_BYTES;
                    mbar_expect_tx(fb, (s & 1) ? STAGE_BYTES : STAGE_BYTES + 8192);
                    if (!(s & 1)) tma_2d(smR + ((s >> 1) & 7) * 8192, &P.x[blk], (s >> 1) * 64, b * 64, fb);
#pragma unroll
                    for (int p = 0; p < 4; p++) {
                        const int w = p >> 1, j = p & 1;
                        tma_3d(dst + p * 8192, &P.wq[blk], 0, s * 32, hp * 8 + j * 4 + w * 2, fb);
                    }
                    if (++slot == NSTAGE) { slot = 0; ph ^= 1; }
                }
                int lim = NSTAGE;
                for (int i = 0; i < 34; i++) {
                    const int u = (i >= 17), r = i - 17 * u;
                    const bool extra = (i == 28) || (i == 33);
                    const int sl = extra ? ((i == 28) ? 3 : 4) : slot;
                    const uint32_t fb = bars + 8 * sl;
                    mbar_wait(bars + 8 * (NSTAGE + sl), extra ? 1 : ph);
                    const uint32_t dst = smS + sl * STAGE_BYTES;
                    mbar_expect_tx(fb, STAGE_BYTES);
                    if (r < 8) {
                        const int row = (b * kHkv + hp * 2 + u) * kSk + (r >> 1) * 128;
                        tma_3d(dst, (r & 1) ? &P.v[blk] : &P.k[blk], 0, row, 0, fb);
                    } else {
                        const int q = r - 8, row = hp * 512 + u * 256;
                        if (q < 8) {
                            tma_3d(dst, &P.wo[blk], 0, row + (q & 3) * 64, (q >> 2) * 4, fb);
                            tma_3d(dst + 16384, &P.wo[blk], 0, row + ((q & 3) ^ 2) * 64, (q >> 2) * 4 + 2, fb);
                        } else {
                            tma_2d(dst, &P.wo8[blk], 512, row, fb);
                            tma_2d(dst + 16384, &P.wo8[blk], 512, row + 128, fb);
                        }
                    }
                    asm volatile("st.volatile.shared.u32 [%0], %1;" ::"r"(prog), "r"(i + 1) : "memory");
                    if (i == 7) lim = 3;
                    if (!extra && ++slot == lim) { slot = 0; ph ^= 1; }
                }
            }
        } else if (wid == 11) {
            if (PF_DIST > 0) {
                uint32_t sink = 0;
                mbar_wait(bars, 0);
                if (PF_WQ) {
                    const char* wqs = (const char*)(P.wqp[blk] + hp * 512) + (size_t)(160 + b * 52) * 8192;
#pragma unroll
                    for (int h = 0; h < 2; h++) {
#pragma unroll
                        for (int j = 0; j < 4; j++) {
                            const int e = (h * 4 + j) * 32 + lane;
                            if (e < 208) sink |= l2_touch(wqs + (size_t)(e >> 2) * 8192 + (e & 3) * 256);
                        }
                        if (sink == 0x9E3779B9u) asm volatile("st.volatile.shared.u32 [%0], %1;" ::"r"(prog + 4), "r"(sink) : "memory");
                    }
                }
                const char* kbase = (const char*)(P.kp[blk] + (size_t)(b * kHkv + hp * 2) * kSk * kDh);
                const char* vbase = (const char*)(P.vp[blk] + (size_t)(b * kHkv + hp * 2) * kSk * kDh);
                const char* wos = (const char*)(P.wop[blk] + (size_t)hp * 512 * kD) + (size_t)b * 36864;
                for (int i = 0; i < 18; i++) {
                    const int u = (i >= 9), r = i - 9 * u;
                    const int pos = u ? (PF_POS1 + r) : r;
                    if (pos >= PF_DIST) {
                        uint32_t pr, n = 0;
                        while (true) {
                            asm volatile("ld.volatile.shared.u32 %0, [%1];" : "=r"(pr) : "r"(prog) : "memory");
                            const int prk = ((int)pr <= 8) ? (int)pr : (((int)pr <= 17) ? 8 + (((int)pr - 8) * (PF_POS1 - 8)) / 9 : (int)pr - 17 + PF_POS1);
                            if (prk + PF_DIST >= pos) break;
                            if (++n > (1u << 22)) break;
                            __nanosleep(100);
                        }
                    }
                    if (r < 8) {
                        const char* p = ((r & 1) ? vbase : kbase) + (size_t)(u * 4 + (r >> 1)) * 32768 + lane * 256;
#pragma unroll
                        for (int j = 0; j < 4; j++) sink |= l2_touch(p + j * 8192);
                    } else {
                        const char* p = wos + (size_t)u * 294912 + lane * 256;
#pragma unroll
                        for (int j = 0; j < 5; j++) if (j * 32 + lane < 144) sink |= l2_touch(p + j * 8192);
                    }
                    if (sink == 0x9E3779B9u) asm volatile("st.volatile.shared.u32 [%0], %1;" ::"r"(prog + 4), "r"(sink) : "memory");
                }
            }
        } else {
            const int hw = wid - 9;
            for (int k = 0; k < 3; k++) {
                mbar_wait(bars + 8 * (2 * NSTAGE + hw * 5 + k), 0);
                const int c = (k < 2) ? (2 * k + hw) : 4;
                asm volatile("fence.acq_rel.gpu;" ::: "memory");
                asm volatile("red.relaxed.gpu.global.add.u32 [%0], 1;" ::"l"(&g_cnt[(grp * 9 + c) * 32 + lane]) : "memory");
            }
        }
    } else {
        asm volatile("setmaxnreg.inc.sync.aligned.u32 232;");
        const int w = wid >> 2;
        const int t = tid & 127;
        int slot = 0, ph = 0, lim = NSTAGE;
        uint32_t qf[8][4];
        const uint32_t stash = smR + (1 + w) * 16384 + t * 16;
        {
            float acc[128];
            int pslot = 0;
            for (int s = 0; s < N_WQ; s++) {
                mbar_wait(bars + 8 * slot, ph);
                if (tid == 0 && s == 0) TS(20);
                if (tid == 0 && s == 5) TS(21);
                if (tid == 0 && s == 10) TS(22);
                const uint64_t da = mk_desc(smR + ((s >> 1) & 7) * 8192 + (s & 1) * 64, 16, 1024);
                const uint64_t db = mk_desc(smS + slot * STAGE_BYTES + w * 16384, 4096, 1024);
                wg_fence();
                wgmma_ss_n256_tb(acc, da, db, s != 0);
                wgmma_ss_n256_tb(acc, da + 2, db + 128, 1);
                wg_commit();
                wg_wait<0>();
                if (lane == 0) mbar_arrive(bars + 8 * (NSTAGE + slot));
                pslot = slot;
                if (++slot == NSTAGE) { slot = 0; ph ^= 1; }
            }
            fence_regs(acc);
            if (tid == 0) TS(1);
#pragma unroll
            for (int kk = 0; kk < 8; kk++) {
#pragma unroll
                for (int i = 0; i < 4; i++) qf[kk][i] = pack_bf16(acc[8 * kk + 2 * i], acc[8 * kk + 2 * i + 1]);
                sts128(stash + kk * 2048,
                       pack_bf16(acc[64 + 8 * kk + 0], acc[64 + 8 * kk + 1]), pack_bf16(acc[64 + 8 * kk + 2], acc[64 + 8 * kk + 3]),
                       pack_bf16(acc[64 + 8 * kk + 4], acc[64 + 8 * kk + 5]), pack_bf16(acc[64 + 8 * kk + 6], acc[64 + 8 * kk + 7]));
            }
        }
        if (w == 1) bar_arrive<5, 256>();
        const float sc = 0.08838834764831845f * 1.4426950408889634f;
        uint2* dst0 = g_part + (size_t)(grp * 80 + 2 * w * 8 + hp) * 1024 + t;
        uint2* dst8 = g_part + (size_t)(grp * 80 + 64 + hp * 2 + w) * 1024 + t;
#pragma unroll
        for (int u = 0; u < 2; u++) {
            uint32_t af[16][4];
            {
                float o[64], s[64];
                float m0 = -INFINITY, m1 = -INFINITY, l0 = 0.f, l1 = 0.f;
                uint32_t pf[8][4];
#pragma unroll
                for (int i = 0; i < 64; i++) { o[i] = 0.f; s[i] = 0.f; }
#pragma unroll
                for (int i = 0; i < 32; i++) pf[i >> 2][i & 3] = 0u;
#pragma unroll 1
                for (int tt = 0; tt <= 4; tt++) {
                    int vslot = slot;
                    if (tt > 0) {
                        mbar_wait(bars + 8 * slot, ph);
                        if (++slot == lim) { slot = 0; ph ^= 1; }
                    }
                    if (tt < 4) mbar_wait(bars + 8 * slot, ph);
                    if (tid == 0) TS(32 + u * 20 + tt * 4);
                    if (w == 0) bar_sync<5, 256>(); else bar_sync<6, 256>();
                    wg_fence();
                    if (tt > 0) {
                        const uint64_t db = mk_desc(smS + vslot * STAGE_BYTES, 16384, 1024);
#pragma unroll
                        for (int kk = 0; kk < 8; kk++)
                            wgmma_rs_n128_tb(o, pf[kk][0], pf[kk][1], pf[kk][2], pf[kk][3], db + kk * 128, (tt > 1) || (kk != 0));
                        wg_commit();
                    }
                    if (tt < 4) {
                        const uint64_t db = mk_desc(smS + slot * STAGE_BYTES, 16, 1024);
#pragma unroll
                        for (int kk = 0; kk < 8; kk++)
                            wgmma_rs_n128(s, qf[kk][0], qf[kk][1], qf[kk][2], qf[kk][3], db + (kk >> 2) * 1024 + (kk & 3) * 2, kk != 0);
                        wg_commit();
                    }
                    if (w == 0) bar_arrive<6, 256>(); else if (!(u == 1 && tt == 4)) bar_arrive<5, 256>();
                    if (tid == 0) TS(32 + u * 20 + tt * 4 + 1);
                    wg_wait<0>();
                    fence_regs(o);
                    fence_regs(s);
                    if (tid == 0) TS(32 + u * 20 + tt * 4 + 2);
                    if (tt > 0 && lane == 0) mbar_arrive(bars + 8 * (NSTAGE + vslot));
                    if (tt == 4) break;
                    if (lane == 0) mbar_arrive(bars + 8 * (NSTAGE + slot));
                    if (++slot == lim) { slot = 0; ph ^= 1; }
                    float mx0 = s[0], mx1 = s[2];
#pragma unroll
                    for (int j = 0; j < 16; j++) {
                        mx0 = fmaxf(mx0, fmaxf(s[4 * j], s[4 * j + 1]));
                        mx1 = fmaxf(mx1, fmaxf(s[4 * j + 2], s[4 * j + 3]));
                    }
                    mx0 = fmaxf(mx0, __shfl_xor_sync(0xffffffffu, mx0, 1));
                    mx1 = fmaxf(mx1, __shfl_xor_sync(0xffffffffu, mx1, 1));
                    mx0 = fmaxf(mx0, __shfl_xor_sync(0xffffffffu, mx0, 2));
                    mx1 = fmaxf(mx1, __shfl_xor_sync(0xffffffffu, mx1, 2));
                    const float mn0 = fmaxf(m0, mx0), mn1 = fmaxf(m1, mx1);
                    const float al0 = ex2((m0 - mn0) * sc), al1 = ex2((m1 - mn1) * sc);
                    m0 = mn0; m1 = mn1;
                    const float ms0 = mn0 * sc, ms1 = mn1 * sc;
                    float rs0 = 0.f, rs1 = 0.f;
#pragma unroll
                    for (int j = 0; j < 16; j++) {
                        const float p0 = ex2(fmaf(s[4 * j], sc, -ms0)), p1 = ex2(fmaf(s[4 * j + 1], sc, -ms0));
                        const float p2 = ex2(fmaf(s[4 * j + 2], sc, -ms1)), p3 = ex2(fmaf(s[4 * j + 3], sc, -ms1));
                        rs0 += p0 + p1; rs1 += p2 + p3;
                        pf[j >> 1][(j & 1) * 2] = pack_bf16(p0, p1);
                        pf[j >> 1][(j & 1) * 2 + 1] = pack_bf16(p2, p3);
                    }
                    l0 = l0 * al0 + rs0; l1 = l1 * al1 + rs1;
                    if (tt > 0) {
#pragma unroll
                        for (int j = 0; j < 16; j++) { o[4 * j] *= al0; o[4 * j + 1] *= al0; o[4 * j + 2] *= al1; o[4 * j + 3] *= al1; }
                    }
                    if (tid == 0) TS(32 + u * 20 + tt * 4 + 3);
                }
                if (tid == 0) TS(2 + u);
                l0 += __shfl_xor_sync(0xffffffffu, l0, 1);
                l1 += __shfl_xor_sync(0xffffffffu, l1, 1);
                l0 += __shfl_xor_sync(0xffffffffu, l0, 2);
                l1 += __shfl_xor_sync(0xffffffffu, l1, 2);
                const float i0 = 1.f / l0, i1 = 1.f / l1;
                const uint32_t zown = smR + (w ? 3 : 0) * 16384 + t * 16;
#pragma unroll
                for (int kk = 0; kk < 8; kk++) {
                    af[kk][0] = pack_bf16(o[8 * kk + 0] * i0, o[8 * kk + 1] * i0);
                    af[kk][1] = pack_bf16(o[8 * kk + 2] * i1, o[8 * kk + 3] * i1);
                    af[kk][2] = pack_bf16(o[8 * kk + 4] * i0, o[8 * kk + 5] * i0);
                    af[kk][3] = pack_bf16(o[8 * kk + 6] * i1, o[8 * kk + 7] * i1);
                    sts128(zown + kk * 2048, af[kk][0], af[kk][1], af[kk][2], af[kk][3]);
                }
            }
            if (w == 0) bar_arrive<7, 256>(); else bar_arrive<8, 256>();
            lim = 3;
            if (u == 0) {
#pragma unroll
                for (int kk = 0; kk < 8; kk++) lds128(stash + kk * 2048, qf[kk]);
            }
            uint32_t nx[8][4];
#pragma unroll
            for (int ps = 0; ps < 2; ps++) {
                float acc[64];
                const uint32_t keep = smS + (3 + ps) * STAGE_BYTES + w * 16384 + t * 16;
                if (u == 0) {
#pragma unroll
                    for (int i = 0; i < 64; i++) acc[i] = 0.f;
                } else {
                    if (ps == 0) {
#pragma unroll
                        for (int j = 0; j < 8; j++) lds128(keep + j * 2048, nx[j]);
                        asm volatile("fence.proxy.async.shared::cta;" ::: "memory");
                        __syncwarp();
                        if (lane == 0) mbar_arrive(bars + 8 * (NSTAGE + 3));
                    }
#pragma unroll
                    for (int j = 0; j < 8; j++)
#pragma unroll
                        for (int i = 0; i < 4; i++) { acc[8 * j + 2 * i] = __uint_as_float(nx[j][i] << 16); acc[8 * j + 2 * i + 1] = __uint_as_float(nx[j][i] & 0xffff0000u); }
                }
#pragma unroll
                for (int st = 0; st < 4; st++) {
                    if (ps == 0 && st == 2) {
                        if (w == 0) bar_sync<8, 256>(); else bar_sync<7, 256>();
#pragma unroll
                        for (int kk = 0; kk < 8; kk++) lds128(smR + (w ? 0 : 3) * 16384 + kk * 2048 + t * 16, af[8 + kk]);
                    }
                    const bool extra = (u == 1) && (ps == 0 && st == 3);
                    const int sl = extra ? (3 + ps) : slot;
                    if (tid == 0) TS(80 + u * 24 + (ps * 4 + st) * 3);
                    mbar_wait(bars + 8 * sl, extra ? 1 : ph);
                    if (tid == 0) TS(80 + u * 24 + (ps * 4 + st) * 3 + 1);
                    const uint64_t db = mk_desc(smS + sl * STAGE_BYTES + w * 16384, 8192, 1024);
                    wg_fence();
#pragma unroll
                    for (int kk = 0; kk < 4; kk++)
                        wgmma_rs_n128_tb(acc, af[st * 4 + kk][0], af[st * 4 + kk][1], af[st * 4 + kk][2], af[st * 4 + kk][3], db + kk * 128, 1);
                    wg_commit();
                    if (u == 1 && st == 1) {
                        if (ps == 0) {
#pragma unroll
                            for (int j = 0; j < 8; j++) lds128(keep + STAGE_BYTES + j * 2048, nx[j]);
                            asm volatile("fence.proxy.async.shared::cta;" ::: "memory");
                            __syncwarp();
                            if (lane == 0) mbar_arrive(bars + 8 * (NSTAGE + 4));
                        } else {
#pragma unroll
                            for (int j = 0; j < 4; j++) lds128(stash + j * 2048, nx[j]);
                        }
                    }
                    wg_wait<0>();
                    if (tid == 0) TS(80 + u * 24 + (ps * 4 + st) * 3 + 2);
                    if (!extra) {
                        if (lane == 0) mbar_arrive(bars + 8 * (NSTAGE + slot));
                        if (++slot == 3) { slot = 0; ph ^= 1; }
                    }
                }
                fence_regs(acc);
                if (u == 0) {
#pragma unroll
                    for (int j = 0; j < 8; j++)
                        sts128(keep + j * 2048, pack_bf16(acc[8 * j], acc[8 * j + 1]), pack_bf16(acc[8 * j + 2], acc[8 * j + 3]),
                               pack_bf16(acc[8 * j + 4], acc[8 * j + 5]), pack_bf16(acc[8 * j + 6], acc[8 * j + 7]));
                } else {
                    uint2* dst = dst0 + (size_t)ps * 32 * 1024;
#pragma unroll
                    for (int j = 0; j < 16; j++)
                        __stcg(dst + (j >> 3) * 8192 + (j & 7) * 128, make_uint2(pack_bf16(acc[4 * j], acc[4 * j + 1]), pack_bf16(acc[4 * j + 2], acc[4 * j + 3])));
                    __syncwarp();
                    if (lane == 0) mbar_arrive(bars + 8 * (2 * NSTAGE + w * 5 + ps));
                }
                if (tid == 0) TS(4 + u * 8 + ps);
            }
            {
                float acc[32];
                if (u == 0) {
#pragma unroll
                    for (int i = 0; i < 32; i++) acc[i] = 0.f;
                } else {
#pragma unroll
                    for (int j = 0; j < 4; j++)
#pragma unroll
                        for (int i = 0; i < 4; i++) { acc[8 * j + 2 * i] = __uint_as_float(nx[j][i] << 16); acc[8 * j + 2 * i + 1] = __uint_as_float(nx[j][i] & 0xffff0000u); }
                }
                const int sl = u ? 4 : slot;
                mbar_wait(bars + 8 * sl, u ? 1 : ph);
                const uint64_t db = mk_desc(smS + sl * STAGE_BYTES + w * 16384, 8192, 1024);
                wg_fence();
#pragma unroll
                for (int kk = 0; kk < 8; kk++)
                    wgmma_rs_n64_tb(acc, af[kk][0], af[kk][1], af[kk][2], af[kk][3], db + kk * 128, 1);
                wg_commit();
                wg_wait<0>();
                if (u == 0) {
                    if (lane == 0) mbar_arrive(bars + 8 * (NSTAGE + slot));
                    if (++slot == 3) { slot = 0; ph ^= 1; }
                }
                fence_regs(acc);
                if (u == 0) {
#pragma unroll
                    for (int j = 0; j < 4; j++)
                        sts128(stash + j * 2048, pack_bf16(acc[8 * j], acc[8 * j + 1]), pack_bf16(acc[8 * j + 2], acc[8 * j + 3]),
                               pack_bf16(acc[8 * j + 4], acc[8 * j + 5]), pack_bf16(acc[8 * j + 6], acc[8 * j + 7]));
                } else {
#pragma unroll
                    for (int j = 0; j < 8; j++)
                        __stcg(dst8 + j * 128, make_uint2(pack_bf16(acc[4 * j], acc[4 * j + 1]), pack_bf16(acc[4 * j + 2], acc[4 * j + 3])));
                    __syncwarp();
                    if (lane == 0) mbar_arrive(bars + 8 * (2 * NSTAGE + w * 5 + 2));
                }
                if (tid == 0) TS(6 + u * 8);
            }
        }
        {
            __nv_bfloat16* orow = P.out + (size_t)(b * 64 + (t >> 5) * 16 + (lane >> 2)) * (2 * kD) + blk * kD + hp * 8 + (lane & 3) * 2;
#pragma unroll
            for (int g = 0; g < 3; g++) {
                if (g == 2 && w != 0) break;
                if (lane == 0) {
                    unsigned* cp = &g_cnt[(grp * 9 + ((g < 2) ? (2 * g + w) : 4)) * 32 + hp * 4 + (wid & 3)];
                    unsigned v, n = 0;
                    while (true) {
                        asm volatile("ld.acquire.gpu.global.u32 %0, [%1];" : "=r"(v) : "l"(cp) : "memory");
                        if (v >= ((g < 2) ? 8u : 16u)) break;
                        if (++n > (1u << 21)) break;
                    }
                    *cp = 0;
                }
                __syncwarp();
                if (tid == 0) TS(16 + g);
                const uint2* src = g_part + ((size_t)(grp * 80 + ((g < 2) ? (g * 32 + 2 * w * 8) : 64)) * 8 + hp) * 128 + t;
                uint2 v[16];
#pragma unroll
                for (int i = 0; i < 16; i++) v[i] = __ldcg(src + (size_t)i * 1024);
                float a[2][4];
#pragma unroll
                for (int h = 0; h < 2; h++) {
                    a[h][0] = a[h][1] = a[h][2] = a[h][3] = 0.f;
#pragma unroll
                    for (int i = 0; i < 8; i++) {
                        const uint2 x = v[h * 8 + i];
                        a[h][0] += __uint_as_float(x.x << 16); a[h][1] += __uint_as_float(x.x & 0xffff0000u);
                        a[h][2] += __uint_as_float(x.y << 16); a[h][3] += __uint_as_float(x.y & 0xffff0000u);
                    }
                }
                if (g < 2) {
#pragma unroll
                    for (int h = 0; h < 2; h++) {
                        *(uint32_t*)(orow + (g * 4 + 2 * w + h) * 64) = pack_bf16(a[h][0], a[h][1]);
                        *(uint32_t*)(orow + (g * 4 + 2 * w + h) * 64 + 8 * 2 * kD) = pack_bf16(a[h][2], a[h][3]);
                    }
                } else {
                    *(uint32_t*)(orow + 512) = pack_bf16(a[0][0] + a[1][0], a[0][1] + a[1][1]);
                    *(uint32_t*)(orow + 512 + 8 * 2 * kD) = pack_bf16(a[0][2] + a[1][2], a[0][3] + a[1][3]);
                }
            }
            if (tid == 0) TS(19);
        }
    }
}

typedef CUresult (*EncodeFn)(CUtensorMap*, CUtensorMapDataType, cuuint32_t, void*, const cuuint64_t*, const cuuint64_t*,
                             const cuuint32_t*, const cuuint32_t*, CUtensorMapInterleave, CUtensorMapSwizzle,
                             CUtensorMapL2promotion, CUtensorMapFloatOOBfill);

void make_map(EncodeFn fn, CUtensorMap* m, const void* ptr, uint64_t cols, uint64_t rows, uint32_t box_rows) {
    cuuint64_t dims[2] = {cols, rows};
    cuuint64_t strides[1] = {cols * 2};
    cuuint32_t box[2] = {64, box_rows};
    cuuint32_t es[2] = {1, 1};
    fn(m, CU_TENSOR_MAP_DATA_TYPE_BFLOAT16, 2, const_cast<void*>(ptr), dims, strides, box, es, CU_TENSOR_MAP_INTERLEAVE_NONE,
       CU_TENSOR_MAP_SWIZZLE_128B, CU_TENSOR_MAP_L2_PROMOTION_L2_256B, CU_TENSOR_MAP_FLOAT_OOB_FILL_NONE);
}

void make_map3(EncodeFn fn, CUtensorMap* m, const void* ptr, uint64_t cols, uint64_t rows, uint32_t box_rows, uint32_t box_groups) {
    cuuint64_t dims[3] = {64, rows, cols / 64};
    cuuint64_t strides[2] = {cols * 2, 128};
    cuuint32_t box[3] = {64, box_rows, box_groups};
    cuuint32_t es[3] = {1, 1, 1};
    fn(m, CU_TENSOR_MAP_DATA_TYPE_BFLOAT16, 3, const_cast<void*>(ptr), dims, strides, box, es, CU_TENSOR_MAP_INTERLEAVE_NONE,
       CU_TENSOR_MAP_SWIZZLE_128B, CU_TENSOR_MAP_L2_PROMOTION_L2_256B, CU_TENSOR_MAP_FLOAT_OOB_FILL_NONE);
}

}

extern "C" void kernel_launch(void* const* d_in, const int* in_sizes, int n_in, void* d_out, int out_size) {
    static EncodeFn enc = nullptr;
    if (!enc) {
        void* fn = nullptr;
        cudaDriverEntryPointQueryResult st;
        cudaGetDriverEntryPoint("cuTensorMapEncodeTiled", &fn, cudaEnableDefault, &st);
        enc = (EncodeFn)fn;
        cudaFuncSetAttribute(fused_gqa_kernel, cudaFuncAttributeMaxDynamicSharedMemorySize, SMEM_BYTES);
    }
    Params P;
    for (int blk = 0; blk < 2; blk++) {
        const void* x = d_in[blk * 5 + 0];
        const void* k = d_in[blk * 5 + 1];
        const void* v = d_in[blk * 5 + 2];
        const void* wq = d_in[blk * 5 + 3];
        const void* wo = d_in[blk * 5 + 4];
        make_map(enc, &P.x[blk], x, kD, kB * kSq, 64);
        make_map3(enc, &P.wq[blk], wq, kHq * kDh, kD, 32, 2);
        make_map3(enc, &P.k[blk], k, kDh, (uint64_t)kB * kHkv * kSk, 128, 2);
        make_map3(enc, &P.v[blk], v, kDh, (uint64_t)kB * kHkv * kSk, 128, 2);
        make_map3(enc, &P.wo[blk], wo, kD, kHq * kDh, 64, 2);
        make_map(enc, &P.wo8[blk], wo, kD, kHq * kDh, 128);
        P.wqp[blk] = (const __nv_bfloat16*)wq;
        P.kp[blk] = (const __nv_bfloat16*)k;
        P.vp[blk] = (const __nv_bfloat16*)v;
        P.wop[blk] = (const __nv_bfloat16*)wo;
    }
    P.out = (__nv_bfloat16*)d_out;
    fused_gqa_kernel<<<128, 384, SMEM_BYTES>>>(P);
}
```

```cpp
#include <cuda_runtime.h>
#include <cuda_bf16.h>
#include <cuda.h>
#include <stdint.h>

namespace {

constexpr int kB = 8, kSq = 64, kD = 576, kHq = 32, kHkv = 16, kSk = 512, kDh = 128;
constexpr int NSTAGE = 5;
constexpr int STAGE_BYTES = 32768;
constexpr int R_BYTES = 65536;
constexpr int SMEM_BYTES = R_BYTES + NSTAGE * STAGE_BYTES + 1024   + 256  ;
constexpr int N_WQ = 18;
#define PF_DIST_V 6
#define OP_WAIT0 1
#define QP_WAIT0 1
#define PF_POS1 9
#define PF_START 1
#define PF_WQ 0
#define PF_SLEEP 1000
constexpr int PF_DIST = PF_DIST_V;

struct __align__(64) Params {
    CUtensorMap x[2], wq[2], k[2], v[2], wo[2], wo8[2];
    const __nv_bfloat16* wqp[2];
    const __nv_bfloat16* kp[2];
    const __nv_bfloat16* vp[2];
    const __nv_bfloat16* wop[2];
    __nv_bfloat16* out;
};

__device__ uint2 g_part[16 * 80 * 8 * 128];
__device__ unsigned int g_cnt[16 * 9 * 32];
#define TS(k) do {} while (0)

__device__ __forceinline__ uint32_t smem_u32(const void* p) { return (uint32_t)__cvta_generic_to_shared(p); }
__device__ __forceinline__ void mbar_init(uint32_t bar, int cnt) {
    asm volatile("mbarrier.init.shared::cta.b64 [%0], %1;" ::"r"(bar), "r"(cnt));
}
__device__ __forceinline__ void mbar_expect_tx(uint32_t bar, uint32_t bytes) {
    asm volatile("mbarrier.arrive.expect_tx.shared::cta.b64 _, [%0], %1;" ::"r"(bar), "r"(bytes) : "memory");
}
__device__ __forceinline__ void mbar_arrive(uint32_t bar) {
    asm volatile("mbarrier.arrive.shared::cta.b64 _, [%0];" ::"r"(bar) : "memory");
}
__device__ __forceinline__ bool mbar_try(uint32_t bar, uint32_t parity) {
    uint32_t ok;
    asm volatile("{\n.reg .pred p;\nmbarrier.try_wait.parity.shared::cta.b64 p, [%1], %2;\nselp.u32 %0, 1, 0, p;\n}\n"
                 : "=r"(ok) : "r"(bar), "r"(parity) : "memory");
    return ok != 0;
}
__device__ __forceinline__ void mbar_wait(uint32_t bar, uint32_t parity) {
    if (mbar_try(bar, parity)) return;
    uint32_t n = 0;
    while (!mbar_try(bar, parity)) {
        if (++n > (1u << 20)) break;
    }
}
__device__ __forceinline__ void tma_2d(uint32_t dst, const CUtensorMap* tm, int c0, int c1, uint32_t bar) {
    asm volatile("cp.async.bulk.tensor.2d.shared::cluster.global.mbarrier::complete_tx::bytes [%0], [%1, {%3, %4}], [%2];"
                 ::"r"(dst), "l"(tm), "r"(bar), "r"(c0), "r"(c1) : "memory");
}
__device__ __forceinline__ void tma_3d(uint32_t dst, const CUtensorMap* tm, int c0, int c1, int c2, uint32_t bar) {
    asm volatile("cp.async.bulk.tensor.3d.shared::cluster.global.mbarrier::complete_tx::bytes [%0], [%1, {%3, %4, %5}], [%2];"
                 ::"r"(dst), "l"(tm), "r"(bar), "r"(c0), "r"(c1), "r"(c2) : "memory");
}
__device__ __forceinline__ void l2_prefetch(const void* p, uint32_t bytes) {
    asm volatile("cp.async.bulk.prefetch.L2.global [%0], %1;" ::"l"(p), "r"(bytes) : "memory");
}
__device__ __forceinline__ uint32_t l2_touch(const void* p) {
    uint32_t v;
    asm volatile("ld.global.L2::256B.b32 %0, [%1];" : "=r"(v) : "l"(p) : "memory");
    return v;
}
__device__ __forceinline__ void wg_fence() { asm volatile("wgmma.fence.sync.aligned;" ::: "memory"); }
__device__ __forceinline__ void wg_commit() { asm volatile("wgmma.commit_group.sync.aligned;" ::: "memory"); }
template <int N> __device__ __forceinline__ void wg_wait() { asm volatile("wgmma.wait_group.sync.aligned %0;" ::"n"(N) : "memory"); }
template <int N> __device__ __forceinline__ void fence_regs(float (&d)[N]) {
#pragma unroll
    for (int i = 0; i < N; i++) asm volatile("" : "+f"(d[i])::"memory");
}
__device__ __forceinline__ uint64_t mk_desc(uint32_t addr, uint32_t lbo, uint32_t sbo) {
    return (uint64_t)((addr & 0x3FFFF) >> 4) | ((uint64_t)(lbo >> 4) << 16) | ((uint64_t)(sbo >> 4) << 32) | (1ull << 62);
}
__device__ __forceinline__ uint32_t pack_bf16(float a, float b) {
    uint32_t r;
    asm("cvt.rn.bf16x2.f32 %0, %1, %2;" : "=r"(r) : "f"(b), "f"(a));
    return r;
}
__device__ __forceinline__ float ex2(float x) {
    float y;
    asm("ex2.approx.ftz.f32 %0, %1;" : "=f"(y) : "f"(x));
    return y;
}
template <int ID, int N> __device__ __forceinline__ void bar_sync() { asm volatile("bar.sync %0, %1;" ::"n"(ID), "n"(N) : "memory"); }
template <int ID, int N> __device__ __forceinline__ void bar_arrive() { asm volatile("bar.arrive %0, %1;" ::"n"(ID), "n"(N) : "memory"); }
__device__ __forceinline__ void sts128(uint32_t addr, uint32_t a, uint32_t b, uint32_t c, uint32_t d) {
    asm volatile("st.shared.v4.b32 [%0], {%1,%2,%3,%4};" ::"r"(addr), "r"(a), "r"(b), "r"(c), "r"(d) : "memory");
}
__device__ __forceinline__ void lds128(uint32_t addr, uint32_t (&r)[4]) {
    asm volatile("ld.shared.v4.b32 {%0,%1,%2,%3}, [%4];" : "=r"(r[0]), "=r"(r[1]), "=r"(r[2]), "=r"(r[3]) : "r"(addr) : "memory");
}

__device__ __forceinline__ void wgmma_ss_n256_tb(float (&d)[128], uint64_t da, uint64_t db, int sd) {
    asm volatile("{\n.reg .pred p;\nsetp.ne.b32 p, %130, 0;\n"
        "wgmma.mma_async.sync.aligned.m64n256k16.f32.bf16.bf16 "
        "{%0, %1, %2, %3, %4, %5, %6, %7, %8, %9, %10, %11, %12, %13, %14, %15, %16, %17, %18, %19, %20, %21, %22, %23, %24, %25, %26, %27, %28, %29, %30, %31, %32, %33, %34, %35, %36, %37, %38, %39, %40, %41, %42, %43, %44, %45, %46, %47, %48, %49, %50, %51, %52, %53, %54, %55, %56, %57, %58, %59, %60, %61, %62, %63, %64, %65, %66, %67, %68, %69, %70, %71, %72, %73, %74, %75, %76, %77, %78, %79, %80, %81, %82, %83, %84, %85, %86, %87, %88, %89, %90, %91, %92, %93, %94, %95, %96, %97, %98, %99, %100, %101, %102, %103, %104, %105, %106, %107, %108, %109, %110, %111, %112, %113, %114, %115, %116, %117, %118, %119, %120, %121, %122, %123, %124, %125, %126, %127}, "
        "%128, %129, p, 1, 1, 0, 1;\n}\n"
        : "+f"(d[0]), "+f"(d[1]), "+f"(d[2]), "+f"(d[3]), "+f"(d[4]), "+f"(d[5]), "+f"(d[6]), "+f"(d[7]), "+f"(d[8]), "+f"(d[9]), "+f"(d[10]), "+f"(d[11]), "+f"(d[12]), "+f"(d[13]), "+f"(d[14]), "+f"(d[15]), "+f"(d[16]), "+f"(d[17]), "+f"(d[18]), "+f"(d[19]), "+f"(d[20]), "+f"(d[21]), "+f"(d[22]), "+f"(d[23]), "+f"(d[24]), "+f"(d[25]), "+f"(d[26]), "+f"(d[27]), "+f"(d[28]), "+f"(d[29]), "+f"(d[30]), "+f"(d[31]), "+f"(d[32]), "+f"(d[33]), "+f"(d[34]), "+f"(d[35]), "+f"(d[36]), "+f"(d[37]), "+f"(d[38]), "+f"(d[39]), "+f"(d[40]), "+f"(d[41]), "+f"(d[42]), "+f"(d[43]), "+f"(d[44]), "+f"(d[45]), "+f"(d[46]), "+f"(d[47]), "+f"(d[48]), "+f"(d[49]), "+f"(d[50]), "+f"(d[51]), "+f"(d[52]), "+f"(d[53]), "+f"(d[54]), "+f"(d[55]), "+f"(d[56]), "+f"(d[57]), "+f"(d[58]), "+f"(d[59]), "+f"(d[60]), "+f"(d[61]), "+f"(d[62]), "+f"(d[63]), "+f"(d[64]), "+f"(d[65]), "+f"(d[66]), "+f"(d[67]), "+f"(d[68]), "+f"(d[69]), "+f"(d[70]), "+f"(d[71]), "+f"(d[72]), "+f"(d[73]), "+f"(d[74]), "+f"(d[75]), "+f"(d[76]), "+f"(d[77]), "+f"(d[78]), "+f"(d[79]), "+f"(d[80]), "+f"(d[81]), "+f"(d[82]), "+f"(d[83]), "+f"(d[84]), "+f"(d[85]), "+f"(d[86]), "+f"(d[87]), "+f"(d[88]), "+f"(d[89]), "+f"(d[90]), "+f"(d[91]), "+f"(d[92]), "+f"(d[93]), "+f"(d[94]), "+f"(d[95]), "+f"(d[96]), "+f"(d[97]), "+f"(d[98]), "+f"(d[99]), "+f"(d[100]), "+f"(d[101]), "+f"(d[102]), "+f"(d[103]), "+f"(d[104]), "+f"(d[105]), "+f"(d[106]), "+f"(d[107]), "+f"(d[108]), "+f"(d[109]), "+f"(d[110]), "+f"(d[111]), "+f"(d[112]), "+f"(d[113]), "+f"(d[114]), "+f"(d[115]), "+f"(d[116]), "+f"(d[117]), "+f"(d[118]), "+f"(d[119]), "+f"(d[120]), "+f"(d[121]), "+f"(d[122]), "+f"(d[123]), "+f"(d[124]), "+f"(d[125]), "+f"(d[126]), "+f"(d[127])
        : "l"(da), "l"(db), "r"(sd));
}
__device__ __forceinline__ void wgmma_rs_n128(float (&d)[64], uint32_t a0, uint32_t a1, uint32_t a2, uint32_t a3, uint64_t db, int sd) {
    asm volatile("{\n.reg .pred p;\nsetp.ne.b32 p, %69, 0;\n"
        "wgmma.mma_async.sync.aligned.m64n128k16.f32.bf16.bf16 "
        "{%0, %1, %2, %3, %4, %5, %6, %7, %8, %9, %10, %11, %12, %13, %14, %15, %16, %17, %18, %19, %20, %21, %22, %23, %24, %25, %26, %27, %28, %29, %30, %31, %32, %33, %34, %35, %36, %37, %38, %39, %40, %41, %42, %43, %44, %45, %46, %47, %48, %49, %50, %51, %52, %53, %54, %55, %56, %57, %58, %59, %60, %61, %62, %63}, "
        "{%64, %65, %66, %67}, %68, p, 1, 1, 0;\n}\n"
        : "+f"(d[0]), "+f"(d[1]), "+f"(d[2]), "+f"(d[3]), "+f"(d[4]), "+f"(d[5]), "+f"(d[6]), "+f"(d[7]), "+f"(d[8]), "+f"(d[9]), "+f"(d[10]), "+f"(d[11]), "+f"(d[12]), "+f"(d[13]), "+f"(d[14]), "+f"(d[15]), "+f"(d[16]), "+f"(d[17]), "+f"(d[18]), "+f"(d[19]), "+f"(d[20]), "+f"(d[21]), "+f"(d[22]), "+f"(d[23]), "+f"(d[24]), "+f"(d[25]), "+f"(d[26]), "+f"(d[27]), "+f"(d[28]), "+f"(d[29]), "+f"(d[30]), "+f"(d[31]), "+f"(d[32]), "+f"(d[33]), "+f"(d[34]), "+f"(d[35]), "+f"(d[36]), "+f"(d[37]), "+f"(d[38]), "+f"(d[39]), "+f"(d[40]), "+f"(d[41]), "+f"(d[42]), "+f"(d[43]), "+f"(d[44]), "+f"(d[45]), "+f"(d[46]), "+f"(d[47]), "+f"(d[48]), "+f"(d[49]), "+f"(d[50]), "+f"(d[51]), "+f"(d[52]), "+f"(d[53]), "+f"(d[54]), "+f"(d[55]), "+f"(d[56]), "+f"(d[57]), "+f"(d[58]), "+f"(d[59]), "+f"(d[60]), "+f"(d[61]), "+f"(d[62]), "+f"(d[63])
        : "r"(a0), "r"(a1), "r"(a2), "r"(a3), "l"(db), "r"(sd));
}
__device__ __forceinline__ void wgmma_rs_n128_tb(float (&d)[64], uint32_t a0, uint32_t a1, uint32_t a2, uint32_t a3, uint64_t db, int sd) {
    asm volatile("{\n.reg .pred p;\nsetp.ne.b32 p, %69, 0;\n"
        "wgmma.mma_async.sync.aligned.m64n128k16.f32.bf16.bf16 "
        "{%0, %1, %2, %3, %4, %5, %6, %7, %8, %9, %10, %11, %12, %13, %14, %15, %16, %17, %18, %19, %20, %21, %22, %23, %24, %25, %26, %27, %28, %29, %30, %31, %32, %33, %34, %35, %36, %37, %38, %39, %40, %41, %42, %43, %44, %45, %46, %47, %48, %49, %50, %51, %52, %53, %54, %55, %56, %57, %58, %59, %60, %61, %62, %63}, "
        "{%64, %65, %66, %67}, %68, p, 1, 1, 1;\n}\n"
        : "+f"(d[0]), "+f"(d[1]), "+f"(d[2]), "+f"(d[3]), "+f"(d[4]), "+f"(d[5]), "+f"(d[6]), "+f"(d[7]), "+f"(d[8]), "+f"(d[9]), "+f"(d[10]), "+f"(d[11]), "+f"(d[12]), "+f"(d[13]), "+f"(d[14]), "+f"(d[15]), "+f"(d[16]), "+f"(d[17]), "+f"(d[18]), "+f"(d[19]), "+f"(d[20]), "+f"(d[21]), "+f"(d[22]), "+f"(d[23]), "+f"(d[24]), "+f"(d[25]), "+f"(d[26]), "+f"(d[27]), "+f"(d[28]), "+f"(d[29]), "+f"(d[30]), "+f"(d[31]), "+f"(d[32]), "+f"(d[33]), "+f"(d[34]), "+f"(d[35]), "+f"(d[36]), "+f"(d[37]), "+f"(d[38]), "+f"(d[39]), "+f"(d[40]), "+f"(d[41]), "+f"(d[42]), "+f"(d[43]), "+f"(d[44]), "+f"(d[45]), "+f"(d[46]), "+f"(d[47]), "+f"(d[48]), "+f"(d[49]), "+f"(d[50]), "+f"(d[51]), "+f"(d[52]), "+f"(d[53]), "+f"(d[54]), "+f"(d[55]), "+f"(d[56]), "+f"(d[57]), "+f"(d[58]), "+f"(d[59]), "+f"(d[60]), "+f"(d[61]), "+f"(d[62]), "+f"(d[63])
        : "r"(a0), "r"(a1), "r"(a2), "r"(a3), "l"(db), "r"(sd));
}
__device__ __forceinline__ void wgmma_rs_n64_tb(float (&d)[32], uint32_t a0, uint32_t a1, uint32_t a2, uint32_t a3, uint64_t db, int sd) {
    asm volatile("{\n.reg .pred p;\nsetp.ne.b32 p, %37, 0;\n"
        "wgmma.mma_async.sync.aligned.m64n64k16.f32.bf16.bf16 "
        "{%0, %1, %2, %3, %4, %5, %6, %7, %8, %9, %10, %11, %12, %13, %14, %15, %16, %17, %18, %19, %20, %21, %22, %23, %24, %25, %26, %27, %28, %29, %30, %31}, "
        "{%32, %33, %34, %35}, %36, p, 1, 1, 1;\n}\n"
        : "+f"(d[0]), "+f"(d[1]), "+f"(d[2]), "+f"(d[3]), "+f"(d[4]), "+f"(d[5]), "+f"(d[6]), "+f"(d[7]), "+f"(d[8]), "+f"(d[9]), "+f"(d[10]), "+f"(d[11]), "+f"(d[12]), "+f"(d[13]), "+f"(d[14]), "+f"(d[15]), "+f"(d[16]), "+f"(d[17]), "+f"(d[18]), "+f"(d[19]), "+f"(d[20]), "+f"(d[21]), "+f"(d[22]), "+f"(d[23]), "+f"(d[24]), "+f"(d[25]), "+f"(d[26]), "+f"(d[27]), "+f"(d[28]), "+f"(d[29]), "+f"(d[30]), "+f"(d[31])
        : "r"(a0), "r"(a1), "r"(a2), "r"(a3), "l"(db), "r"(sd));
}

__global__ void __launch_bounds__(384, 1) fused_gqa_kernel(const __grid_constant__ Params P) {
    extern __shared__ uint8_t smem_raw[];
    const uint32_t base = (smem_u32(smem_raw) + 1023u) & ~1023u;
    const uint32_t smR = base;
    const uint32_t smS = base + R_BYTES;
    const uint32_t bars = smS + NSTAGE * STAGE_BYTES;
    const uint32_t prog = bars + 8 * (2 * NSTAGE + 10);
    const int tid = threadIdx.x;
    const int wid = __shfl_sync(0xffffffffu, tid >> 5, 0);
    const int lane = tid & 31;

    const int cta = blockIdx.x;
    const int blk = cta >> 6;
    const int hp = (cta >> 3) & 7;
    const int b = cta & 7;
    const int grp = blk * 8 + b;

    if (tid == 256) {
        TS(0);
        asm volatile("prefetch.tensormap [%0];" ::"l"(&P.x[blk]) : "memory");
        asm volatile("prefetch.tensormap [%0];" ::"l"(&P.wq[blk]) : "memory");
        for (int i = 0; i < NSTAGE; i++) {
            mbar_init(bars + 8 * i, 1);
            mbar_init(bars + 8 * (NSTAGE + i), 8);
        }
        for (int i = 0; i < 10; i++) mbar_init(bars + 8 * (2 * NSTAGE + i), 4);
        asm volatile("st.volatile.shared.u32 [%0], %1;" ::"r"(prog), "r"(0) : "memory");
        asm volatile("fence.mbarrier_init.release.cluster;" ::: "memory");
        asm volatile("fence.proxy.async.shared::cta;" ::: "memory");
#pragma unroll
        for (int s = 0; s < NSTAGE; s++) {
            const uint32_t fb = bars + 8 * s;
            const uint32_t dst = smS + s * STAGE_BYTES;
            mbar_expect_tx(fb, (s & 1) ? STAGE_BYTES : STAGE_BYTES + 8192);
            if (!(s & 1)) tma_2d(smR + (s >> 1) * 8192, &P.x[blk], (s >> 1) * 64, b * 64, fb);
#pragma unroll
            for (int p = 0; p < 4; p++) tma_3d(dst + p * 8192, &P.wq[blk], 0, s * 32, hp * 8 + (p & 1) * 4 + (p >> 1) * 2, fb);
        }
        asm volatile("prefetch.tensormap [%0];" ::"l"(&P.k[blk]) : "memory");
        asm volatile("prefetch.tensormap [%0];" ::"l"(&P.v[blk]) : "memory");
        asm volatile("prefetch.tensormap [%0];" ::"l"(&P.wo[blk]) : "memory");
        asm volatile("prefetch.tensormap [%0];" ::"l"(&P.wo8[blk]) : "memory");
    }
    __syncthreads();

    if (wid >= 8) {
        asm volatile("setmaxnreg.dec.sync.aligned.u32 40;");
        if (wid == 8) {
            if (lane == 0) {
                int slot = 0, ph = 0;
                for (int s = NSTAGE; s < N_WQ; s++) {
                    const uint32_t fb = bars + 8 * slot;
                    mbar_wait(bars + 8 * (NSTAGE + slot), ph);
                    const uint32_t dst = smS + slot * STAGE_BYTES;
                    mbar_expect_tx(fb, (s & 1) ? STAGE_BYTES : STAGE_BYTES + 8192);
                    if (!(s & 1)) tma_2d(smR + ((s >> 1) & 7) * 8192, &P.x[blk], (s >> 1) * 64, b * 64, fb);
#pragma unroll
                    for (int p = 0; p < 4; p++) {
                        const int w = p >> 1, j = p & 1;
                        tma_3d(dst + p * 8192, &P.wq[blk], 0, s * 32, hp * 8 + j * 4 + w * 2, fb);
                    }
                    if (++slot == NSTAGE) { slot = 0; ph ^= 1; }
                }
                int lim = NSTAGE;
                for (int i = 0; i < 34; i++) {
                    const int u = (i >= 17), r = i - 17 * u;
                    const bool extra = (i == 28) || (i == 33);
                    const int sl = extra ? ((i == 28) ? 3 : 4) : slot;
                    const uint32_t fb = bars + 8 * sl;
                    mbar_wait(bars + 8 * (NSTAGE + sl), extra ? 1 : ph);
                    const uint32_t dst = smS + sl * STAGE_BYTES;
                    mbar_expect_tx(fb, STAGE_BYTES);
                    if (r < 8) {
                        const int row = (b * kHkv + hp * 2 + u) * kSk + (r >> 1) * 128;
                        tma_3d(dst, (r & 1) ? &P.v[blk] : &P.k[blk], 0, row, 0, fb);
                    } else {
                        const int q = r - 8, row = hp * 512 + u * 256;
                        if (q < 8) {
                            tma_3d(dst, &P.wo[blk], 0, row + (q & 3) * 64, (q >> 2) * 4, fb);
                            tma_3d(dst + 16384, &P.wo[blk], 0, row + ((q & 3) ^ 2) * 64, (q >> 2) * 4 + 2, fb);
                        } else {
                            tma_2d(dst, &P.wo8[blk], 512, row, fb);
                            tma_2d(dst + 16384, &P.wo8[blk], 512, row + 128, fb);
                        }
                    }
                    asm volatile("st.volatile.shared.u32 [%0], %1;" ::"r"(prog), "r"(i + 1) : "memory");
                    if (i == 7) lim = 3;
                    if (!extra && ++slot == lim) { slot = 0; ph ^= 1; }
                }
            }
        } else if (wid == 11) {
            if (PF_DIST > 0) {
                uint32_t sink = 0;
                mbar_wait(bars, 0);
                if (PF_WQ) {
                    const char* wqs = (const char*)(P.wqp[blk] + hp * 512) + (size_t)(160 + b * 52) * 8192;
#pragma unroll
                    for (int h = 0; h < 2; h++) {
#pragma unroll
                        for (int j = 0; j < 4; j++) {
                            const int e = (h * 4 + j) * 32 + lane;
                            if (e < 208) sink |= l2_touch(wqs + (size_t)(e >> 2) * 8192 + (e & 3) * 256);
                        }
                        if (sink == 0x9E3779B9u) asm volatile("st.volatile.shared.u32 [%0], %1;" ::"r"(prog + 4), "r"(sink) : "memory");
                    }
                }
                const char* kbase = (const char*)(P.kp[blk] + (size_t)(b * kHkv + hp * 2) * kSk * kDh);
                const char* vbase = (const char*)(P.vp[blk] + (size_t)(b * kHkv + hp * 2) * kSk * kDh);
                const char* wos = (const char*)(P.wop[blk] + (size_t)hp * 512 * kD) + (size_t)b * 36864;
                for (int i = 0; i < 18; i++) {
                    const int u = (i >= 9), r = i - 9 * u;
                    const int pos = u ? (PF_POS1 + r) : r;
                    if (pos >= PF_DIST) {
                        uint32_t pr, n = 0;
                        while (true) {
                            asm volatile("ld.volatile.shared.u32 %0, [%1];" : "=r"(pr) : "r"(prog) : "memory");
                            const int prk = ((int)pr <= 8) ? (int)pr : (((int)pr <= 17) ? 8 + (((int)pr - 8) * (PF_POS1 - 8)) / 9 : (int)pr - 17 + PF_POS1);
                            if (prk + PF_DIST >= pos) break;
                            if (++n > (1u << 22)) break;
                            __nanosleep(100);
                        }
                    }
                    if (r < 8) {
                        const char* p = ((r & 1) ? vbase : kbase) + (size_t)(u * 4 + (r >> 1)) * 32768 + lane * 256;
#pragma unroll
                        for (int j = 0; j < 4; j++) sink |= l2_touch(p + j * 8192);
                    } else {
                        const char* p = wos + (size_t)u * 294912 + lane * 256;
#pragma unroll
                        for (int j = 0; j < 5; j++) if (j * 32 + lane < 144) sink |= l2_touch(p + j * 8192);
                    }
                    if (sink == 0x9E3779B9u) asm volatile("st.volatile.shared.u32 [%0], %1;" ::"r"(prog + 4), "r"(sink) : "memory");
                }
            }
        } else {
            const int hw = wid - 9;
            for (int k = 0; k < 3; k++) {
                mbar_wait(bars + 8 * (2 * NSTAGE + hw * 5 + k), 0);
                const int c = (k < 2) ? (2 * k + hw) : 4;
                asm volatile("fence.acq_rel.gpu;" ::: "memory");
                asm volatile("red.relaxed.gpu.global.add.u32 [%0], 1;" ::"l"(&g_cnt[(grp * 9 + c) * 32 + lane]) : "memory");
            }
        }
    } else {
        asm volatile("setmaxnreg.inc.sync.aligned.u32 232;");
        const int w = wid >> 2;
        const int t = tid & 127;
        int slot = 0, ph = 0, lim = NSTAGE;
        uint32_t qf[8][4];
        const uint32_t stash = smR + (1 + w) * 16384 + t * 16;
        {
            float acc[128];
            int pslot = 0;
            for (int s = 0; s < N_WQ; s++) {
                mbar_wait(bars + 8 * slot, ph);
                if (tid == 0 && s == 0) TS(20);
                if (tid == 0 && s == 5) TS(21);
                if (tid == 0 && s == 10) TS(22);
                const uint64_t da = mk_desc(smR + ((s >> 1) & 7) * 8192 + (s & 1) * 64, 16, 1024);
                const uint64_t db = mk_desc(smS + slot * STAGE_BYTES + w * 16384, 4096, 1024);
                wg_fence();
                wgmma_ss_n256_tb(acc, da, db, s != 0);
                wgmma_ss_n256_tb(acc, da + 2, db + 128, 1);
                wg_commit();
                wg_wait<0>();
                if (lane == 0) mbar_arrive(bars + 8 * (NSTAGE + slot));
                pslot = slot;
                if (++slot == NSTAGE) { slot = 0; ph ^= 1; }
            }
            fence_regs(acc);
            if (tid == 0) TS(1);
#pragma unroll
            for (int kk = 0; kk < 8; kk++) {
#pragma unroll
                for (int i = 0; i < 4; i++) qf[kk][i] = pack_bf16(acc[8 * kk + 2 * i], acc[8 * kk + 2 * i + 1]);
                sts128(stash + kk * 2048,
                       pack_bf16(acc[64 + 8 * kk + 0], acc[64 + 8 * kk + 1]), pack_bf16(acc[64 + 8 * kk + 2], acc[64 + 8 * kk + 3]),
                       pack_bf16(acc[64 + 8 * kk + 4], acc[64 + 8 * kk + 5]), pack_bf16(acc[64 + 8 * kk + 6], acc[64 + 8 * kk + 7]));
            }
        }
        if (w == 1) bar_arrive<5, 256>();
        const float sc = 0.08838834764831845f * 1.4426950408889634f;
        uint2* dst0 = g_part + (size_t)(grp * 80 + 2 * w * 8 + hp) * 1024 + t;
        uint2* dst8 = g_part + (size_t)(grp * 80 + 64 + hp * 2 + w) * 1024 + t;
#pragma unroll
        for (int u = 0; u < 2; u++) {
            uint32_t af[16][4];
            {
                float o[64], s[64];
                float m0 = -INFINITY, m1 = -INFINITY, l0 = 0.f, l1 = 0.f;
                uint32_t pf[8][4];
#pragma unroll
                for (int i = 0; i < 64; i++) { o[i] = 0.f; s[i] = 0.f; }
#pragma unroll
                for (int i = 0; i < 32; i++) pf[i >> 2][i & 3] = 0u;
#pragma unroll 1
                for (int tt = 0; tt <= 4; tt++) {
                    int vslot = slot;
                    if (tt > 0) {
                        mbar_wait(bars + 8 * slot, ph);
                        if (++slot == lim) { slot = 0; ph ^= 1; }
                    }
                    if (tt < 4) mbar_wait(bars + 8 * slot, ph);
                    if (tid == 0) TS(32 + u * 20 + tt * 4);
                    if (w == 0) bar_sync<5, 256>(); else bar_sync<6, 256>();
                    wg_fence();
                    if (tt > 0) {
                        const uint64_t db = mk_desc(smS + vslot * STAGE_BYTES, 16384, 1024);
#pragma unroll
                        for (int kk = 0; kk < 8; kk++)
                            wgmma_rs_n128_tb(o, pf[kk][0], pf[kk][1], pf[kk][2], pf[kk][3], db + kk * 128, (tt > 1) || (kk != 0));
                        wg_commit();
                    }
                    if (tt < 4) {
                        const uint64_t db = mk_desc(smS + slot * STAGE_BYTES, 16, 1024);
#pragma unroll
                        for (int kk = 0; kk < 8; kk++)
                            wgmma_rs_n128(s, qf[kk][0], qf[kk][1], qf[kk][2], qf[kk][3], db + (kk >> 2) * 1024 + (kk & 3) * 2, kk != 0);
                        wg_commit();
                    }
                    if (w == 0) bar_arrive<6, 256>(); else if (!(u == 1 && tt == 4)) bar_arrive<5, 256>();
                    if (tid == 0) TS(32 + u * 20 + tt * 4 + 1);
                    wg_wait<0>();
                    fence_regs(o);
                    fence_regs(s);
                    if (tid == 0) TS(32 + u * 20 + tt * 4 + 2);
                    if (tt > 0 && lane == 0) mbar_arrive(bars + 8 * (NSTAGE + vslot));
                    if (tt == 4) break;
                    if (lane == 0) mbar_arrive(bars + 8 * (NSTAGE + slot));
                    if (++slot == lim) { slot = 0; ph ^= 1; }
                    float mx0 = s[0], mx1 = s[2];
#pragma unroll
                    for (int j = 0; j < 16; j++) {
                        mx0 = fmaxf(mx0, fmaxf(s[4 * j], s[4 * j + 1]));
                        mx1 = fmaxf(mx1, fmaxf(s[4 * j + 2], s[4 * j + 3]));
                    }
                    mx0 = fmaxf(mx0, __shfl_xor_sync(0xffffffffu, mx0, 1));
                    mx1 = fmaxf(mx1, __shfl_xor_sync(0xffffffffu, mx1, 1));
                    mx0 = fmaxf(mx0, __shfl_xor_sync(0xffffffffu, mx0, 2));
                    mx1 = fmaxf(mx1, __shfl_xor_sync(0xffffffffu, mx1, 2));
                    const float mn0 = fmaxf(m0, mx0), mn1 = fmaxf(m1, mx1);
                    const float al0 = ex2((m0 - mn0) * sc), al1 = ex2((m1 - mn1) * sc);
                    m0 = mn0; m1 = mn1;
                    const float ms0 = mn0 * sc, ms1 = mn1 * sc;
                    float rs0 = 0.f, rs1 = 0.f;
#pragma unroll
                    for (int j = 0; j < 16; j++) {
                        const float p0 = ex2(fmaf(s[4 * j], sc, -ms0)), p1 = ex2(fmaf(s[4 * j + 1], sc, -ms0));
                        const float p2 = ex2(fmaf(s[4 * j + 2], sc, -ms1)), p3 = ex2(fmaf(s[4 * j + 3], sc, -ms1));
                        rs0 += p0 + p1; rs1 += p2 + p3;
                        pf[j >> 1][(j & 1) * 2] = pack_bf16(p0, p1);
                        pf[j >> 1][(j & 1) * 2 + 1] = pack_bf16(p2, p3);
                    }
                    l0 = l0 * al0 + rs0; l1 = l1 * al1 + rs1;
                    if (tt > 0) {
#pragma unroll
                        for (int j = 0; j < 16; j++) { o[4 * j] *= al0; o[4 * j + 1] *= al0; o[4 * j + 2] *= al1; o[4 * j + 3] *= al1; }
                    }
                    if (tid == 0) TS(32 + u * 20 + tt * 4 + 3);
                }
                if (tid == 0) TS(2 + u);
                l0 += __shfl_xor_sync(0xffffffffu, l0, 1);
                l1 += __shfl_xor_sync(0xffffffffu, l1, 1);
                l0 += __shfl_xor_sync(0xffffffffu, l0, 2);
                l1 += __shfl_xor_sync(0xffffffffu, l1, 2);
                const float i0 = 1.f / l0, i1 = 1.f / l1;
                const uint32_t zown = smR + (w ? 3 : 0) * 16384 + t * 16;
#pragma unroll
                for (int kk = 0; kk < 8; kk++) {
                    af[kk][0] = pack_bf16(o[8 * kk + 0] * i0, o[8 * kk + 1] * i0);
                    af[kk][1] = pack_bf16(o[8 * kk + 2] * i1, o[8 * kk + 3] * i1);
                    af[kk][2] = pack_bf16(o[8 * kk + 4] * i0, o[8 * kk + 5] * i0);
                    af[kk][3] = pack_bf16(o[8 * kk + 6] * i1, o[8 * kk + 7] * i1);
                    sts128(zown + kk * 2048, af[kk][0], af[kk][1], af[kk][2], af[kk][3]);
                }
            }
            if (w == 0) bar_arrive<7, 256>(); else bar_arrive<8, 256>();
            lim = 3;
            if (u == 0) {
#pragma unroll
                for (int kk = 0; kk < 8; kk++) lds128(stash + kk * 2048, qf[kk]);
            }
            uint32_t nx[8][4];
#pragma unroll
            for (int ps = 0; ps < 2; ps++) {
                float acc[64];
                const uint32_t keep = smS + (3 + ps) * STAGE_BYTES + w * 16384 + t * 16;
                if (u == 0) {
#pragma unroll
                    for (int i = 0; i < 64; i++) acc[i] = 0.f;
                } else {
                    if (ps == 0) {
#pragma unroll
                        for (int j = 0; j < 8; j++) lds128(keep + j * 2048, nx[j]);
                        asm volatile("fence.proxy.async.shared::cta;" ::: "memory");
                        __syncwarp();
                        if (lane == 0) mbar_arrive(bars + 8 * (NSTAGE + 3));
                    }
#pragma unroll
                    for (int j = 0; j < 8; j++)
#pragma unroll
                        for (int i = 0; i < 4; i++) { acc[8 * j + 2 * i] = __uint_as_float(nx[j][i] << 16); acc[8 * j + 2 * i + 1] = __uint_as_float(nx[j][i] & 0xffff0000u); }
                }
#pragma unroll
                for (int st = 0; st < 4; st++) {
                    if (ps == 0 && st == 2) {
                        if (w == 0) bar_sync<8, 256>(); else bar_sync<7, 256>();
#pragma unroll
                        for (int kk = 0; kk < 8; kk++) lds128(smR + (w ? 0 : 3) * 16384 + kk * 2048 + t * 16, af[8 + kk]);
                    }
                    const bool extra = (u == 1) && (ps == 0 && st == 3);
                    const int sl = extra ? (3 + ps) : slot;
                    if (tid == 0) TS(80 + u * 24 + (ps * 4 + st) * 3);
                    mbar_wait(bars + 8 * sl, extra ? 1 : ph);
                    if (tid == 0) TS(80 + u * 24 + (ps * 4 + st) * 3 + 1);
                    const uint64_t db = mk_desc(smS + sl * STAGE_BYTES + w * 16384, 8192, 1024);
                    wg_fence();
#pragma unroll
                    for (int kk = 0; kk < 4; kk++)
                        wgmma_rs_n128_tb(acc, af[st * 4 + kk][0], af[st * 4 + kk][1], af[st * 4 + kk][2], af[st * 4 + kk][3], db + kk * 128, 1);
                    wg_commit();
                    if (u == 1 && st == 1) {
                        if (ps == 0) {
#pragma unroll
                            for (int j = 0; j < 8; j++) lds128(keep + STAGE_BYTES + j * 2048, nx[j]);
                            asm volatile("fence.proxy.async.shared::cta;" ::: "memory");
                            __syncwarp();
                            if (lane == 0) mbar_arrive(bars + 8 * (NSTAGE + 4));
                        } else {
#pragma unroll
                            for (int j = 0; j < 4; j++) lds128(stash + j * 2048, nx[j]);
                        }
                    }
                    wg_wait<0>();
                    if (tid == 0) TS(80 + u * 24 + (ps * 4 + st) * 3 + 2);
                    if (!extra) {
                        if (lane == 0) mbar_arrive(bars + 8 * (NSTAGE + slot));
                        if (++slot == 3) { slot = 0; ph ^= 1; }
                    }
                }
                fence_regs(acc);
                if (u == 0) {
#pragma unroll
                    for (int j = 0; j < 8; j++)
                        sts128(keep + j * 2048, pack_bf16(acc[8 * j], acc[8 * j + 1]), pack_bf16(acc[8 * j + 2], acc[8 * j + 3]),
                               pack_bf16(acc[8 * j + 4], acc[8 * j + 5]), pack_bf16(acc[8 * j + 6], acc[8 * j + 7]));
                } else {
                    uint2* dst = dst0 + (size_t)ps * 32 * 1024;
#pragma unroll
                    for (int j = 0; j < 16; j++)
                        __stcg(dst + (j >> 3) * 8192 + (j & 7) * 128, make_uint2(pack_bf16(acc[4 * j], acc[4 * j + 1]), pack_bf16(acc[4 * j + 2], acc[4 * j + 3])));
                    __syncwarp();
                    if (lane == 0) mbar_arrive(bars + 8 * (2 * NSTAGE + w * 5 + ps));
                }
                if (tid == 0) TS(4 + u * 8 + ps);
            }
            {
                float acc[32];
                if (u == 0) {
#pragma unroll
                    for (int i = 0; i < 32; i++) acc[i] = 0.f;
                } else {
#pragma unroll
                    for (int j = 0; j < 4; j++)
#pragma unroll
                        for (int i = 0; i < 4; i++) { acc[8 * j + 2 * i] = __uint_as_float(nx[j][i] << 16); acc[8 * j + 2 * i + 1] = __uint_as_float(nx[j][i] & 0xffff0000u); }
                }
                const int sl = u ? 4 : slot;
                mbar_wait(bars + 8 * sl, u ? 1 : ph);
                const uint64_t db = mk_desc(smS + sl * STAGE_BYTES + w * 16384, 8192, 1024);
                wg_fence();
#pragma unroll
                for (int kk = 0; kk < 8; kk++)
                    wgmma_rs_n64_tb(acc, af[kk][0], af[kk][1], af[kk][2], af[kk][3], db + kk * 128, 1);
                wg_commit();
                wg_wait<0>();
                if (u == 0) {
                    if (lane == 0) mbar_arrive(bars + 8 * (NSTAGE + slot));
                    if (++slot == 3) { slot = 0; ph ^= 1; }
                }
                fence_regs(acc);
                if (u == 0) {
#pragma unroll
                    for (int j = 0; j < 4; j++)
                        sts128(stash + j * 2048, pack_bf16(acc[8 * j], acc[8 * j + 1]), pack_bf16(acc[8 * j + 2], acc[8 * j + 3]),
                               pack_bf16(acc[8 * j + 4], acc[8 * j + 5]), pack_bf16(acc[8 * j + 6], acc[8 * j + 7]));
                } else {
#pragma unroll
                    for (int j = 0; j < 8; j++)
                        __stcg(dst8 + j * 128, make_uint2(pack_bf16(acc[4 * j], acc[4 * j + 1]), pack_bf16(acc[4 * j + 2], acc[4 * j + 3])));
                    __syncwarp();
                    if (lane == 0) mbar_arrive(bars + 8 * (2 * NSTAGE + w * 5 + 2));
                }
                if (tid == 0) TS(6 + u * 8);
            }
        }
        {
            __nv_bfloat16* orow = P.out + (size_t)(b * 64 + (t >> 5) * 16 + (lane >> 2)) * (2 * kD) + blk * kD + hp * 8 + (lane & 3) * 2;
#pragma unroll
            for (int g = 0; g < 2; g++) {
                const bool last = (g == 1) && (w == 0);
                if (lane == 0 || (last && lane == 1)) {
                    unsigned* cp = &g_cnt[(grp * 9 + (lane ? 4 : (2 * g + w))) * 32 + hp * 4 + (wid & 3)];
                    unsigned v, n = 0;
                    while (true) {
                        asm volatile("ld.acquire.gpu.global.u32 %0, [%1];" : "=r"(v) : "l"(cp) : "memory");
                        if (v >= (lane ? 16u : 8u)) break;
                        if (++n > (1u << 21)) break;
                    }
                    *cp = 0;
                }
                __syncwarp();
                if (tid == 0) TS(16 + g);
                const uint2* src = g_part + ((size_t)(grp * 80 + g * 32 + 2 * w * 8) * 8 + hp) * 128 + t;
                uint2 v[16], u8[16];
#pragma unroll
                for (int i = 0; i < 16; i++) v[i] = __ldcg(src + (size_t)i * 1024);
                if (last) {
                    const uint2* src8 = g_part + ((size_t)(grp * 80 + 64) * 8 + hp) * 128 + t;
#pragma unroll
                    for (int i = 0; i < 16; i++) u8[i] = __ldcg(src8 + (size_t)i * 1024);
                }
#pragma unroll
                for (int h = 0; h < 2; h++) {
                    float a0 = 0.f, a1 = 0.f, a2 = 0.f, a3 = 0.f;
#pragma unroll
                    for (int i = 0; i < 8; i++) {
                        const uint2 x = v[h * 8 + i];
                        a0 += __uint_as_float(x.x << 16); a1 += __uint_as_float(x.x & 0xffff0000u);
                        a2 += __uint_as_float(x.y << 16); a3 += __uint_as_float(x.y & 0xffff0000u);
                    }
                    *(uint32_t*)(orow + (g * 4 + 2 * w + h) * 64) = pack_bf16(a0, a1);
                    *(uint32_t*)(orow + (g * 4 + 2 * w + h) * 64 + 8 * 2 * kD) = pack_bf16(a2, a3);
                }
                if (last) {
                    float a0 = 0.f, a1 = 0.f, a2 = 0.f, a3 = 0.f;
#pragma unroll
                    for (int i = 0; i < 16; i++) {
                        const uint2 x = u8[i];
                        a0 += __uint_as_float(x.x << 16); a1 += __uint_as_float(x.x & 0xffff0000u);
                        a2 += __uint_as_float(x.y << 16); a3 += __uint_as_float(x.y & 0xffff0000u);
                    }
                    *(uint32_t*)(orow + 512) = pack_bf16(a0, a1);
                    *(uint32_t*)(orow + 512 + 8 * 2 * kD) = pack_bf16(a2, a3);
                }
            }
            if (tid == 0) TS(19);
        }
    }
}

typedef CUresult (*EncodeFn)(CUtensorMap*, CUtensorMapDataType, cuuint32_t, void*, const cuuint64_t*, const cuuint64_t*,
                             const cuuint32_t*, const cuuint32_t*, CUtensorMapInterleave, CUtensorMapSwizzle,
                             CUtensorMapL2promotion, CUtensorMapFloatOOBfill);

void make_map(EncodeFn fn, CUtensorMap* m, const void* ptr, uint64_t cols, uint64_t rows, uint32_t box_rows) {
    cuuint64_t dims[2] = {cols, rows};
    cuuint64_t strides[1] = {cols * 2};
    cuuint32_t box[2] = {64, box_rows};
    cuuint32_t es[2] = {1, 1};
    fn(m, CU_TENSOR_MAP_DATA_TYPE_BFLOAT16, 2, const_cast<void*>(ptr), dims, strides, box, es, CU_TENSOR_MAP_INTERLEAVE_NONE,
       CU_TENSOR_MAP_SWIZZLE_128B, CU_TENSOR_MAP_L2_PROMOTION_L2_256B, CU_TENSOR_MAP_FLOAT_OOB_FILL_NONE);
}

void make_map3(EncodeFn fn, CUtensorMap* m, const void* ptr, uint64_t cols, uint64_t rows, uint32_t box_rows, uint32_t box_groups) {
    cuuint64_t dims[3] = {64, rows, cols / 64};
    cuuint64_t strides[2] = {cols * 2, 128};
    cuuint32_t box[3] = {64, box_rows, box_groups};
    cuuint32_t es[3] = {1, 1, 1};
    fn(m, CU_TENSOR_MAP_DATA_TYPE_BFLOAT16, 3, const_cast<void*>(ptr), dims, strides, box, es, CU_TENSOR_MAP_INTERLEAVE_NONE,
       CU_TENSOR_MAP_SWIZZLE_128B, CU_TENSOR_MAP_L2_PROMOTION_L2_256B, CU_TENSOR_MAP_FLOAT_OOB_FILL_NONE);
}

}

extern "C" void kernel_launch(void* const* d_in, const int* in_sizes, int n_in, void* d_out, int out_size) {
    static EncodeFn enc = nullptr;
    if (!enc) {
        void* fn = nullptr;
        cudaDriverEntryPointQueryResult st;
        cudaGetDriverEntryPoint("cuTensorMapEncodeTiled", &fn, cudaEnableDefault, &st);
        enc = (EncodeFn)fn;
        cudaFuncSetAttribute(fused_gqa_kernel, cudaFuncAttributeMaxDynamicSharedMemorySize, SMEM_BYTES);
    }
    Params P;
    for (int blk = 0; blk < 2; blk++) {
        const void* x = d_in[blk * 5 + 0];
        const void* k = d_in[blk * 5 + 1];
        const void* v = d_in[blk * 5 + 2];
        const void* wq = d_in[blk * 5 + 3];
        const void* wo = d_in[blk * 5 + 4];
        make_map(enc, &P.x[blk], x, kD, kB * kSq, 64);
        make_map3(enc, &P.wq[blk], wq, kHq * kDh, kD, 32, 2);
        make_map3(enc, &P.k[blk], k, kDh, (uint64_t)kB * kHkv * kSk, 128, 2);
        make_map3(enc, &P.v[blk], v, kDh, (uint64_t)kB * kHkv * kSk, 128, 2);
        make_map3(enc, &P.wo[blk], wo, kD, kHq * kDh, 64, 2);
        make_map(enc, &P.wo8[blk], wo, kD, kHq * kDh, 128);
        P.wqp[blk] = (const __nv_bfloat16*)wq;
        P.kp[blk] = (const __nv_bfloat16*)k;
        P.vp[blk] = (const __nv_bfloat16*)v;
        P.wop[blk] = (const __nv_bfloat16*)wo;
    }
    P.out = (__nv_bfloat16*)d_out;
    fused_gqa_kernel<<<128, 384, SMEM_BYTES>>>(P);
}
```

```cpp
#include <cuda_runtime.h>
#include <cuda_bf16.h>
#include <cuda.h>
#include <stdint.h>

namespace {

constexpr int kB = 8, kSq = 64, kD = 576, kHq = 32, kHkv = 16, kSk = 512, kDh = 128;
constexpr int NSTAGE = 5;
constexpr int STAGE_BYTES = 32768;
constexpr int R_BYTES = 65536;
constexpr int SMEM_BYTES = R_BYTES + NSTAGE * STAGE_BYTES + 1024   + 256  ;
constexpr int N_WQ = 18;
#define PF_DIST_V 6
#define OP_WAIT0 1
#define QP_WAIT0 1
#define PF_POS1 9
#define PF_START 1
#define PF_WQ 0
#define PF_SLEEP 1000
constexpr int PF_DIST = PF_DIST_V;

struct __align__(64) Params {
    CUtensorMap x[2], wq[2], k[2], v[2], wo[2], wo8[2];
    const __nv_bfloat16* wqp[2];
    const __nv_bfloat16* kp[2];
    const __nv_bfloat16* vp[2];
    const __nv_bfloat16* wop[2];
    __nv_bfloat16* out;
};

__device__ uint2 g_part[16 * 80 * 8 * 128];
__device__ unsigned int g_cnt[16 * 9 * 32];
#define TS(k) do {} while (0)

__device__ __forceinline__ uint32_t smem_u32(const void* p) { return (uint32_t)__cvta_generic_to_shared(p); }
__device__ __forceinline__ void mbar_init(uint32_t bar, int cnt) {
    asm volatile("mbarrier.init.shared::cta.b64 [%0], %1;" ::"r"(bar), "r"(cnt));
}
__device__ __forceinline__ void mbar_expect_tx(uint32_t bar, uint32_t bytes) {
    asm volatile("mbarrier.arrive.expect_tx.shared::cta.b64 _, [%0], %1;" ::"r"(bar), "r"(bytes) : "memory");
}
__device__ __forceinline__ void mbar_arrive(uint32_t bar) {
    asm volatile("mbarrier.arrive.shared::cta.b64 _, [%0];" ::"r"(bar) : "memory");
}
__device__ __forceinline__ bool mbar_try(uint32_t bar, uint32_t parity) {
    uint32_t ok;
    asm volatile("{\n.reg .pred p;\nmbarrier.try_wait.parity.shared::cta.b64 p, [%1], %2;\nselp.u32 %0, 1, 0, p;\n}\n"
                 : "=r"(ok) : "r"(bar), "r"(parity) : "memory");
    return ok != 0;
}
__device__ __forceinline__ void mbar_wait(uint32_t bar, uint32_t parity) {
    if (mbar_try(bar, parity)) return;
    uint32_t n = 0;
    while (!mbar_try(bar, parity)) {
        if (++n > (1u << 20)) break;
    }
}
__device__ __forceinline__ void tma_2d(uint32_t dst, const CUtensorMap* tm, int c0, int c1, uint32_t bar) {
    asm volatile("cp.async.bulk.tensor.2d.shared::cluster.global.mbarrier::complete_tx::bytes [%0], [%1, {%3, %4}], [%2];"
                 ::"r"(dst), "l"(tm), "r"(bar), "r"(c0), "r"(c1) : "memory");
}
__device__ __forceinline__ void tma_3d(uint32_t dst, const CUtensorMap* tm, int c0, int c1, int c2, uint32_t bar) {
    asm volatile("cp.async.bulk.tensor.3d.shared::cluster.global.mbarrier::complete_tx::bytes [%0], [%1, {%3, %4, %5}], [%2];"
                 ::"r"(dst), "l"(tm), "r"(bar), "r"(c0), "r"(c1), "r"(c2) : "memory");
}
__device__ __forceinline__ void l2_prefetch(const void* p, uint32_t bytes) {
    asm volatile("cp.async.bulk.prefetch.L2.global [%0], %1;" ::"l"(p), "r"(bytes) : "memory");
}
__device__ __forceinline__ uint32_t l2_touch(const void* p) {
    uint32_t v;
    asm volatile("ld.global.L2::256B.b32 %0, [%1];" : "=r"(v) : "l"(p) : "memory");
    return v;
}
__device__ __forceinline__ void wg_fence() { asm volatile("wgmma.fence.sync.aligned;" ::: "memory"); }
__device__ __forceinline__ void wg_commit() { asm volatile("wgmma.commit_group.sync.aligned;" ::: "memory"); }
template <int N> __device__ __forceinline__ void wg_wait() { asm volatile("wgmma.wait_group.sync.aligned %0;" ::"n"(N) : "memory"); }
template <int N> __device__ __forceinline__ void fence_regs(float (&d)[N]) {
#pragma unroll
    for (int i = 0; i < N; i++) asm volatile("" : "+f"(d[i])::"memory");
}
__device__ __forceinline__ uint64_t mk_desc(uint32_t addr, uint32_t lbo, uint32_t sbo) {
    return (uint64_t)((addr & 0x3FFFF) >> 4) | ((uint64_t)(lbo >> 4) << 16) | ((uint64_t)(sbo >> 4) << 32) | (1ull << 62);
}
__device__ __forceinline__ uint32_t pack_bf16(float a, float b) {
    uint32_t r;
    asm("cvt.rn.bf16x2.f32 %0, %1, %2;" : "=r"(r) : "f"(b), "f"(a));
    return r;
}
__device__ __forceinline__ float ex2(float x) {
    float y;
    asm("ex2.approx.ftz.f32 %0, %1;" : "=f"(y) : "f"(x));
    return y;
}
template <int ID, int N> __device__ __forceinline__ void bar_sync() { asm volatile("bar.sync %0, %1;" ::"n"(ID), "n"(N) : "memory"); }
template <int ID, int N> __device__ __forceinline__ void bar_arrive() { asm volatile("bar.arrive %0, %1;" ::"n"(ID), "n"(N) : "memory"); }
__device__ __forceinline__ void sts128(uint32_t addr, uint32_t a, uint32_t b, uint32_t c, uint32_t d) {
    asm volatile("st.shared.v4.b32 [%0], {%1,%2,%3,%4};" ::"r"(addr), "r"(a), "r"(b), "r"(c), "r"(d) : "memory");
}
__device__ __forceinline__ void lds128(uint32_t addr, uint32_t (&r)[4]) {
    asm volatile("ld.shared.v4.b32 {%0,%1,%2,%3}, [%4];" : "=r"(r[0]), "=r"(r[1]), "=r"(r[2]), "=r"(r[3]) : "r"(addr) : "memory");
}

__device__ __forceinline__ void wgmma_ss_n256_tb(float (&d)[128], uint64_t da, uint64_t db, int sd) {
    asm volatile("{\n.reg .pred p;\nsetp.ne.b32 p, %130, 0;\n"
        "wgmma.mma_async.sync.aligned.m64n256k16.f32.bf16.bf16 "
        "{%0, %1, %2, %3, %4, %5, %6, %7, %8, %9, %10, %11, %12, %13, %14, %15, %16, %17, %18, %19, %20, %21, %22, %23, %24, %25, %26, %27, %28, %29, %30, %31, %32, %33, %34, %35, %36, %37, %38, %39, %40, %41, %42, %43, %44, %45, %46, %47, %48, %49, %50, %51, %52, %53, %54, %55, %56, %57, %58, %59, %60, %61, %62, %63, %64, %65, %66, %67, %68, %69, %70, %71, %72, %73, %74, %75, %76, %77, %78, %79, %80, %81, %82, %83, %84, %85, %86, %87, %88, %89, %90, %91, %92, %93, %94, %95, %96, %97, %98, %99, %100, %101, %102, %103, %104, %105, %106, %107, %108, %109, %110, %111, %112, %113, %114, %115, %116, %117, %118, %119, %120, %121, %122, %123, %124, %125, %126, %127}, "
        "%128, %129, p, 1, 1, 0, 1;\n}\n"
        : "+f"(d[0]), "+f"(d[1]), "+f"(d[2]), "+f"(d[3]), "+f"(d[4]), "+f"(d[5]), "+f"(d[6]), "+f"(d[7]), "+f"(d[8]), "+f"(d[9]), "+f"(d[10]), "+f"(d[11]), "+f"(d[12]), "+f"(d[13]), "+f"(d[14]), "+f"(d[15]), "+f"(d[16]), "+f"(d[17]), "+f"(d[18]), "+f"(d[19]), "+f"(d[20]), "+f"(d[21]), "+f"(d[22]), "+f"(d[23]), "+f"(d[24]), "+f"(d[25]), "+f"(d[26]), "+f"(d[27]), "+f"(d[28]), "+f"(d[29]), "+f"(d[30]), "+f"(d[31]), "+f"(d[32]), "+f"(d[33]), "+f"(d[34]), "+f"(d[35]), "+f"(d[36]), "+f"(d[37]), "+f"(d[38]), "+f"(d[39]), "+f"(d[40]), "+f"(d[41]), "+f"(d[42]), "+f"(d[43]), "+f"(d[44]), "+f"(d[45]), "+f"(d[46]), "+f"(d[47]), "+f"(d[48]), "+f"(d[49]), "+f"(d[50]), "+f"(d[51]), "+f"(d[52]), "+f"(d[53]), "+f"(d[54]), "+f"(d[55]), "+f"(d[56]), "+f"(d[57]), "+f"(d[58]), "+f"(d[59]), "+f"(d[60]), "+f"(d[61]), "+f"(d[62]), "+f"(d[63]), "+f"(d[64]), "+f"(d[65]), "+f"(d[66]), "+f"(d[67]), "+f"(d[68]), "+f"(d[69]), "+f"(d[70]), "+f"(d[71]), "+f"(d[72]), "+f"(d[73]), "+f"(d[74]), "+f"(d[75]), "+f"(d[76]), "+f"(d[77]), "+f"(d[78]), "+f"(d[79]), "+f"(d[80]), "+f"(d[81]), "+f"(d[82]), "+f"(d[83]), "+f"(d[84]), "+f"(d[85]), "+f"(d[86]), "+f"(d[87]), "+f"(d[88]), "+f"(d[89]), "+f"(d[90]), "+f"(d[91]), "+f"(d[92]), "+f"(d[93]), "+f"(d[94]), "+f"(d[95]), "+f"(d[96]), "+f"(d[97]), "+f"(d[98]), "+f"(d[99]), "+f"(d[100]), "+f"(d[101]), "+f"(d[102]), "+f"(d[103]), "+f"(d[104]), "+f"(d[105]), "+f"(d[106]), "+f"(d[107]), "+f"(d[108]), "+f"(d[109]), "+f"(d[110]), "+f"(d[111]), "+f"(d[112]), "+f"(d[113]), "+f"(d[114]), "+f"(d[115]), "+f"(d[116]), "+f"(d[117]), "+f"(d[118]), "+f"(d[119]), "+f"(d[120]), "+f"(d[121]), "+f"(d[122]), "+f"(d[123]), "+f"(d[124]), "+f"(d[125]), "+f"(d[126]), "+f"(d[127])
        : "l"(da), "l"(db), "r"(sd));
}
__device__ __forceinline__ void wgmma_rs_n128(float (&d)[64], uint32_t a0, uint32_t a1, uint32_t a2, uint32_t a3, uint64_t db, int sd) {
    asm volatile("{\n.reg .pred p;\nsetp.ne.b32 p, %69, 0;\n"
        "wgmma.mma_async.sync.aligned.m64n128k16.f32.bf16.bf16 "
        "{%0, %1, %2, %3, %4, %5, %6, %7, %8, %9, %10, %11, %12, %13, %14, %15, %16, %17, %18, %19, %20, %21, %22, %23, %24, %25, %26, %27, %28, %29, %30, %31, %32, %33, %34, %35, %36, %37, %38, %39, %40, %41, %42, %43, %44, %45, %46, %47, %48, %49, %50, %51, %52, %53, %54, %55, %56, %57, %58, %59, %60, %61, %62, %63}, "
        "{%64, %65, %66, %67}, %68, p, 1, 1, 0;\n}\n"
        : "+f"(d[0]), "+f"(d[1]), "+f"(d[2]), "+f"(d[3]), "+f"(d[4]), "+f"(d[5]), "+f"(d[6]), "+f"(d[7]), "+f"(d[8]), "+f"(d[9]), "+f"(d[10]), "+f"(d[11]), "+f"(d[12]), "+f"(d[13]), "+f"(d[14]), "+f"(d[15]), "+f"(d[16]), "+f"(d[17]), "+f"(d[18]), "+f"(d[19]), "+f"(d[20]), "+f"(d[21]), "+f"(d[22]), "+f"(d[23]), "+f"(d[24]), "+f"(d[25]), "+f"(d[26]), "+f"(d[27]), "+f"(d[28]), "+f"(d[29]), "+f"(d[30]), "+f"(d[31]), "+f"(d[32]), "+f"(d[33]), "+f"(d[34]), "+f"(d[35]), "+f"(d[36]), "+f"(d[37]), "+f"(d[38]), "+f"(d[39]), "+f"(d[40]), "+f"(d[41]), "+f"(d[42]), "+f"(d[43]), "+f"(d[44]), "+f"(d[45]), "+f"(d[46]), "+f"(d[47]), "+f"(d[48]), "+f"(d[49]), "+f"(d[50]), "+f"(d[51]), "+f"(d[52]), "+f"(d[53]), "+f"(d[54]), "+f"(d[55]), "+f"(d[56]), "+f"(d[57]), "+f"(d[58]), "+f"(d[59]), "+f"(d[60]), "+f"(d[61]), "+f"(d[62]), "+f"(d[63])
        : "r"(a0), "r"(a1), "r"(a2), "r"(a3), "l"(db), "r"(sd));
}
__device__ __forceinline__ void wgmma_rs_n128_tb(float (&d)[64], uint32_t a0, uint32_t a1, uint32_t a2, uint32_t a3, uint64_t db, int sd) {
    asm volatile("{\n.reg .pred p;\nsetp.ne.b32 p, %69, 0;\n"
        "wgmma.mma_async.sync.aligned.m64n128k16.f32.bf16.bf16 "
        "{%0, %1, %2, %3, %4, %5, %6, %7, %8, %9, %10, %11, %12, %13, %14, %15, %16, %17, %18, %19, %20, %21, %22, %23, %24, %25, %26, %27, %28, %29, %30, %31, %32, %33, %34, %35, %36, %37, %38, %39, %40, %41, %42, %43, %44, %45, %46, %47, %48, %49, %50, %51, %52, %53, %54, %55, %56, %57, %58, %59, %60, %61, %62, %63}, "
        "{%64, %65, %66, %67}, %68, p, 1, 1, 1;\n}\n"
        : "+f"(d[0]), "+f"(d[1]), "+f"(d[2]), "+f"(d[3]), "+f"(d[4]), "+f"(d[5]), "+f"(d[6]), "+f"(d[7]), "+f"(d[8]), "+f"(d[9]), "+f"(d[10]), "+f"(d[11]), "+f"(d[12]), "+f"(d[13]), "+f"(d[14]), "+f"(d[15]), "+f"(d[16]), "+f"(d[17]), "+f"(d[18]), "+f"(d[19]), "+f"(d[20]), "+f"(d[21]), "+f"(d[22]), "+f"(d[23]), "+f"(d[24]), "+f"(d[25]), "+f"(d[26]), "+f"(d[27]), "+f"(d[28]), "+f"(d[29]), "+f"(d[30]), "+f"(d[31]), "+f"(d[32]), "+f"(d[33]), "+f"(d[34]), "+f"(d[35]), "+f"(d[36]), "+f"(d[37]), "+f"(d[38]), "+f"(d[39]), "+f"(d[40]), "+f"(d[41]), "+f"(d[42]), "+f"(d[43]), "+f"(d[44]), "+f"(d[45]), "+f"(d[46]), "+f"(d[47]), "+f"(d[48]), "+f"(d[49]), "+f"(d[50]), "+f"(d[51]), "+f"(d[52]), "+f"(d[53]), "+f"(d[54]), "+f"(d[55]), "+f"(d[56]), "+f"(d[57]), "+f"(d[58]), "+f"(d[59]), "+f"(d[60]), "+f"(d[61]), "+f"(d[62]), "+f"(d[63])
        : "r"(a0), "r"(a1), "r"(a2), "r"(a3), "l"(db), "r"(sd));
}
__device__ __forceinline__ void wgmma_rs_n64_tb(float (&d)[32], uint32_t a0, uint32_t a1, uint32_t a2, uint32_t a3, uint64_t db, int sd) {
    asm volatile("{\n.reg .pred p;\nsetp.ne.b32 p, %37, 0;\n"
        "wgmma.mma_async.sync.aligned.m64n64k16.f32.bf16.bf16 "
        "{%0, %1, %2, %3, %4, %5, %6, %7, %8, %9, %10, %11, %12, %13, %14, %15, %16, %17, %18, %19, %20, %21, %22, %23, %24, %25, %26, %27, %28, %29, %30, %31}, "
        "{%32, %33, %34, %35}, %36, p, 1, 1, 1;\n}\n"
        : "+f"(d[0]), "+f"(d[1]), "+f"(d[2]), "+f"(d[3]), "+f"(d[4]), "+f"(d[5]), "+f"(d[6]), "+f"(d[7]), "+f"(d[8]), "+f"(d[9]), "+f"(d[10]), "+f"(d[11]), "+f"(d[12]), "+f"(d[13]), "+f"(d[14]), "+f"(d[15]), "+f"(d[16]), "+f"(d[17]), "+f"(d[18]), "+f"(d[19]), "+f"(d[20]), "+f"(d[21]), "+f"(d[22]), "+f"(d[23]), "+f"(d[24]), "+f"(d[25]), "+f"(d[26]), "+f"(d[27]), "+f"(d[28]), "+f"(d[29]), "+f"(d[30]), "+f"(d[31])
        : "r"(a0), "r"(a1), "r"(a2), "r"(a3), "l"(db), "r"(sd));
}

__global__ void __launch_bounds__(384, 1) fused_gqa_kernel(const __grid_constant__ Params P) {
    extern __shared__ uint8_t smem_raw[];
    const uint32_t base = (smem_u32(smem_raw) + 1023u) & ~1023u;
    const uint32_t smR = base;
    const uint32_t smS = base + R_BYTES;
    const uint32_t bars = smS + NSTAGE * STAGE_BYTES;
    const uint32_t prog = bars + 8 * (2 * NSTAGE + 10);
    const int tid = threadIdx.x;
    const int wid = __shfl_sync(0xffffffffu, tid >> 5, 0);
    const int lane = tid & 31;

    const int cta = blockIdx.x;
    const int blk = cta >> 6;
    const int hp = (cta >> 3) & 7;
    const int b = cta & 7;
    const int grp = blk * 8 + b;

    if (tid == 256) {
        TS(0);
        asm volatile("prefetch.tensormap [%0];" ::"l"(&P.x[blk]) : "memory");
        asm volatile("prefetch.tensormap [%0];" ::"l"(&P.wq[blk]) : "memory");
        for (int i = 0; i < NSTAGE; i++) {
            mbar_init(bars + 8 * i, 1);
            mbar_init(bars + 8 * (NSTAGE + i), 8);
        }
        for (int i = 0; i < 10; i++) mbar_init(bars + 8 * (2 * NSTAGE + i), 4);
        asm volatile("st.volatile.shared.u32 [%0], %1;" ::"r"(prog), "r"(0) : "memory");
        asm volatile("fence.mbarrier_init.release.cluster;" ::: "memory");
        asm volatile("fence.proxy.async.shared::cta;" ::: "memory");
#pragma unroll
        for (int s = 0; s < NSTAGE; s++) {
            const uint32_t fb = bars + 8 * s;
            const uint32_t dst = smS + s * STAGE_BYTES;
            mbar_expect_tx(fb, (s & 1) ? STAGE_BYTES : STAGE_BYTES + 8192);
            if (!(s & 1)) tma_2d(smR + (s >> 1) * 8192, &P.x[blk], (s >> 1) * 64, b * 64, fb);
#pragma unroll
            for (int p = 0; p < 4; p++) tma_3d(dst + p * 8192, &P.wq[blk], 0, s * 32, hp * 8 + (p & 1) * 4 + (p >> 1) * 2, fb);
        }
        asm volatile("prefetch.tensormap [%0];" ::"l"(&P.k[blk]) : "memory");
        asm volatile("prefetch.tensormap [%0];" ::"l"(&P.v[blk]) : "memory");
        asm volatile("prefetch.tensormap [%0];" ::"l"(&P.wo[blk]) : "memory");
        asm volatile("prefetch.tensormap [%0];" ::"l"(&P.wo8[blk]) : "memory");
    }
    __syncthreads();

    if (wid >= 8) {
        asm volatile("setmaxnreg.dec.sync.aligned.u32 40;");
        auto publish = [&](int hw, int k) {
            mbar_wait(bars + 8 * (2 * NSTAGE + hw * 5 + k), 0);
            const int c = (k < 2) ? (2 * k + hw) : 4;
            asm volatile("fence.acq_rel.gpu;" ::: "memory");
            asm volatile("red.relaxed.gpu.global.add.u32 [%0], 1;" ::"l"(&g_cnt[(grp * 9 + c) * 32 + lane]) : "memory");
        };
        if (wid == 8) {
            if (lane == 0) {
                int slot = 0, ph = 0;
                for (int s = NSTAGE; s < N_WQ; s++) {
                    const uint32_t fb = bars + 8 * slot;
                    mbar_wait(bars + 8 * (NSTAGE + slot), ph);
                    const uint32_t dst = smS + slot * STAGE_BYTES;
                    mbar_expect_tx(fb, (s & 1) ? STAGE_BYTES : STAGE_BYTES + 8192);
                    if (!(s & 1)) tma_2d(smR + ((s >> 1) & 7) * 8192, &P.x[blk], (s >> 1) * 64, b * 64, fb);
#pragma unroll
                    for (int p = 0; p < 4; p++) {
                        const int w = p >> 1, j = p & 1;
                        tma_3d(dst + p * 8192, &P.wq[blk], 0, s * 32, hp * 8 + j * 4 + w * 2, fb);
                    }
                    if (++slot == NSTAGE) { slot = 0; ph ^= 1; }
                }
                int lim = NSTAGE;
                for (int i = 0; i < 34; i++) {
                    const int u = (i >= 17), r = i - 17 * u;
                    const bool extra = (i == 28) || (i == 33);
                    const int sl = extra ? ((i == 28) ? 3 : 4) : slot;
                    const uint32_t fb = bars + 8 * sl;
                    mbar_wait(bars + 8 * (NSTAGE + sl), extra ? 1 : ph);
                    const uint32_t dst = smS + sl * STAGE_BYTES;
                    mbar_expect_tx(fb, STAGE_BYTES);
                    if (r < 8) {
                        const int row = (b * kHkv + hp * 2 + u) * kSk + (r >> 1) * 128;
                        tma_3d(dst, (r & 1) ? &P.v[blk] : &P.k[blk], 0, row, 0, fb);
                    } else {
                        const int q = r - 8, row = hp * 512 + u * 256;
                        if (q < 8) {
                            tma_3d(dst, &P.wo[blk], 0, row + (q & 3) * 64, (q >> 2) * 4, fb);
                            tma_3d(dst + 16384, &P.wo[blk], 0, row + ((q & 3) ^ 2) * 64, (q >> 2) * 4 + 2, fb);
                        } else {
                            tma_2d(dst, &P.wo8[blk], 512, row, fb);
                            tma_2d(dst + 16384, &P.wo8[blk], 512, row + 128, fb);
                        }
                    }
                    asm volatile("st.volatile.shared.u32 [%0], %1;" ::"r"(prog), "r"(i + 1) : "memory");
                    if (i == 7) lim = 3;
                    if (!extra && ++slot == lim) { slot = 0; ph ^= 1; }
                }
            }
            __syncwarp();
            publish(1, 1);
        } else if (wid == 11) {
            if (PF_DIST > 0) {
                uint32_t sink = 0;
                mbar_wait(bars, 0);
                if (PF_WQ) {
                    const char* wqs = (const char*)(P.wqp[blk] + hp * 512) + (size_t)(160 + b * 52) * 8192;
#pragma unroll
                    for (int h = 0; h < 2; h++) {
#pragma unroll
                        for (int j = 0; j < 4; j++) {
                            const int e = (h * 4 + j) * 32 + lane;
                            if (e < 208) sink |= l2_touch(wqs + (size_t)(e >> 2) * 8192 + (e & 3) * 256);
                        }
                        if (sink == 0x9E3779B9u) asm volatile("st.volatile.shared.u32 [%0], %1;" ::"r"(prog + 4), "r"(sink) : "memory");
                    }
                }
                const char* kbase = (const char*)(P.kp[blk] + (size_t)(b * kHkv + hp * 2) * kSk * kDh);
                const char* vbase = (const char*)(P.vp[blk] + (size_t)(b * kHkv + hp * 2) * kSk * kDh);
                const char* wos = (const char*)(P.wop[blk] + (size_t)hp * 512 * kD) + (size_t)b * 36864;
                for (int i = 0; i < 18; i++) {
                    const int u = (i >= 9), r = i - 9 * u;
                    const int pos = u ? (PF_POS1 + r) : r;
                    if (pos >= PF_DIST) {
                        uint32_t pr, n = 0;
                        while (true) {
                            asm volatile("ld.volatile.shared.u32 %0, [%1];" : "=r"(pr) : "r"(prog) : "memory");
                            const int prk = ((int)pr <= 8) ? (int)pr : (((int)pr <= 17) ? 8 + (((int)pr - 8) * (PF_POS1 - 8)) / 9 : (int)pr - 17 + PF_POS1);
                            if (prk + PF_DIST >= pos) break;
                            if (++n > (1u << 22)) break;
                            __nanosleep(100);
                        }
                    }
                    if (r < 8) {
                        const char* p = ((r & 1) ? vbase : kbase) + (size_t)(u * 4 + (r >> 1)) * 32768 + lane * 256;
#pragma unroll
                        for (int j = 0; j < 4; j++) sink |= l2_touch(p + j * 8192);
                    } else {
                        const char* p = wos + (size_t)u * 294912 + lane * 256;
#pragma unroll
                        for (int j = 0; j < 5; j++) if (j * 32 + lane < 144) sink |= l2_touch(p + j * 8192);
                    }
                    if (sink == 0x9E3779B9u) asm volatile("st.volatile.shared.u32 [%0], %1;" ::"r"(prog + 4), "r"(sink) : "memory");
                }
            }
            publish(0, 1);
        } else {
            const int hw = wid - 9;
            publish(hw, 0);
            publish(hw, 2);
        }
    } else {
        asm volatile("setmaxnreg.inc.sync.aligned.u32 232;");
        const int w = wid >> 2;
        const int t = tid & 127;
        int slot = 0, ph = 0, lim = NSTAGE;
        uint32_t qf[8][4];
        const uint32_t stash = smR + (1 + w) * 16384 + t * 16;
        {
            float acc[128];
            int pslot = 0;
            for (int s = 0; s < N_WQ; s++) {
                mbar_wait(bars + 8 * slot, ph);
                if (tid == 0 && s == 0) TS(20);
                if (tid == 0 && s == 5) TS(21);
                if (tid == 0 && s == 10) TS(22);
                const uint64_t da = mk_desc(smR + ((s >> 1) & 7) * 8192 + (s & 1) * 64, 16, 1024);
                const uint64_t db = mk_desc(smS + slot * STAGE_BYTES + w * 16384, 4096, 1024);
                wg_fence();
                wgmma_ss_n256_tb(acc, da, db, s != 0);
                wgmma_ss_n256_tb(acc, da + 2, db + 128, 1);
                wg_commit();
                wg_wait<0>();
                if (lane == 0) mbar_arrive(bars + 8 * (NSTAGE + slot));
                pslot = slot;
                if (++slot == NSTAGE) { slot = 0; ph ^= 1; }
            }
            fence_regs(acc);
            if (tid == 0) TS(1);
#pragma unroll
            for (int kk = 0; kk < 8; kk++) {
#pragma unroll
                for (int i = 0; i < 4; i++) qf[kk][i] = pack_bf16(acc[8 * kk + 2 * i], acc[8 * kk + 2 * i + 1]);
                sts128(stash + kk * 2048,
                       pack_bf16(acc[64 + 8 * kk + 0], acc[64 + 8 * kk + 1]), pack_bf16(acc[64 + 8 * kk + 2], acc[64 + 8 * kk + 3]),
                       pack_bf16(acc[64 + 8 * kk + 4], acc[64 + 8 * kk + 5]), pack_bf16(acc[64 + 8 * kk + 6], acc[64 + 8 * kk + 7]));
            }
        }
        if (w == 1) bar_arrive<5, 256>();
        const float sc = 0.08838834764831845f * 1.4426950408889634f;
        uint2* dst0 = g_part + (size_t)(grp * 80 + 2 * w * 8 + hp) * 1024 + t;
        uint2* dst8 = g_part + (size_t)(grp * 80 + 64 + hp * 2 + w) * 1024 + t;
#pragma unroll
        for (int u = 0; u < 2; u++) {
            uint32_t af[16][4];
            {
                float o[64], s[64];
                float m0 = -INFINITY, m1 = -INFINITY, l0 = 0.f, l1 = 0.f;
                uint32_t pf[8][4];
#pragma unroll
                for (int i = 0; i < 64; i++) { o[i] = 0.f; s[i] = 0.f; }
#pragma unroll
                for (int i = 0; i < 32; i++) pf[i >> 2][i & 3] = 0u;
#pragma unroll 1
                for (int tt = 0; tt <= 4; tt++) {
                    int vslot = slot;
                    if (tt > 0) {
                        mbar_wait(bars + 8 * slot, ph);
                        if (++slot == lim) { slot = 0; ph ^= 1; }
                    }
                    if (tt < 4) mbar_wait(bars + 8 * slot, ph);
                    if (tid == 0) TS(32 + u * 20 + tt * 4);
                    if (w == 0) bar_sync<5, 256>(); else bar_sync<6, 256>();
                    wg_fence();
                    if (tt > 0) {
                        const uint64_t db = mk_desc(smS + vslot * STAGE_BYTES, 16384, 1024);
#pragma unroll
                        for (int kk = 0; kk < 8; kk++)
                            wgmma_rs_n128_tb(o, pf[kk][0], pf[kk][1], pf[kk][2], pf[kk][3], db + kk * 128, (tt > 1) || (kk != 0));
                        wg_commit();
                    }
                    if (tt < 4) {
                        const uint64_t db = mk_desc(smS + slot * STAGE_BYTES, 16, 1024);
#pragma unroll
                        for (int kk = 0; kk < 8; kk++)
                            wgmma_rs_n128(s, qf[kk][0], qf[kk][1], qf[kk][2], qf[kk][3], db + (kk >> 2) * 1024 + (kk & 3) * 2, kk != 0);
                        wg_commit();
                    }
                    if (w == 0) bar_arrive<6, 256>(); else if (!(u == 1 && tt == 4)) bar_arrive<5, 256>();
                    if (tid == 0) TS(32 + u * 20 + tt * 4 + 1);
                    wg_wait<0>();
                    fence_regs(o);
                    fence_regs(s);
                    if (tid == 0) TS(32 + u * 20 + tt * 4 + 2);
                    if (tt > 0 && lane == 0) mbar_arrive(bars + 8 * (NSTAGE + vslot));
                    if (tt == 4) break;
                    if (lane == 0) mbar_arrive(bars + 8 * (NSTAGE + slot));
                    if (++slot == lim) { slot = 0; ph ^= 1; }
                    float mx0 = s[0], mx1 = s[2];
#pragma unroll
                    for (int j = 0; j < 16; j++) {
                        mx0 = fmaxf(mx0, fmaxf(s[4 * j], s[4 * j + 1]));
                        mx1 = fmaxf(mx1, fmaxf(s[4 * j + 2], s[4 * j + 3]));
                    }
                    mx0 = fmaxf(mx0, __shfl_xor_sync(0xffffffffu, mx0, 1));
                    mx1 = fmaxf(mx1, __shfl_xor_sync(0xffffffffu, mx1, 1));
                    mx0 = fmaxf(mx0, __shfl_xor_sync(0xffffffffu, mx0, 2));
                    mx1 = fmaxf(mx1, __shfl_xor_sync(0xffffffffu, mx1, 2));
                    const float mn0 = fmaxf(m0, mx0), mn1 = fmaxf(m1, mx1);
                    const float al0 = ex2((m0 - mn0) * sc), al1 = ex2((m1 - mn1) * sc);
                    m0 = mn0; m1 = mn1;
                    const float ms0 = mn0 * sc, ms1 = mn1 * sc;
                    float rs0 = 0.f, rs1 = 0.f;
#pragma unroll
                    for (int j = 0; j < 16; j++) {
                        const float p0 = ex2(fmaf(s[4 * j], sc, -ms0)), p1 = ex2(fmaf(s[4 * j + 1], sc, -ms0));
                        const float p2 = ex2(fmaf(s[4 * j + 2], sc, -ms1)), p3 = ex2(fmaf(s[4 * j + 3], sc, -ms1));
                        rs0 += p0 + p1; rs1 += p2 + p3;
                        pf[j >> 1][(j & 1) * 2] = pack_bf16(p0, p1);
                        pf[j >> 1][(j & 1) * 2 + 1] = pack_bf16(p2, p3);
                    }
                    l0 = l0 * al0 + rs0; l1 = l1 * al1 + rs1;
                    if (tt > 0) {
#pragma unroll
                        for (int j = 0; j < 16; j++) { o[4 * j] *= al0; o[4 * j + 1] *= al0; o[4 * j + 2] *= al1; o[4 * j + 3] *= al1; }
                    }
                    if (tid == 0) TS(32 + u * 20 + tt * 4 + 3);
                }
                if (tid == 0) TS(2 + u);
                l0 += __shfl_xor_sync(0xffffffffu, l0, 1);
                l1 += __shfl_xor_sync(0xffffffffu, l1, 1);
                l0 += __shfl_xor_sync(0xffffffffu, l0, 2);
                l1 += __shfl_xor_sync(0xffffffffu, l1, 2);
                const float i0 = 1.f / l0, i1 = 1.f / l1;
                const uint32_t zown = smR + (w ? 3 : 0) * 16384 + t * 16;
#pragma unroll
                for (int kk = 0; kk < 8; kk++) {
                    af[kk][0] = pack_bf16(o[8 * kk + 0] * i0, o[8 * kk + 1] * i0);
                    af[kk][1] = pack_bf16(o[8 * kk + 2] * i1, o[8 * kk + 3] * i1);
                    af[kk][2] = pack_bf16(o[8 * kk + 4] * i0, o[8 * kk + 5] * i0);
                    af[kk][3] = pack_bf16(o[8 * kk + 6] * i1, o[8 * kk + 7] * i1);
                    sts128(zown + kk * 2048, af[kk][0], af[kk][1], af[kk][2], af[kk][3]);
                }
            }
            if (w == 0) bar_arrive<7, 256>(); else bar_arrive<8, 256>();
            lim = 3;
            if (u == 0) {
#pragma unroll
                for (int kk = 0; kk < 8; kk++) lds128(stash + kk * 2048, qf[kk]);
            }
            uint32_t nx[8][4];
#pragma unroll
            for (int ps = 0; ps < 2; ps++) {
                float acc[64];
                const uint32_t keep = smS + (3 + ps) * STAGE_BYTES + w * 16384 + t * 16;
                if (u == 0) {
#pragma unroll
                    for (int i = 0; i < 64; i++) acc[i] = 0.f;
                } else {
                    if (ps == 0) {
#pragma unroll
                        for (int j = 0; j < 8; j++) lds128(keep + j * 2048, nx[j]);
                        asm volatile("fence.proxy.async.shared::cta;" ::: "memory");
                        __syncwarp();
                        if (lane == 0) mbar_arrive(bars + 8 * (NSTAGE + 3));
                    }
#pragma unroll
                    for (int j = 0; j < 8; j++)
#pragma unroll
                        for (int i = 0; i < 4; i++) { acc[8 * j + 2 * i] = __uint_as_float(nx[j][i] << 16); acc[8 * j + 2 * i + 1] = __uint_as_float(nx[j][i] & 0xffff0000u); }
                }
#pragma unroll
                for (int st = 0; st < 4; st++) {
                    if (ps == 0 && st == 2) {
                        if (w == 0) bar_sync<8, 256>(); else bar_sync<7, 256>();
#pragma unroll
                        for (int kk = 0; kk < 8; kk++) lds128(smR + (w ? 0 : 3) * 16384 + kk * 2048 + t * 16, af[8 + kk]);
                    }
                    const bool extra = (u == 1) && (ps == 0 && st == 3);
                    const int sl = extra ? (3 + ps) : slot;
                    if (tid == 0) TS(80 + u * 24 + (ps * 4 + st) * 3);
                    mbar_wait(bars + 8 * sl, extra ? 1 : ph);
                    if (tid == 0) TS(80 + u * 24 + (ps * 4 + st) * 3 + 1);
                    const uint64_t db = mk_desc(smS + sl * STAGE_BYTES + w * 16384, 8192, 1024);
                    wg_fence();
#pragma unroll
                    for (int kk = 0; kk < 4; kk++)
                        wgmma_rs_n128_tb(acc, af[st * 4 + kk][0], af[st * 4 + kk][1], af[st * 4 + kk][2], af[st * 4 + kk][3], db + kk * 128, 1);
                    wg_commit();
                    if (u == 1 && st == 1) {
                        if (ps == 0) {
#pragma unroll
                            for (int j = 0; j < 8; j++) lds128(keep + STAGE_BYTES + j * 2048, nx[j]);
                            asm volatile("fence.proxy.async.shared::cta;" ::: "memory");
                            __syncwarp();
                            if (lane == 0) mbar_arrive(bars + 8 * (NSTAGE + 4));
                        } else {
#pragma unroll
                            for (int j = 0; j < 4; j++) lds128(stash + j * 2048, nx[j]);
                        }
                    }
                    wg_wait<0>();
                    if (tid == 0) TS(80 + u * 24 + (ps * 4 + st) * 3 + 2);
                    if (!extra) {
                        if (lane == 0) mbar_arrive(bars + 8 * (NSTAGE + slot));
                        if (++slot == 3) { slot = 0; ph ^= 1; }
                    }
                }
                fence_regs(acc);
                if (u == 0) {
#pragma unroll
                    for (int j = 0; j < 8; j++)
                        sts128(keep + j * 2048, pack_bf16(acc[8 * j], acc[8 * j + 1]), pack_bf16(acc[8 * j + 2], acc[8 * j + 3]),
                               pack_bf16(acc[8 * j + 4], acc[8 * j + 5]), pack_bf16(acc[8 * j + 6], acc[8 * j + 7]));
                } else {
                    uint2* dst = dst0 + (size_t)ps * 32 * 1024;
#pragma unroll
                    for (int j = 0; j < 16; j++)
                        __stcg(dst + (j >> 3) * 8192 + (j & 7) * 128, make_uint2(pack_bf16(acc[4 * j], acc[4 * j + 1]), pack_bf16(acc[4 * j + 2], acc[4 * j + 3])));
                    __syncwarp();
                    if (lane == 0) mbar_arrive(bars + 8 * (2 * NSTAGE + w * 5 + ps));
                }
                if (tid == 0) TS(4 + u * 8 + ps);
            }
            {
                float acc[32];
                if (u == 0) {
#pragma unroll
                    for (int i = 0; i < 32; i++) acc[i] = 0.f;
                } else {
#pragma unroll
                    for (int j = 0; j < 4; j++)
#pragma unroll
                        for (int i = 0; i < 4; i++) { acc[8 * j + 2 * i] = __uint_as_float(nx[j][i] << 16); acc[8 * j + 2 * i + 1] = __uint_as_float(nx[j][i] & 0xffff0000u); }
                }
                const int sl = u ? 4 : slot;
                mbar_wait(bars + 8 * sl, u ? 1 : ph);
                const uint64_t db = mk_desc(smS + sl * STAGE_BYTES + w * 16384, 8192, 1024);
                wg_fence();
#pragma unroll
                for (int kk = 0; kk < 8; kk++)
                    wgmma_rs_n64_tb(acc, af[kk][0], af[kk][1], af[kk][2], af[kk][3], db + kk * 128, 1);
                wg_commit();
                wg_wait<0>();
                if (u == 0) {
                    if (lane == 0) mbar_arrive(bars + 8 * (NSTAGE + slot));
                    if (++slot == 3) { slot = 0; ph ^= 1; }
                }
                fence_regs(acc);
                if (u == 0) {
#pragma unroll
                    for (int j = 0; j < 4; j++)
                        sts128(stash + j * 2048, pack_bf16(acc[8 * j], acc[8 * j + 1]), pack_bf16(acc[8 * j + 2], acc[8 * j + 3]),
                               pack_bf16(acc[8 * j + 4], acc[8 * j + 5]), pack_bf16(acc[8 * j + 6], acc[8 * j + 7]));
                } else {
#pragma unroll
                    for (int j = 0; j < 8; j++)
                        __stcg(dst8 + j * 128, make_uint2(pack_bf16(acc[4 * j], acc[4 * j + 1]), pack_bf16(acc[4 * j + 2], acc[4 * j + 3])));
                    __syncwarp();
                    if (lane == 0) mbar_arrive(bars + 8 * (2 * NSTAGE + w * 5 + 2));
                }
                if (tid == 0) TS(6 + u * 8);
            }
        }
        {
            __nv_bfloat16* orow = P.out + (size_t)(b * 64 + (t >> 5) * 16 + (lane >> 2)) * (2 * kD) + blk * kD + hp * 8 + (lane & 3) * 2;
#pragma unroll
            for (int g = 0; g < 2; g++) {
                const bool last = (g == 1) && (w == 0);
                if (lane == 0 || (last && lane == 1)) {
                    unsigned* cp = &g_cnt[(grp * 9 + (lane ? 4 : (2 * g + w))) * 32 + hp * 4 + (wid & 3)];
                    unsigned v, n = 0;
                    while (true) {
                        asm volatile("ld.acquire.gpu.global.u32 %0, [%1];" : "=r"(v) : "l"(cp) : "memory");
                        if (v >= (lane ? 16u : 8u)) break;
                        if (++n > (1u << 21)) break;
                    }
                    *cp = 0;
                }
                __syncwarp();
                if (tid == 0) TS(16 + g);
                const uint2* src = g_part + ((size_t)(grp * 80 + g * 32 + 2 * w * 8) * 8 + hp) * 128 + t;
                uint2 v[16], u8[16];
#pragma unroll
                for (int i = 0; i < 16; i++) v[i] = __ldcg(src + (size_t)i * 1024);
                if (last) {
                    const uint2* src8 = g_part + ((size_t)(grp * 80 + 64) * 8 + hp) * 128 + t;
#pragma unroll
                    for (int i = 0; i < 16; i++) u8[i] = __ldcg(src8 + (size_t)i * 1024);
                }
#pragma unroll
                for (int h = 0; h < 2; h++) {
                    float a0 = 0.f, a1 = 0.f, a2 = 0.f, a3 = 0.f;
#pragma unroll
                    for (int i = 0; i < 8; i++) {
                        const uint2 x = v[h * 8 + i];
                        a0 += __uint_as_float(x.x << 16); a1 += __uint_as_float(x.x & 0xffff0000u);
                        a2 += __uint_as_float(x.y << 16); a3 += __uint_as_float(x.y & 0xffff0000u);
                    }
                    *(uint32_t*)(orow + (g * 4 + 2 * w + h) * 64) = pack_bf16(a0, a1);
                    *(uint32_t*)(orow + (g * 4 + 2 * w + h) * 64 + 8 * 2 * kD) = pack_bf16(a2, a3);
                }
                if (last) {
                    float a0 = 0.f, a1 = 0.f, a2 = 0.f, a3 = 0.f;
#pragma unroll
                    for (int i = 0; i < 16; i++) {
                        const uint2 x = u8[i];
                        a0 += __uint_as_float(x.x << 16); a1 += __uint_as_float(x.x & 0xffff0000u);
                        a2 += __uint_as_float(x.y << 16); a3 += __uint_as_float(x.y & 0xffff0000u);
                    }
                    *(uint32_t*)(orow + 512) = pack_bf16(a0, a1);
                    *(uint32_t*)(orow + 512 + 8 * 2 * kD) = pack_bf16(a2, a3);
                }
            }
            if (tid == 0) TS(19);
        }
    }
}

typedef CUresult (*EncodeFn)(CUtensorMap*, CUtensorMapDataType, cuuint32_t, void*, const cuuint64_t*, const cuuint64_t*,
                             const cuuint32_t*, const cuuint32_t*, CUtensorMapInterleave, CUtensorMapSwizzle,
                             CUtensorMapL2promotion, CUtensorMapFloatOOBfill);

void make_map(EncodeFn fn, CUtensorMap* m, const void* ptr, uint64_t cols, uint64_t rows, uint32_t box_rows) {
    cuuint64_t dims[2] = {cols, rows};
    cuuint64_t strides[1] = {cols * 2};
    cuuint32_t box[2] = {64, box_rows};
    cuuint32_t es[2] = {1, 1};
    fn(m, CU_TENSOR_MAP_DATA_TYPE_BFLOAT16, 2, const_cast<void*>(ptr), dims, strides, box, es, CU_TENSOR_MAP_INTERLEAVE_NONE,
       CU_TENSOR_MAP_SWIZZLE_128B, CU_TENSOR_MAP_L2_PROMOTION_L2_256B, CU_TENSOR_MAP_FLOAT_OOB_FILL_NONE);
}

void make_map3(EncodeFn fn, CUtensorMap* m, const void* ptr, uint64_t cols, uint64_t rows, uint32_t box_rows, uint32_t box_groups) {
    cuuint64_t dims[3] = {64, rows, cols / 64};
    cuuint64_t strides[2] = {cols * 2, 128};
    cuuint32_t box[3] = {64, box_rows, box_groups};
    cuuint32_t es[3] = {1, 1, 1};
    fn(m, CU_TENSOR_MAP_DATA_TYPE_BFLOAT16, 3, const_cast<void*>(ptr), dims, strides, box, es, CU_TENSOR_MAP_INTERLEAVE_NONE,
       CU_TENSOR_MAP_SWIZZLE_128B, CU_TENSOR_MAP_L2_PROMOTION_L2_256B, CU_TENSOR_MAP_FLOAT_OOB_FILL_NONE);
}

}

extern "C" void kernel_launch(void* const* d_in, const int* in_sizes, int n_in, void* d_out, int out_size) {
    static EncodeFn enc = nullptr;
    if (!enc) {
        void* fn = nullptr;
        cudaDriverEntryPointQueryResult st;
        cudaGetDriverEntryPoint("cuTensorMapEncodeTiled", &fn, cudaEnableDefault, &st);
        enc = (EncodeFn)fn;
        cudaFuncSetAttribute(fused_gqa_kernel, cudaFuncAttributeMaxDynamicSharedMemorySize, SMEM_BYTES);
    }
    Params P;
    for (int blk = 0; blk < 2; blk++) {
        const void* x = d_in[blk * 5 + 0];
        const void* k = d_in[blk * 5 + 1];
        const void* v = d_in[blk * 5 + 2];
        const void* wq = d_in[blk * 5 + 3];
        const void* wo = d_in[blk * 5 + 4];
        make_map(enc, &P.x[blk], x, kD, kB * kSq, 64);
        make_map3(enc, &P.wq[blk], wq, kHq * kDh, kD, 32, 2);
        make_map3(enc, &P.k[blk], k, kDh, (uint64_t)kB * kHkv * kSk, 128, 2);
        make_map3(enc, &P.v[blk], v, kDh, (uint64_t)kB * kHkv * kSk, 128, 2);
        make_map3(enc, &P.wo[blk], wo, kD, kHq * kDh, 64, 2);
        make_map(enc, &P.wo8[blk], wo, kD, kHq * kDh, 128);
        P.wqp[blk] = (const __nv_bfloat16*)wq;
        P.kp[blk] = (const __nv_bfloat16*)k;
        P.vp[blk] = (const __nv_bfloat16*)v;
        P.wop[blk] = (const __nv_bfloat16*)wo;
    }
    P.out = (__nv_bfloat16*)d_out;
    fused_gqa_kernel<<<128, 384, SMEM_BYTES>>>(P);
}
```

```cpp
#include <cuda_runtime.h>
#include <cuda_bf16.h>
#include <cuda.h>
#include <stdint.h>

namespace {

constexpr int kB = 8, kSq = 64, kD = 576, kHq = 32, kHkv = 16, kSk = 512, kDh = 128;
constexpr int NSTAGE = 5;
constexpr int STAGE_BYTES = 32768;
constexpr int R_BYTES = 65536;
constexpr int SMEM_BYTES = R_BYTES + NSTAGE * STAGE_BYTES + 1024   + 256  ;
constexpr int N_WQ = 18;
constexpr int PF_DIST = 6;

struct __align__(64) Params {
    CUtensorMap x[2], wq[2], k[2], v[2], wo[2], wo8[2];
    const __nv_bfloat16* kp[2];
    const __nv_bfloat16* vp[2];
    const __nv_bfloat16* wop[2];
    __nv_bfloat16* out;
};

__device__ uint2 g_part[16 * 80 * 8 * 128];
__device__ unsigned int g_cnt[16 * 9 * 32];

__device__ __forceinline__ uint32_t smem_u32(const void* p) { return (uint32_t)__cvta_generic_to_shared(p); }
__device__ __forceinline__ void mbar_init(uint32_t bar, int cnt) {
    asm volatile("mbarrier.init.shared::cta.b64 [%0], %1;" ::"r"(bar), "r"(cnt));
}
__device__ __forceinline__ void mbar_expect_tx(uint32_t bar, uint32_t bytes) {
    asm volatile("mbarrier.arrive.expect_tx.shared::cta.b64 _, [%0], %1;" ::"r"(bar), "r"(bytes) : "memory");
}
__device__ __forceinline__ void mbar_arrive(uint32_t bar) {
    asm volatile("mbarrier.arrive.shared::cta.b64 _, [%0];" ::"r"(bar) : "memory");
}
__device__ __forceinline__ bool mbar_try(uint32_t bar, uint32_t parity) {
    uint32_t ok;
    asm volatile("{\n.reg .pred p;\nmbarrier.try_wait.parity.shared::cta.b64 p, [%1], %2;\nselp.u32 %0, 1, 0, p;\n}\n"
                 : "=r"(ok) : "r"(bar), "r"(parity) : "memory");
    return ok != 0;
}
__device__ __forceinline__ void mbar_wait(uint32_t bar, uint32_t parity) {
    if (mbar_try(bar, parity)) return;
    uint32_t n = 0;
    while (!mbar_try(bar, parity)) {
        if (++n > (1u << 20)) break;
    }
}
__device__ __forceinline__ void tma_2d(uint32_t dst, const CUtensorMap* tm, int c0, int c1, uint32_t bar) {
    asm volatile("cp.async.bulk.tensor.2d.shared::cluster.global.mbarrier::complete_tx::bytes [%0], [%1, {%3, %4}], [%2];"
                 ::"r"(dst), "l"(tm), "r"(bar), "r"(c0), "r"(c1) : "memory");
}
__device__ __forceinline__ void tma_3d(uint32_t dst, const CUtensorMap* tm, int c0, int c1, int c2, uint32_t bar) {
    asm volatile("cp.async.bulk.tensor.3d.shared::cluster.global.mbarrier::complete_tx::bytes [%0], [%1, {%3, %4, %5}], [%2];"
                 ::"r"(dst), "l"(tm), "r"(bar), "r"(c0), "r"(c1), "r"(c2) : "memory");
}
__device__ __forceinline__ uint32_t l2_touch(const void* p) {
    uint32_t v;
    asm volatile("ld.global.L2::256B.b32 %0, [%1];" : "=r"(v) : "l"(p) : "memory");
    return v;
}
__device__ __forceinline__ void wg_fence() { asm volatile("wgmma.fence.sync.aligned;" ::: "memory"); }
__device__ __forceinline__ void wg_commit() { asm volatile("wgmma.commit_group.sync.aligned;" ::: "memory"); }
template <int N> __device__ __forceinline__ void wg_wait() { asm volatile("wgmma.wait_group.sync.aligned %0;" ::"n"(N) : "memory"); }
template <int N> __device__ __forceinline__ void fence_regs(float (&d)[N]) {
#pragma unroll
    for (int i = 0; i < N; i++) asm volatile("" : "+f"(d[i])::"memory");
}
__device__ __forceinline__ uint64_t mk_desc(uint32_t addr, uint32_t lbo, uint32_t sbo) {
    return (uint64_t)((addr & 0x3FFFF) >> 4) | ((uint64_t)(lbo >> 4) << 16) | ((uint64_t)(sbo >> 4) << 32) | (1ull << 62);
}
__device__ __forceinline__ uint32_t pack_bf16(float a, float b) {
    uint32_t r;
    asm("cvt.rn.bf16x2.f32 %0, %1, %2;" : "=r"(r) : "f"(b), "f"(a));
    return r;
}
__device__ __forceinline__ float ex2(float x) {
    float y;
    asm("ex2.approx.ftz.f32 %0, %1;" : "=f"(y) : "f"(x));
    return y;
}
template <int ID, int N> __device__ __forceinline__ void bar_sync() { asm volatile("bar.sync %0, %1;" ::"n"(ID), "n"(N) : "memory"); }
template <int ID, int N> __device__ __forceinline__ void bar_arrive() { asm volatile("bar.arrive %0, %1;" ::"n"(ID), "n"(N) : "memory"); }
__device__ __forceinline__ void sts128(uint32_t addr, uint32_t a, uint32_t b, uint32_t c, uint32_t d) {
    asm volatile("st.shared.v4.b32 [%0], {%1,%2,%3,%4};" ::"r"(addr), "r"(a), "r"(b), "r"(c), "r"(d) : "memory");
}
__device__ __forceinline__ void lds128(uint32_t addr, uint32_t (&r)[4]) {
    asm volatile("ld.shared.v4.b32 {%0,%1,%2,%3}, [%4];" : "=r"(r[0]), "=r"(r[1]), "=r"(r[2]), "=r"(r[3]) : "r"(addr) : "memory");
}

__device__ __forceinline__ void wgmma_ss_n256_tb(float (&d)[128], uint64_t da, uint64_t db, int sd) {
    asm volatile("{\n.reg .pred p;\nsetp.ne.b32 p, %130, 0;\n"
        "wgmma.mma_async.sync.aligned.m64n256k16.f32.bf16.bf16 "
        "{%0, %1, %2, %3, %4, %5, %6, %7, %8, %9, %10, %11, %12, %13, %14, %15, %16, %17, %18, %19, %20, %21, %22, %23, %24, %25, %26, %27, %28, %29, %30, %31, %32, %33, %34, %35, %36, %37, %38, %39, %40, %41, %42, %43, %44, %45, %46, %47, %48, %49, %50, %51, %52, %53, %54, %55, %56, %57, %58, %59, %60, %61, %62, %63, %64, %65, %66, %67, %68, %69, %70, %71, %72, %73, %74, %75, %76, %77, %78, %79, %80, %81, %82, %83, %84, %85, %86, %87, %88, %89, %90, %91, %92, %93, %94, %95, %96, %97, %98, %99, %100, %101, %102, %103, %104, %105, %106, %107, %108, %109, %110, %111, %112, %113, %114, %115, %116, %117, %118, %119, %120, %121, %122, %123, %124, %125, %126, %127}, "
        "%128, %129, p, 1, 1, 0, 1;\n}\n"
        : "+f"(d[0]), "+f"(d[1]), "+f"(d[2]), "+f"(d[3]), "+f"(d[4]), "+f"(d[5]), "+f"(d[6]), "+f"(d[7]), "+f"(d[8]), "+f"(d[9]), "+f"(d[10]), "+f"(d[11]), "+f"(d[12]), "+f"(d[13]), "+f"(d[14]), "+f"(d[15]), "+f"(d[16]), "+f"(d[17]), "+f"(d[18]), "+f"(d[19]), "+f"(d[20]), "+f"(d[21]), "+f"(d[22]), "+f"(d[23]), "+f"(d[24]), "+f"(d[25]), "+f"(d[26]), "+f"(d[27]), "+f"(d[28]), "+f"(d[29]), "+f"(d[30]), "+f"(d[31]), "+f"(d[32]), "+f"(d[33]), "+f"(d[34]), "+f"(d[35]), "+f"(d[36]), "+f"(d[37]), "+f"(d[38]), "+f"(d[39]), "+f"(d[40]), "+f"(d[41]), "+f"(d[42]), "+f"(d[43]), "+f"(d[44]), "+f"(d[45]), "+f"(d[46]), "+f"(d[47]), "+f"(d[48]), "+f"(d[49]), "+f"(d[50]), "+f"(d[51]), "+f"(d[52]), "+f"(d[53]), "+f"(d[54]), "+f"(d[55]), "+f"(d[56]), "+f"(d[57]), "+f"(d[58]), "+f"(d[59]), "+f"(d[60]), "+f"(d[61]), "+f"(d[62]), "+f"(d[63]), "+f"(d[64]), "+f"(d[65]), "+f"(d[66]), "+f"(d[67]), "+f"(d[68]), "+f"(d[69]), "+f"(d[70]), "+f"(d[71]), "+f"(d[72]), "+f"(d[73]), "+f"(d[74]), "+f"(d[75]), "+f"(d[76]), "+f"(d[77]), "+f"(d[78]), "+f"(d[79]), "+f"(d[80]), "+f"(d[81]), "+f"(d[82]), "+f"(d[83]), "+f"(d[84]), "+f"(d[85]), "+f"(d[86]), "+f"(d[87]), "+f"(d[88]), "+f"(d[89]), "+f"(d[90]), "+f"(d[91]), "+f"(d[92]), "+f"(d[93]), "+f"(d[94]), "+f"(d[95]), "+f"(d[96]), "+f"(d[97]), "+f"(d[98]), "+f"(d[99]), "+f"(d[100]), "+f"(d[101]), "+f"(d[102]), "+f"(d[103]), "+f"(d[104]), "+f"(d[105]), "+f"(d[106]), "+f"(d[107]), "+f"(d[108]), "+f"(d[109]), "+f"(d[110]), "+f"(d[111]), "+f"(d[112]), "+f"(d[113]), "+f"(d[114]), "+f"(d[115]), "+f"(d[116]), "+f"(d[117]), "+f"(d[118]), "+f"(d[119]), "+f"(d[120]), "+f"(d[121]), "+f"(d[122]), "+f"(d[123]), "+f"(d[124]), "+f"(d[125]), "+f"(d[126]), "+f"(d[127])
        : "l"(da), "l"(db), "r"(sd));
}
__device__ __forceinline__ void wgmma_rs_n128(float (&d)[64], uint32_t a0, uint32_t a1, uint32_t a2, uint32_t a3, uint64_t db, int sd) {
    asm volatile("{\n.reg .pred p;\nsetp.ne.b32 p, %69, 0;\n"
        "wgmma.mma_async.sync.aligned.m64n128k16.f32.bf16.bf16 "
        "{%0, %1, %2, %3, %4, %5, %6, %7, %8, %9, %10, %11, %12, %13, %14, %15, %16, %17, %18, %19, %20, %21, %22, %23, %24, %25, %26, %27, %28, %29, %30, %31, %32, %33, %34, %35, %36, %37, %38, %39, %40, %41, %42, %43, %44, %45, %46, %47, %48, %49, %50, %51, %52, %53, %54, %55, %56, %57, %58, %59, %60, %61, %62, %63}, "
        "{%64, %65, %66, %67}, %68, p, 1, 1, 0;\n}\n"
        : "+f"(d[0]), "+f"(d[1]), "+f"(d[2]), "+f"(d[3]), "+f"(d[4]), "+f"(d[5]), "+f"(d[6]), "+f"(d[7]), "+f"(d[8]), "+f"(d[9]), "+f"(d[10]), "+f"(d[11]), "+f"(d[12]), "+f"(d[13]), "+f"(d[14]), "+f"(d[15]), "+f"(d[16]), "+f"(d[17]), "+f"(d[18]), "+f"(d[19]), "+f"(d[20]), "+f"(d[21]), "+f"(d[22]), "+f"(d[23]), "+f"(d[24]), "+f"(d[25]), "+f"(d[26]), "+f"(d[27]), "+f"(d[28]), "+f"(d[29]), "+f"(d[30]), "+f"(d[31]), "+f"(d[32]), "+f"(d[33]), "+f"(d[34]), "+f"(d[35]), "+f"(d[36]), "+f"(d[37]), "+f"(d[38]), "+f"(d[39]), "+f"(d[40]), "+f"(d[41]), "+f"(d[42]), "+f"(d[43]), "+f"(d[44]), "+f"(d[45]), "+f"(d[46]), "+f"(d[47]), "+f"(d[48]), "+f"(d[49]), "+f"(d[50]), "+f"(d[51]), "+f"(d[52]), "+f"(d[53]), "+f"(d[54]), "+f"(d[55]), "+f"(d[56]), "+f"(d[57]), "+f"(d[58]), "+f"(d[59]), "+f"(d[60]), "+f"(d[61]), "+f"(d[62]), "+f"(d[63])
        : "r"(a0), "r"(a1), "r"(a2), "r"(a3), "l"(db), "r"(sd));
}
__device__ __forceinline__ void wgmma_rs_n128_tb(float (&d)[64], uint32_t a0, uint32_t a1, uint32_t a2, uint32_t a3, uint64_t db, int sd) {
    asm volatile("{\n.reg .pred p;\nsetp.ne.b32 p, %69, 0;\n"
        "wgmma.mma_async.sync.aligned.m64n128k16.f32.bf16.bf16 "
        "{%0, %1, %2, %3, %4, %5, %6, %7, %8, %9, %10, %11, %12, %13, %14, %15, %16, %17, %18, %19, %20, %21, %22, %23, %24, %25, %26, %27, %28, %29, %30, %31, %32, %33, %34, %35, %36, %37, %38, %39, %40, %41, %42, %43, %44, %45, %46, %47, %48, %49, %50, %51, %52, %53, %54, %55, %56, %57, %58, %59, %60, %61, %62, %63}, "
        "{%64, %65, %66, %67}, %68, p, 1, 1, 1;\n}\n"
        : "+f"(d[0]), "+f"(d[1]), "+f"(d[2]), "+f"(d[3]), "+f"(d[4]), "+f"(d[5]), "+f"(d[6]), "+f"(d[7]), "+f"(d[8]), "+f"(d[9]), "+f"(d[10]), "+f"(d[11]), "+f"(d[12]), "+f"(d[13]), "+f"(d[14]), "+f"(d[15]), "+f"(d[16]), "+f"(d[17]), "+f"(d[18]), "+f"(d[19]), "+f"(d[20]), "+f"(d[21]), "+f"(d[22]), "+f"(d[23]), "+f"(d[24]), "+f"(d[25]), "+f"(d[26]), "+f"(d[27]), "+f"(d[28]), "+f"(d[29]), "+f"(d[30]), "+f"(d[31]), "+f"(d[32]), "+f"(d[33]), "+f"(d[34]), "+f"(d[35]), "+f"(d[36]), "+f"(d[37]), "+f"(d[38]), "+f"(d[39]), "+f"(d[40]), "+f"(d[41]), "+f"(d[42]), "+f"(d[43]), "+f"(d[44]), "+f"(d[45]), "+f"(d[46]), "+f"(d[47]), "+f"(d[48]), "+f"(d[49]), "+f"(d[50]), "+f"(d[51]), "+f"(d[52]), "+f"(d[53]), "+f"(d[54]), "+f"(d[55]), "+f"(d[56]), "+f"(d[57]), "+f"(d[58]), "+f"(d[59]), "+f"(d[60]), "+f"(d[61]), "+f"(d[62]), "+f"(d[63])
        : "r"(a0), "r"(a1), "r"(a2), "r"(a3), "l"(db), "r"(sd));
}
__device__ __forceinline__ void wgmma_rs_n64_tb(float (&d)[32], uint32_t a0, uint32_t a1, uint32_t a2, uint32_t a3, uint64_t db, int sd) {
    asm volatile("{\n.reg .pred p;\nsetp.ne.b32 p, %37, 0;\n"
        "wgmma.mma_async.sync.aligned.m64n64k16.f32.bf16.bf16 "
        "{%0, %1, %2, %3, %4, %5, %6, %7, %8, %9, %10, %11, %12, %13, %14, %15, %16, %17, %18, %19, %20, %21, %22, %23, %24, %25, %26, %27, %28, %29, %30, %31}, "
        "{%32, %33, %34, %35}, %36, p, 1, 1, 1;\n}\n"
        : "+f"(d[0]), "+f"(d[1]), "+f"(d[2]), "+f"(d[3]), "+f"(d[4]), "+f"(d[5]), "+f"(d[6]), "+f"(d[7]), "+f"(d[8]), "+f"(d[9]), "+f"(d[10]), "+f"(d[11]), "+f"(d[12]), "+f"(d[13]), "+f"(d[14]), "+f"(d[15]), "+f"(d[16]), "+f"(d[17]), "+f"(d[18]), "+f"(d[19]), "+f"(d[20]), "+f"(d[21]), "+f"(d[22]), "+f"(d[23]), "+f"(d[24]), "+f"(d[25]), "+f"(d[26]), "+f"(d[27]), "+f"(d[28]), "+f"(d[29]), "+f"(d[30]), "+f"(d[31])
        : "r"(a0), "r"(a1), "r"(a2), "r"(a3), "l"(db), "r"(sd));
}


__global__ void __launch_bounds__(384, 1) fused_gqa_kernel(const __grid_constant__ Params P) {
    extern __shared__ uint8_t smem_raw[];
    const uint32_t base = (smem_u32(smem_raw) + 1023u) & ~1023u;
    const uint32_t smR = base;
    const uint32_t smS = base + R_BYTES;
    const uint32_t bars = smS + NSTAGE * STAGE_BYTES;
    const uint32_t prog = bars + 8 * (2 * NSTAGE + 10);
    const int tid = threadIdx.x;
    const int wid = __shfl_sync(0xffffffffu, tid >> 5, 0);
    const int lane = tid & 31;

    const int cta = blockIdx.x;
    const int blk = cta >> 6;
    const int hp = (cta >> 3) & 7;
    const int b = cta & 7;
    const int grp = blk * 8 + b;

    if (tid == 256) {
        asm volatile("prefetch.tensormap [%0];" ::"l"(&P.x[blk]) : "memory");
        asm volatile("prefetch.tensormap [%0];" ::"l"(&P.wq[blk]) : "memory");
        for (int i = 0; i < NSTAGE; i++) {
            mbar_init(bars + 8 * i, 1);
            mbar_init(bars + 8 * (NSTAGE + i), 8);
        }
        for (int i = 0; i < 10; i++) mbar_init(bars + 8 * (2 * NSTAGE + i), 4);
        asm volatile("st.volatile.shared.u32 [%0], %1;" ::"r"(prog), "r"(0) : "memory");
        asm volatile("fence.mbarrier_init.release.cluster;" ::: "memory");
        asm volatile("fence.proxy.async.shared::cta;" ::: "memory");
#pragma unroll
        for (int s = 0; s < NSTAGE; s++) {
            const uint32_t fb = bars + 8 * s;
            const uint32_t dst = smS + s * STAGE_BYTES;
            mbar_expect_tx(fb, (s & 1) ? STAGE_BYTES : STAGE_BYTES + 8192);
            if (!(s & 1)) tma_2d(smR + (s >> 1) * 8192, &P.x[blk], (s >> 1) * 64, b * 64, fb);
#pragma unroll
            for (int p = 0; p < 4; p++) tma_3d(dst + p * 8192, &P.wq[blk], 0, s * 32, hp * 8 + (p & 1) * 4 + (p >> 1) * 2, fb);
        }
        asm volatile("prefetch.tensormap [%0];" ::"l"(&P.k[blk]) : "memory");
        asm volatile("prefetch.tensormap [%0];" ::"l"(&P.v[blk]) : "memory");
        asm volatile("prefetch.tensormap [%0];" ::"l"(&P.wo[blk]) : "memory");
        asm volatile("prefetch.tensormap [%0];" ::"l"(&P.wo8[blk]) : "memory");
    }
    __syncthreads();

    if (wid >= 8) {
        asm volatile("setmaxnreg.dec.sync.aligned.u32 40;");
        auto publish = [&](int hw, int k) {
            mbar_wait(bars + 8 * (2 * NSTAGE + hw * 5 + k), 0);
            const int c = (k < 2) ? (2 * k + hw) : 4;
            asm volatile("fence.acq_rel.gpu;" ::: "memory");
            asm volatile("red.relaxed.gpu.global.add.u32 [%0], 1;" ::"l"(&g_cnt[(grp * 9 + c) * 32 + lane]) : "memory");
        };
        if (wid == 8) {
            if (lane == 0) {
                int slot = 0, ph = 0;
                for (int s = NSTAGE; s < N_WQ; s++) {
                    const uint32_t fb = bars + 8 * slot;
                    mbar_wait(bars + 8 * (NSTAGE + slot), ph);
                    const uint32_t dst = smS + slot * STAGE_BYTES;
                    mbar_expect_tx(fb, (s & 1) ? STAGE_BYTES : STAGE_BYTES + 8192);
                    if (!(s & 1)) tma_2d(smR + ((s >> 1) & 7) * 8192, &P.x[blk], (s >> 1) * 64, b * 64, fb);
#pragma unroll
                    for (int p = 0; p < 4; p++) {
                        const int w = p >> 1, j = p & 1;
                        tma_3d(dst + p * 8192, &P.wq[blk], 0, s * 32, hp * 8 + j * 4 + w * 2, fb);
                    }
                    if (++slot == NSTAGE) { slot = 0; ph ^= 1; }
                }
                int lim = NSTAGE;
                for (int i = 0; i < 34; i++) {
                    const int u = (i >= 17), r = i - 17 * u;
                    const bool extra = (i == 28) || (i == 33);
                    const int sl = extra ? ((i == 28) ? 3 : 4) : slot;
                    const uint32_t fb = bars + 8 * sl;
                    mbar_wait(bars + 8 * (NSTAGE + sl), extra ? 1 : ph);
                    const uint32_t dst = smS + sl * STAGE_BYTES;
                    mbar_expect_tx(fb, STAGE_BYTES);
                    if (r < 8) {
                        const int row = (b * kHkv + hp * 2 + u) * kSk + (r >> 1) * 128;
                        tma_3d(dst, (r & 1) ? &P.v[blk] : &P.k[blk], 0, row, 0, fb);
                    } else {
                        const int q = r - 8, row = hp * 512 + u * 256;
                        if (q < 8) {
                            tma_3d(dst, &P.wo[blk], 0, row + (q & 3) * 64, (q >> 2) * 4, fb);
                            tma_3d(dst + 16384, &P.wo[blk], 0, row + ((q & 3) ^ 2) * 64, (q >> 2) * 4 + 2, fb);
                        } else {
                            tma_2d(dst, &P.wo8[blk], 512, row, fb);
                            tma_2d(dst + 16384, &P.wo8[blk], 512, row + 128, fb);
                        }
                    }
                    asm volatile("st.volatile.shared.u32 [%0], %1;" ::"r"(prog), "r"(i + 1) : "memory");
                    if (i == 7) lim = 3;
                    if (!extra && ++slot == lim) { slot = 0; ph ^= 1; }
                }
            }
            __syncwarp();
            publish(1, 1);
        } else if (wid == 11) {
            uint32_t sink = 0;
            mbar_wait(bars, 0);
            const char* kbase = (const char*)(P.kp[blk] + (size_t)(b * kHkv + hp * 2) * kSk * kDh);
            const char* vbase = (const char*)(P.vp[blk] + (size_t)(b * kHkv + hp * 2) * kSk * kDh);
            const char* wos = (const char*)(P.wop[blk] + (size_t)hp * 512 * kD) + (size_t)b * 36864;
            for (int i = 0; i < 18; i++) {
                const int u = (i >= 9), r = i - 9 * u;
                if (i >= PF_DIST) {
                    uint32_t pr, n = 0;
                    while (true) {
                        asm volatile("ld.volatile.shared.u32 %0, [%1];" : "=r"(pr) : "r"(prog) : "memory");
                        const int prk = ((int)pr <= 8) ? (int)pr : (((int)pr <= 17) ? 8 + ((int)pr - 8) / 9 : (int)pr - 8);
                        if (prk + PF_DIST >= i) break;
                        if (++n > (1u << 22)) break;
                        __nanosleep(100);
                    }
                }
                const char* p = (r < 8) ? (((r & 1) ? vbase : kbase) + (size_t)(u * 4 + (r >> 1)) * 32768 + lane * 256) : (wos + (size_t)u * 294912 + lane * 256);
                uint32_t c[5];
                if (sink == 0x9E3779B9u) asm volatile("st.volatile.shared.u32 [%0], %1;" ::"r"(prog + 4), "r"(sink) : "memory");
#pragma unroll
                for (int j = 0; j < 4; j++) c[j] = l2_touch(p + j * 8192);
                c[4] = 0;
                if (r == 8 && lane < 16) c[4] = l2_touch(p + 4 * 8192);
                sink = c[0] | c[1] | c[2] | c[3] | c[4];
            }
            if (sink == 0x9E3779B9u) asm volatile("st.volatile.shared.u32 [%0], %1;" ::"r"(prog + 4), "r"(sink) : "memory");
            publish(0, 1);
        } else {
            const int hw = wid - 9;
            publish(hw, 0);
            publish(hw, 2);
        }
    } else {
        asm volatile("setmaxnreg.inc.sync.aligned.u32 232;");
        const int w = wid >> 2;
        const int t = tid & 127;
        int slot = 0, ph = 0, lim = NSTAGE;
        uint32_t qf[8][4];
        const uint32_t stash = smR + (1 + w) * 16384 + t * 16;
        {
            float acc[128];
            for (int s = 0; s < N_WQ; s++) {
                mbar_wait(bars + 8 * slot, ph);
                const uint64_t da = mk_desc(smR + ((s >> 1) & 7) * 8192 + (s & 1) * 64, 16, 1024);
                const uint64_t db = mk_desc(smS + slot * STAGE_BYTES + w * 16384, 4096, 1024);
                wg_fence();
                wgmma_ss_n256_tb(acc, da, db, s != 0);
                wgmma_ss_n256_tb(acc, da + 2, db + 128, 1);
                wg_commit();
                wg_wait<0>();
                if (lane == 0) mbar_arrive(bars + 8 * (NSTAGE + slot));
                if (++slot == NSTAGE) { slot = 0; ph ^= 1; }
            }
            fence_regs(acc);
#pragma unroll
            for (int kk = 0; kk < 8; kk++) {
#pragma unroll
                for (int i = 0; i < 4; i++) qf[kk][i] = pack_bf16(acc[8 * kk + 2 * i], acc[8 * kk + 2 * i + 1]);
                sts128(stash + kk * 2048,
                       pack_bf16(acc[64 + 8 * kk + 0], acc[64 + 8 * kk + 1]), pack_bf16(acc[64 + 8 * kk + 2], acc[64 + 8 * kk + 3]),
                       pack_bf16(acc[64 + 8 * kk + 4], acc[64 + 8 * kk + 5]), pack_bf16(acc[64 + 8 * kk + 6], acc[64 + 8 * kk + 7]));
            }
        }
        if (w == 1) bar_arrive<5, 256>();
        const float sc = 0.08838834764831845f * 1.4426950408889634f;
        uint2* dst0 = g_part + (size_t)(grp * 80 + 2 * w * 8 + hp) * 1024 + t;
        uint2* dst8 = g_part + (size_t)(grp * 80 + 64 + hp * 2 + w) * 1024 + t;
#pragma unroll
        for (int u = 0; u < 2; u++) {
            uint32_t af[16][4];
            {
                float o[64], s[64];
                float m0 = -INFINITY, m1 = -INFINITY, l0 = 0.f, l1 = 0.f;
                uint32_t pf[8][4];
#pragma unroll
                for (int i = 0; i < 64; i++) { o[i] = 0.f; s[i] = 0.f; }
#pragma unroll
                for (int i = 0; i < 32; i++) pf[i >> 2][i & 3] = 0u;
#pragma unroll 1
                for (int tt = 0; tt <= 4; tt++) {
                    int vslot = slot;
                    if (tt > 0) {
                        mbar_wait(bars + 8 * slot, ph);
                        if (++slot == lim) { slot = 0; ph ^= 1; }
                    }
                    if (tt < 4) mbar_wait(bars + 8 * slot, ph);
                    if (w == 0) bar_sync<5, 256>(); else bar_sync<6, 256>();
                    wg_fence();
                    if (tt > 0) {
                        const uint64_t db = mk_desc(smS + vslot * STAGE_BYTES, 16384, 1024);
#pragma unroll
                        for (int kk = 0; kk < 8; kk++)
                            wgmma_rs_n128_tb(o, pf[kk][0], pf[kk][1], pf[kk][2], pf[kk][3], db + kk * 128, (tt > 1) || (kk != 0));
                        wg_commit();
                    }
                    if (tt < 4) {
                        const uint64_t db = mk_desc(smS + slot * STAGE_BYTES, 16, 1024);
#pragma unroll
                        for (int kk = 0; kk < 8; kk++)
                            wgmma_rs_n128(s, qf[kk][0], qf[kk][1], qf[kk][2], qf[kk][3], db + (kk >> 2) * 1024 + (kk & 3) * 2, kk != 0);
                        wg_commit();
                    }
                    if (w == 0) bar_arrive<6, 256>(); else if (!(u == 1 && tt == 4)) bar_arrive<5, 256>();
                    wg_wait<0>();
                    fence_regs(o);
                    fence_regs(s);
                    if (tt > 0 && lane == 0) mbar_arrive(bars + 8 * (NSTAGE + vslot));
                    if (tt == 4) break;
                    if (lane == 0) mbar_arrive(bars + 8 * (NSTAGE + slot));
                    if (++slot == lim) { slot = 0; ph ^= 1; }
                    float mx0 = s[0], mx1 = s[2];
#pragma unroll
                    for (int j = 0; j < 16; j++) {
                        mx0 = fmaxf(mx0, fmaxf(s[4 * j], s[4 * j + 1]));
                        mx1 = fmaxf(mx1, fmaxf(s[4 * j + 2], s[4 * j + 3]));
                    }
                    mx0 = fmaxf(mx0, __shfl_xor_sync(0xffffffffu, mx0, 1));
                    mx1 = fmaxf(mx1, __shfl_xor_sync(0xffffffffu, mx1, 1));
                    mx0 = fmaxf(mx0, __shfl_xor_sync(0xffffffffu, mx0, 2));
                    mx1 = fmaxf(mx1, __shfl_xor_sync(0xffffffffu, mx1, 2));
                    const float mn0 = fmaxf(m0, mx0), mn1 = fmaxf(m1, mx1);
                    const float al0 = ex2((m0 - mn0) * sc), al1 = ex2((m1 - mn1) * sc);
                    m0 = mn0; m1 = mn1;
                    const float ms0 = mn0 * sc, ms1 = mn1 * sc;
                    float rs0 = 0.f, rs1 = 0.f;
#pragma unroll
                    for (int j = 0; j < 16; j++) {
                        const float p0 = ex2(fmaf(s[4 * j], sc, -ms0)), p1 = ex2(fmaf(s[4 * j + 1], sc, -ms0));
                        const float p2 = ex2(fmaf(s[4 * j + 2], sc, -ms1)), p3 = ex2(fmaf(s[4 * j + 3], sc, -ms1));
                        rs0 += p0 + p1; rs1 += p2 + p3;
                        pf[j >> 1][(j & 1) * 2] = pack_bf16(p0, p1);
                        pf[j >> 1][(j & 1) * 2 + 1] = pack_bf16(p2, p3);
                    }
                    l0 = l0 * al0 + rs0; l1 = l1 * al1 + rs1;
                    if (tt > 0) {
#pragma unroll
                        for (int j = 0; j < 16; j++) { o[4 * j] *= al0; o[4 * j + 1] *= al0; o[4 * j + 2] *= al1; o[4 * j + 3] *= al1; }
                    }
                }
                l0 += __shfl_xor_sync(0xffffffffu, l0, 1);
                l1 += __shfl_xor_sync(0xffffffffu, l1, 1);
                l0 += __shfl_xor_sync(0xffffffffu, l0, 2);
                l1 += __shfl_xor_sync(0xffffffffu, l1, 2);
                const float i0 = 1.f / l0, i1 = 1.f / l1;
                const uint32_t zown = smR + (w ? 3 : 0) * 16384 + t * 16;
#pragma unroll
                for (int kk = 0; kk < 8; kk++) {
                    af[kk][0] = pack_bf16(o[8 * kk + 0] * i0, o[8 * kk + 1] * i0);
                    af[kk][1] = pack_bf16(o[8 * kk + 2] * i1, o[8 * kk + 3] * i1);
                    af[kk][2] = pack_bf16(o[8 * kk + 4] * i0, o[8 * kk + 5] * i0);
                    af[kk][3] = pack_bf16(o[8 * kk + 6] * i1, o[8 * kk + 7] * i1);
                    sts128(zown + kk * 2048, af[kk][0], af[kk][1], af[kk][2], af[kk][3]);
                }
            }
            if (w == 0) bar_arrive<7, 256>(); else bar_arrive<8, 256>();
            lim = 3;
            if (u == 0) {
#pragma unroll
                for (int kk = 0; kk < 8; kk++) lds128(stash + kk * 2048, qf[kk]);
            }
            uint32_t nx[8][4];
#pragma unroll
            for (int ps = 0; ps < 2; ps++) {
                float acc[64];
                const uint32_t keep = smS + (3 + ps) * STAGE_BYTES + w * 16384 + t * 16;
                if (u == 0) {
#pragma unroll
                    for (int i = 0; i < 64; i++) acc[i] = 0.f;
                } else {
                    if (ps == 0) {
#pragma unroll
                        for (int j = 0; j < 8; j++) lds128(keep + j * 2048, nx[j]);
                        asm volatile("fence.proxy.async.shared::cta;" ::: "memory");
                        __syncwarp();
                        if (lane == 0) mbar_arrive(bars + 8 * (NSTAGE + 3));
                    }
#pragma unroll
                    for (int j = 0; j < 8; j++)
#pragma unroll
                        for (int i = 0; i < 4; i++) { acc[8 * j + 2 * i] = __uint_as_float(nx[j][i] << 16); acc[8 * j + 2 * i + 1] = __uint_as_float(nx[j][i] & 0xffff0000u); }
                }
#pragma unroll
                for (int st = 0; st < 4; st++) {
                    if (ps == 0 && st == 2) {
                        if (w == 0) bar_sync<8, 256>(); else bar_sync<7, 256>();
#pragma unroll
                        for (int kk = 0; kk < 8; kk++) lds128(smR + (w ? 0 : 3) * 16384 + kk * 2048 + t * 16, af[8 + kk]);
                    }
                    const bool extra = (u == 1) && (ps == 0 && st == 3);
                    const int sl = extra ? (3 + ps) : slot;
                    mbar_wait(bars + 8 * sl, extra ? 1 : ph);
                    const uint64_t db = mk_desc(smS + sl * STAGE_BYTES + w * 16384, 8192, 1024);
                    wg_fence();
#pragma unroll
                    for (int kk = 0; kk < 4; kk++)
                        wgmma_rs_n128_tb(acc, af[st * 4 + kk][0], af[st * 4 + kk][1], af[st * 4 + kk][2], af[st * 4 + kk][3], db + kk * 128, 1);
                    wg_commit();
                    if (u == 1 && st == 1) {
                        if (ps == 0) {
#pragma unroll
                            for (int j = 0; j < 8; j++) lds128(keep + STAGE_BYTES + j * 2048, nx[j]);
                            asm volatile("fence.proxy.async.shared::cta;" ::: "memory");
                            __syncwarp();
                            if (lane == 0) mbar_arrive(bars + 8 * (NSTAGE + 4));
                        } else {
#pragma unroll
                            for (int j = 0; j < 4; j++) lds128(stash + j * 2048, nx[j]);
                        }
                    }
                    wg_wait<0>();
                    if (!extra) {
                        if (lane == 0) mbar_arrive(bars + 8 * (NSTAGE + slot));
                        if (++slot == 3) { slot = 0; ph ^= 1; }
                    }
                }
                fence_regs(acc);
                if (u == 0) {
#pragma unroll
                    for (int j = 0; j < 8; j++)
                        sts128(keep + j * 2048, pack_bf16(acc[8 * j], acc[8 * j + 1]), pack_bf16(acc[8 * j + 2], acc[8 * j + 3]),
                               pack_bf16(acc[8 * j + 4], acc[8 * j + 5]), pack_bf16(acc[8 * j + 6], acc[8 * j + 7]));
                } else {
                    uint2* dst = dst0 + (size_t)ps * 32 * 1024;
#pragma unroll
                    for (int j = 0; j < 16; j++)
                        __stcg(dst + (j >> 3) * 8192 + (j & 7) * 128, make_uint2(pack_bf16(acc[4 * j], acc[4 * j + 1]), pack_bf16(acc[4 * j + 2], acc[4 * j + 3])));
                    __syncwarp();
                    if (lane == 0) mbar_arrive(bars + 8 * (2 * NSTAGE + w * 5 + ps));
                }
            }
            {
                float acc[32];
                if (u == 0) {
#pragma unroll
                    for (int i = 0; i < 32; i++) acc[i] = 0.f;
                } else {
#pragma unroll
                    for (int j = 0; j < 4; j++)
#pragma unroll
                        for (int i = 0; i < 4; i++) { acc[8 * j + 2 * i] = __uint_as_float(nx[j][i] << 16); acc[8 * j + 2 * i + 1] = __uint_as_float(nx[j][i] & 0xffff0000u); }
                }
                const int sl = u ? 4 : slot;
                mbar_wait(bars + 8 * sl, u ? 1 : ph);
                const uint64_t db = mk_desc(smS + sl * STAGE_BYTES + w * 16384, 8192, 1024);
                wg_fence();
#pragma unroll
                for (int kk = 0; kk < 8; kk++)
                    wgmma_rs_n64_tb(acc, af[kk][0], af[kk][1], af[kk][2], af[kk][3], db + kk * 128, 1);
                wg_commit();
                wg_wait<0>();
                if (u == 0) {
                    if (lane == 0) mbar_arrive(bars + 8 * (NSTAGE + slot));
                    if (++slot == 3) { slot = 0; ph ^= 1; }
                }
                fence_regs(acc);
                if (u == 0) {
#pragma unroll
                    for (int j = 0; j < 4; j++)
                        sts128(stash + j * 2048, pack_bf16(acc[8 * j], acc[8 * j + 1]), pack_bf16(acc[8 * j + 2], acc[8 * j + 3]),
                               pack_bf16(acc[8 * j + 4], acc[8 * j + 5]), pack_bf16(acc[8 * j + 6], acc[8 * j + 7]));
                } else {
#pragma unroll
                    for (int j = 0; j < 8; j++)
                        __stcg(dst8 + j * 128, make_uint2(pack_bf16(acc[4 * j], acc[4 * j + 1]), pack_bf16(acc[4 * j + 2], acc[4 * j + 3])));
                    __syncwarp();
                    if (lane == 0) mbar_arrive(bars + 8 * (2 * NSTAGE + w * 5 + 2));
                }
            }
        }
        {
            __nv_bfloat16* orow = P.out + (size_t)(b * 64 + (t >> 5) * 16 + (lane >> 2)) * (2 * kD) + blk * kD + hp * 8 + (lane & 3) * 2;
#pragma unroll
            for (int g = 0; g < 2; g++) {
                const bool last = (g == 1) && (w == 0);
                if (lane == 0 || (last && lane == 1)) {
                    unsigned* cp = &g_cnt[(grp * 9 + (lane ? 4 : (2 * g + w))) * 32 + hp * 4 + (wid & 3)];
                    unsigned v, n = 0;
                    while (true) {
                        asm volatile("ld.acquire.gpu.global.u32 %0, [%1];" : "=r"(v) : "l"(cp) : "memory");
                        if (v >= (lane ? 16u : 8u)) break;
                        if (++n > (1u << 21)) break;
                    }
                    *cp = 0;
                }
                __syncwarp();
                const uint2* src = g_part + ((size_t)(grp * 80 + g * 32 + 2 * w * 8) * 8 + hp) * 128 + t;
                uint2 v[16], u8[16];
#pragma unroll
                for (int i = 0; i < 16; i++) v[i] = __ldcg(src + (size_t)i * 1024);
                if (last) {
                    const uint2* src8 = g_part + ((size_t)(grp * 80 + 64) * 8 + hp) * 128 + t;
#pragma unroll
                    for (int i = 0; i < 16; i++) u8[i] = __ldcg(src8 + (size_t)i * 1024);
                }
#pragma unroll
                for (int h = 0; h < 2; h++) {
                    float a0 = 0.f, a1 = 0.f, a2 = 0.f, a3 = 0.f;
#pragma unroll
                    for (int i = 0; i < 8; i++) {
                        const uint2 x = v[h * 8 + i];
                        a0 += __uint_as_float(x.x << 16); a1 += __uint_as_float(x.x & 0xffff0000u);
                        a2 += __uint_as_float(x.y << 16); a3 += __uint_as_float(x.y & 0xffff0000u);
                    }
                    *(uint32_t*)(orow + (g * 4 + 2 * w + h) * 64) = pack_bf16(a0, a1);
                    *(uint32_t*)(orow + (g * 4 + 2 * w + h) * 64 + 8 * 2 * kD) = pack_bf16(a2, a3);
                }
                if (last) {
                    float a0 = 0.f, a1 = 0.f, a2 = 0.f, a3 = 0.f;
#pragma unroll
                    for (int i = 0; i < 16; i++) {
                        const uint2 x = u8[i];
                        a0 += __uint_as_float(x.x << 16); a1 += __uint_as_float(x.x & 0xffff0000u);
                        a2 += __uint_as_float(x.y << 16); a3 += __uint_as_float(x.y & 0xffff0000u);
                    }
                    *(uint32_t*)(orow + 512) = pack_bf16(a0, a1);
                    *(uint32_t*)(orow + 512 + 8 * 2 * kD) = pack_bf16(a2, a3);
                }
            }
        }
    }
}

typedef CUresult (*EncodeFn)(CUtensorMap*, CUtensorMapDataType, cuuint32_t, void*, const cuuint64_t*, const cuuint64_t*,
                             const cuuint32_t*, const cuuint32_t*, CUtensorMapInterleave, CUtensorMapSwizzle,
                             CUtensorMapL2promotion, CUtensorMapFloatOOBfill);

void make_map(EncodeFn fn, CUtensorMap* m, const void* ptr, uint64_t cols, uint64_t rows, uint32_t box_rows) {
    cuuint64_t dims[2] = {cols, rows};
    cuuint64_t strides[1] = {cols * 2};
    cuuint32_t box[2] = {64, box_rows};
    cuuint32_t es[2] = {1, 1};
    fn(m, CU_TENSOR_MAP_DATA_TYPE_BFLOAT16, 2, const_cast<void*>(ptr), dims, strides, box, es, CU_TENSOR_MAP_INTERLEAVE_NONE,
       CU_TENSOR_MAP_SWIZZLE_128B, CU_TENSOR_MAP_L2_PROMOTION_L2_256B, CU_TENSOR_MAP_FLOAT_OOB_FILL_NONE);
}

void make_map3(EncodeFn fn, CUtensorMap* m, const void* ptr, uint64_t cols, uint64_t rows, uint32_t box_rows, uint32_t box_groups) {
    cuuint64_t dims[3] = {64, rows, cols / 64};
    cuuint64_t strides[2] = {cols * 2, 128};
    cuuint32_t box[3] = {64, box_rows, box_groups};
    cuuint32_t es[3] = {1, 1, 1};
    fn(m, CU_TENSOR_MAP_DATA_TYPE_BFLOAT16, 3, const_cast<void*>(ptr), dims, strides, box, es, CU_TENSOR_MAP_INTERLEAVE_NONE,
       CU_TENSOR_MAP_SWIZZLE_128B, CU_TENSOR_MAP_L2_PROMOTION_L2_256B, CU_TENSOR_MAP_FLOAT_OOB_FILL_NONE);
}

}

extern "C" void kernel_launch(void* const* d_in, const int* in_sizes, int n_in, void* d_out, int out_size) {
    static EncodeFn enc = nullptr;
    if (!enc) {
        void* fn = nullptr;
        cudaDriverEntryPointQueryResult st;
        cudaGetDriverEntryPoint("cuTensorMapEncodeTiled", &fn, cudaEnableDefault, &st);
        enc = (EncodeFn)fn;
        cudaFuncSetAttribute(fused_gqa_kernel, cudaFuncAttributeMaxDynamicSharedMemorySize, SMEM_BYTES);
    }
    Params P;
    for (int blk = 0; blk < 2; blk++) {
        const void* x = d_in[blk * 5 + 0];
        const void* k = d_in[blk * 5 + 1];
        const void* v = d_in[blk * 5 + 2];
        const void* wq = d_in[blk * 5 + 3];
        const void* wo = d_in[blk * 5 + 4];
        make_map(enc, &P.x[blk], x, kD, kB * kSq, 64);
        make_map3(enc, &P.wq[blk], wq, kHq * kDh, kD, 32, 2);
        make_map3(enc, &P.k[blk], k, kDh, (uint64_t)kB * kHkv * kSk, 128, 2);
        make_map3(enc, &P.v[blk], v, kDh, (uint64_t)kB * kHkv * kSk, 128, 2);
        make_map3(enc, &P.wo[blk], wo, kD, kHq * kDh, 64, 2);
        make_map(enc, &P.wo8[blk], wo, kD, kHq * kDh, 128);
        P.kp[blk] = (const __nv_bfloat16*)k;
        P.vp[blk] = (const __nv_bfloat16*)v;
        P.wop[blk] = (const __nv_bfloat16*)wo;
    }
    P.out = (__nv_bfloat16*)d_out;
    fused_gqa_kernel<<<128, 384, SMEM_BYTES>>>(P);
}
```

```cpp
#include <cuda_runtime.h>
#include <cuda_bf16.h>
#include <cuda.h>
#include <stdint.h>

namespace {

constexpr int kB = 8, kSq = 64, kD = 576, kHq = 32, kHkv = 16, kSk = 512, kDh = 128;
constexpr int NSTAGE = 5;
constexpr int STAGE_BYTES = 32768;
constexpr int R_BYTES = 65536;
constexpr int SMEM_BYTES = R_BYTES + NSTAGE * STAGE_BYTES + 1024   + 256  ;
constexpr int N_WQ = 18;
#define PF_DIST_V 6
#define OP_WAIT0 1
#define QP_WAIT0 1
#define PF_POS1 9
#define PF_START 1
#define L2PROMO CU_TENSOR_MAP_L2_PROMOTION_L2_256B
#define PF_SPLIT 0
#define PF_SKIP 0
#define PF_EARLY 2
#define PF_WQ 0
#define PF_SLEEP 1000
constexpr int PF_DIST = PF_DIST_V;

struct __align__(64) Params {
    CUtensorMap x[2], wq[2], k[2], v[2], wo[2], wo8[2];
    const __nv_bfloat16* wqp[2];
    const __nv_bfloat16* kp[2];
    const __nv_bfloat16* vp[2];
    const __nv_bfloat16* wop[2];
    __nv_bfloat16* out;
};

__device__ uint4 g_p1[16 * 8 * 8 * 4 * 128];
__device__ uint4 g_ox[16 * 8 * 2 * 8 * 128];
__device__ uint2 g_p8[16 * 16 * 8 * 128];
__device__ unsigned int g_c1[16 * 8 * 8];
__device__ unsigned int g_co[16 * 16 * 32];
__device__ unsigned int g_c8[16 * 32];
#define TS(k) do {} while (0)

__device__ __forceinline__ uint32_t smem_u32(const void* p) { return (uint32_t)__cvta_generic_to_shared(p); }
__device__ __forceinline__ void mbar_init(uint32_t bar, int cnt) {
    asm volatile("mbarrier.init.shared::cta.b64 [%0], %1;" ::"r"(bar), "r"(cnt));
}
__device__ __forceinline__ void mbar_expect_tx(uint32_t bar, uint32_t bytes) {
    asm volatile("mbarrier.arrive.expect_tx.shared::cta.b64 _, [%0], %1;" ::"r"(bar), "r"(bytes) : "memory");
}
__device__ __forceinline__ void mbar_arrive(uint32_t bar) {
    asm volatile("mbarrier.arrive.shared::cta.b64 _, [%0];" ::"r"(bar) : "memory");
}
__device__ __forceinline__ bool mbar_try(uint32_t bar, uint32_t parity) {
    uint32_t ok;
    asm volatile("{\n.reg .pred p;\nmbarrier.try_wait.parity.shared::cta.b64 p, [%1], %2;\nselp.u32 %0, 1, 0, p;\n}\n"
                 : "=r"(ok) : "r"(bar), "r"(parity) : "memory");
    return ok != 0;
}
__device__ __forceinline__ void mbar_wait(uint32_t bar, uint32_t parity) {
    if (mbar_try(bar, parity)) return;
    uint32_t n = 0;
    while (!mbar_try(bar, parity)) {
        if (++n > (1u << 20)) break;
    }
}
__device__ __forceinline__ void tma_2d(uint32_t dst, const CUtensorMap* tm, int c0, int c1, uint32_t bar) {
    asm volatile("cp.async.bulk.tensor.2d.shared::cluster.global.mbarrier::complete_tx::bytes [%0], [%1, {%3, %4}], [%2];"
                 ::"r"(dst), "l"(tm), "r"(bar), "r"(c0), "r"(c1) : "memory");
}
__device__ __forceinline__ void tma_3d(uint32_t dst, const CUtensorMap* tm, int c0, int c1, int c2, uint32_t bar) {
    asm volatile("cp.async.bulk.tensor.3d.shared::cluster.global.mbarrier::complete_tx::bytes [%0], [%1, {%3, %4, %5}], [%2];"
                 ::"r"(dst), "l"(tm), "r"(bar), "r"(c0), "r"(c1), "r"(c2) : "memory");
}
__device__ __forceinline__ void l2_prefetch(const void* p, uint32_t bytes) {
    asm volatile("cp.async.bulk.prefetch.L2.global [%0], %1;" ::"l"(p), "r"(bytes) : "memory");
}
__device__ __forceinline__ uint32_t l2_touch(const void* p) {
    uint32_t v;
    asm volatile("ld.global.L2::256B.b32 %0, [%1];" : "=r"(v) : "l"(p) : "memory");
    return v;
}
__device__ __forceinline__ void wg_fence() { asm volatile("wgmma.fence.sync.aligned;" ::: "memory"); }
__device__ __forceinline__ void wg_commit() { asm volatile("wgmma.commit_group.sync.aligned;" ::: "memory"); }
template <int N> __device__ __forceinline__ void wg_wait() { asm volatile("wgmma.wait_group.sync.aligned %0;" ::"n"(N) : "memory"); }
template <int N> __device__ __forceinline__ void fence_regs(float (&d)[N]) {
#pragma unroll
    for (int i = 0; i < N; i++) asm volatile("" : "+f"(d[i])::"memory");
}
__device__ __forceinline__ uint64_t mk_desc(uint32_t addr, uint32_t lbo, uint32_t sbo) {
    return (uint64_t)((addr & 0x3FFFF) >> 4) | ((uint64_t)(lbo >> 4) << 16) | ((uint64_t)(sbo >> 4) << 32) | (1ull << 62);
}
__device__ __forceinline__ uint32_t pack_bf16(float a, float b) {
    uint32_t r;
    asm("cvt.rn.bf16x2.f32 %0, %1, %2;" : "=r"(r) : "f"(b), "f"(a));
    return r;
}
__device__ __forceinline__ float ex2(float x) {
    float y;
    asm("ex2.approx.ftz.f32 %0, %1;" : "=f"(y) : "f"(x));
    return y;
}
template <int ID, int N> __device__ __forceinline__ void bar_sync() { asm volatile("bar.sync %0, %1;" ::"n"(ID), "n"(N) : "memory"); }
template <int ID, int N> __device__ __forceinline__ void bar_arrive() { asm volatile("bar.arrive %0, %1;" ::"n"(ID), "n"(N) : "memory"); }
__device__ __forceinline__ void sts128(uint32_t addr, uint32_t a, uint32_t b, uint32_t c, uint32_t d) {
    asm volatile("st.shared.v4.b32 [%0], {%1,%2,%3,%4};" ::"r"(addr), "r"(a), "r"(b), "r"(c), "r"(d) : "memory");
}
__device__ __forceinline__ void lds128(uint32_t addr, uint32_t (&r)[4]) {
    asm volatile("ld.shared.v4.b32 {%0,%1,%2,%3}, [%4];" : "=r"(r[0]), "=r"(r[1]), "=r"(r[2]), "=r"(r[3]) : "r"(addr) : "memory");
}

__device__ __forceinline__ void wait_count(unsigned* cp, unsigned need, int lane) {
    if (lane == 0) {
        unsigned v, n = 0;
        while (true) {
            asm volatile("ld.acquire.gpu.global.u32 %0, [%1];" : "=r"(v) : "l"(cp) : "memory");
            if (v >= need) break;
            if (++n > (1u << 21)) break;
        }
        *cp = 0;
    }
    __syncwarp();
}

__device__ __forceinline__ void wgmma_ss_n256_tb(float (&d)[128], uint64_t da, uint64_t db, int sd) {
    asm volatile("{\n.reg .pred p;\nsetp.ne.b32 p, %130, 0;\n"
        "wgmma.mma_async.sync.aligned.m64n256k16.f32.bf16.bf16 "
        "{%0, %1, %2, %3, %4, %5, %6, %7, %8, %9, %10, %11, %12, %13, %14, %15, %16, %17, %18, %19, %20, %21, %22, %23, %24, %25, %26, %27, %28, %29, %30, %31, %32, %33, %34, %35, %36, %37, %38, %39, %40, %41, %42, %43, %44, %45, %46, %47, %48, %49, %50, %51, %52, %53, %54, %55, %56, %57, %58, %59, %60, %61, %62, %63, %64, %65, %66, %67, %68, %69, %70, %71, %72, %73, %74, %75, %76, %77, %78, %79, %80, %81, %82, %83, %84, %85, %86, %87, %88, %89, %90, %91, %92, %93, %94, %95, %96, %97, %98, %99, %100, %101, %102, %103, %104, %105, %106, %107, %108, %109, %110, %111, %112, %113, %114, %115, %116, %117, %118, %119, %120, %121, %122, %123, %124, %125, %126, %127}, "
        "%128, %129, p, 1, 1, 0, 1;\n}\n"
        : "+f"(d[0]), "+f"(d[1]), "+f"(d[2]), "+f"(d[3]), "+f"(d[4]), "+f"(d[5]), "+f"(d[6]), "+f"(d[7]), "+f"(d[8]), "+f"(d[9]), "+f"(d[10]), "+f"(d[11]), "+f"(d[12]), "+f"(d[13]), "+f"(d[14]), "+f"(d[15]), "+f"(d[16]), "+f"(d[17]), "+f"(d[18]), "+f"(d[19]), "+f"(d[20]), "+f"(d[21]), "+f"(d[22]), "+f"(d[23]), "+f"(d[24]), "+f"(d[25]), "+f"(d[26]), "+f"(d[27]), "+f"(d[28]), "+f"(d[29]), "+f"(d[30]), "+f"(d[31]), "+f"(d[32]), "+f"(d[33]), "+f"(d[34]), "+f"(d[35]), "+f"(d[36]), "+f"(d[37]), "+f"(d[38]), "+f"(d[39]), "+f"(d[40]), "+f"(d[41]), "+f"(d[42]), "+f"(d[43]), "+f"(d[44]), "+f"(d[45]), "+f"(d[46]), "+f"(d[47]), "+f"(d[48]), "+f"(d[49]), "+f"(d[50]), "+f"(d[51]), "+f"(d[52]), "+f"(d[53]), "+f"(d[54]), "+f"(d[55]), "+f"(d[56]), "+f"(d[57]), "+f"(d[58]), "+f"(d[59]), "+f"(d[60]), "+f"(d[61]), "+f"(d[62]), "+f"(d[63]), "+f"(d[64]), "+f"(d[65]), "+f"(d[66]), "+f"(d[67]), "+f"(d[68]), "+f"(d[69]), "+f"(d[70]), "+f"(d[71]), "+f"(d[72]), "+f"(d[73]), "+f"(d[74]), "+f"(d[75]), "+f"(d[76]), "+f"(d[77]), "+f"(d[78]), "+f"(d[79]), "+f"(d[80]), "+f"(d[81]), "+f"(d[82]), "+f"(d[83]), "+f"(d[84]), "+f"(d[85]), "+f"(d[86]), "+f"(d[87]), "+f"(d[88]), "+f"(d[89]), "+f"(d[90]), "+f"(d[91]), "+f"(d[92]), "+f"(d[93]), "+f"(d[94]), "+f"(d[95]), "+f"(d[96]), "+f"(d[97]), "+f"(d[98]), "+f"(d[99]), "+f"(d[100]), "+f"(d[101]), "+f"(d[102]), "+f"(d[103]), "+f"(d[104]), "+f"(d[105]), "+f"(d[106]), "+f"(d[107]), "+f"(d[108]), "+f"(d[109]), "+f"(d[110]), "+f"(d[111]), "+f"(d[112]), "+f"(d[113]), "+f"(d[114]), "+f"(d[115]), "+f"(d[116]), "+f"(d[117]), "+f"(d[118]), "+f"(d[119]), "+f"(d[120]), "+f"(d[121]), "+f"(d[122]), "+f"(d[123]), "+f"(d[124]), "+f"(d[125]), "+f"(d[126]), "+f"(d[127])
        : "l"(da), "l"(db), "r"(sd));
}
__device__ __forceinline__ void wgmma_rs_n128(float (&d)[64], uint32_t a0, uint32_t a1, uint32_t a2, uint32_t a3, uint64_t db, int sd) {
    asm volatile("{\n.reg .pred p;\nsetp.ne.b32 p, %69, 0;\n"
        "wgmma.mma_async.sync.aligned.m64n128k16.f32.bf16.bf16 "
        "{%0, %1, %2, %3, %4, %5, %6, %7, %8, %9, %10, %11, %12, %13, %14, %15, %16, %17, %18, %19, %20, %21, %22, %23, %24, %25, %26, %27, %28, %29, %30, %31, %32, %33, %34, %35, %36, %37, %38, %39, %40, %41, %42, %43, %44, %45, %46, %47, %48, %49, %50, %51, %52, %53, %54, %55, %56, %57, %58, %59, %60, %61, %62, %63}, "
        "{%64, %65, %66, %67}, %68, p, 1, 1, 0;\n}\n"
        : "+f"(d[0]), "+f"(d[1]), "+f"(d[2]), "+f"(d[3]), "+f"(d[4]), "+f"(d[5]), "+f"(d[6]), "+f"(d[7]), "+f"(d[8]), "+f"(d[9]), "+f"(d[10]), "+f"(d[11]), "+f"(d[12]), "+f"(d[13]), "+f"(d[14]), "+f"(d[15]), "+f"(d[16]), "+f"(d[17]), "+f"(d[18]), "+f"(d[19]), "+f"(d[20]), "+f"(d[21]), "+f"(d[22]), "+f"(d[23]), "+f"(d[24]), "+f"(d[25]), "+f"(d[26]), "+f"(d[27]), "+f"(d[28]), "+f"(d[29]), "+f"(d[30]), "+f"(d[31]), "+f"(d[32]), "+f"(d[33]), "+f"(d[34]), "+f"(d[35]), "+f"(d[36]), "+f"(d[37]), "+f"(d[38]), "+f"(d[39]), "+f"(d[40]), "+f"(d[41]), "+f"(d[42]), "+f"(d[43]), "+f"(d[44]), "+f"(d[45]), "+f"(d[46]), "+f"(d[47]), "+f"(d[48]), "+f"(d[49]), "+f"(d[50]), "+f"(d[51]), "+f"(d[52]), "+f"(d[53]), "+f"(d[54]), "+f"(d[55]), "+f"(d[56]), "+f"(d[57]), "+f"(d[58]), "+f"(d[59]), "+f"(d[60]), "+f"(d[61]), "+f"(d[62]), "+f"(d[63])
        : "r"(a0), "r"(a1), "r"(a2), "r"(a3), "l"(db), "r"(sd));
}
__device__ __forceinline__ void wgmma_rs_n128_tb(float (&d)[64], uint32_t a0, uint32_t a1, uint32_t a2, uint32_t a3, uint64_t db, int sd) {
    asm volatile("{\n.reg .pred p;\nsetp.ne.b32 p, %69, 0;\n"
        "wgmma.mma_async.sync.aligned.m64n128k16.f32.bf16.bf16 "
        "{%0, %1, %2, %3, %4, %5, %6, %7, %8, %9, %10, %11, %12, %13, %14, %15, %16, %17, %18, %19, %20, %21, %22, %23, %24, %25, %26, %27, %28, %29, %30, %31, %32, %33, %34, %35, %36, %37, %38, %39, %40, %41, %42, %43, %44, %45, %46, %47, %48, %49, %50, %51, %52, %53, %54, %55, %56, %57, %58, %59, %60, %61, %62, %63}, "
        "{%64, %65, %66, %67}, %68, p, 1, 1, 1;\n}\n"
        : "+f"(d[0]), "+f"(d[1]), "+f"(d[2]), "+f"(d[3]), "+f"(d[4]), "+f"(d[5]), "+f"(d[6]), "+f"(d[7]), "+f"(d[8]), "+f"(d[9]), "+f"(d[10]), "+f"(d[11]), "+f"(d[12]), "+f"(d[13]), "+f"(d[14]), "+f"(d[15]), "+f"(d[16]), "+f"(d[17]), "+f"(d[18]), "+f"(d[19]), "+f"(d[20]), "+f"(d[21]), "+f"(d[22]), "+f"(d[23]), "+f"(d[24]), "+f"(d[25]), "+f"(d[26]), "+f"(d[27]), "+f"(d[28]), "+f"(d[29]), "+f"(d[30]), "+f"(d[31]), "+f"(d[32]), "+f"(d[33]), "+f"(d[34]), "+f"(d[35]), "+f"(d[36]), "+f"(d[37]), "+f"(d[38]), "+f"(d[39]), "+f"(d[40]), "+f"(d[41]), "+f"(d[42]), "+f"(d[43]), "+f"(d[44]), "+f"(d[45]), "+f"(d[46]), "+f"(d[47]), "+f"(d[48]), "+f"(d[49]), "+f"(d[50]), "+f"(d[51]), "+f"(d[52]), "+f"(d[53]), "+f"(d[54]), "+f"(d[55]), "+f"(d[56]), "+f"(d[57]), "+f"(d[58]), "+f"(d[59]), "+f"(d[60]), "+f"(d[61]), "+f"(d[62]), "+f"(d[63])
        : "r"(a0), "r"(a1), "r"(a2), "r"(a3), "l"(db), "r"(sd));
}
__device__ __forceinline__ void wgmma_rs_n64_tb(float (&d)[32], uint32_t a0, uint32_t a1, uint32_t a2, uint32_t a3, uint64_t db, int sd) {
    asm volatile("{\n.reg .pred p;\nsetp.ne.b32 p, %37, 0;\n"
        "wgmma.mma_async.sync.aligned.m64n64k16.f32.bf16.bf16 "
        "{%0, %1, %2, %3, %4, %5, %6, %7, %8, %9, %10, %11, %12, %13, %14, %15, %16, %17, %18, %19, %20, %21, %22, %23, %24, %25, %26, %27, %28, %29, %30, %31}, "
        "{%32, %33, %34, %35}, %36, p, 1, 1, 1;\n}\n"
        : "+f"(d[0]), "+f"(d[1]), "+f"(d[2]), "+f"(d[3]), "+f"(d[4]), "+f"(d[5]), "+f"(d[6]), "+f"(d[7]), "+f"(d[8]), "+f"(d[9]), "+f"(d[10]), "+f"(d[11]), "+f"(d[12]), "+f"(d[13]), "+f"(d[14]), "+f"(d[15]), "+f"(d[16]), "+f"(d[17]), "+f"(d[18]), "+f"(d[19]), "+f"(d[20]), "+f"(d[21]), "+f"(d[22]), "+f"(d[23]), "+f"(d[24]), "+f"(d[25]), "+f"(d[26]), "+f"(d[27]), "+f"(d[28]), "+f"(d[29]), "+f"(d[30]), "+f"(d[31])
        : "r"(a0), "r"(a1), "r"(a2), "r"(a3), "l"(db), "r"(sd));
}

__global__ void __launch_bounds__(384, 1) fused_gqa_kernel(const __grid_constant__ Params P) {
    extern __shared__ uint8_t smem_raw[];
    const uint32_t base = (smem_u32(smem_raw) + 1023u) & ~1023u;
    const uint32_t smR = base;
    const uint32_t smS = base + R_BYTES;
    const uint32_t bars = smS + NSTAGE * STAGE_BYTES;
    const uint32_t prog = bars + 8 * (2 * NSTAGE + 10);
    const int tid = threadIdx.x;
    const int wid = __shfl_sync(0xffffffffu, tid >> 5, 0);
    const int lane = tid & 31;

    const int cta = blockIdx.x;
    const int blk = cta >> 6;
    const int hp = (cta >> 3) & 7;
    const int b = cta & 7;
    const int grp = blk * 8 + b;

    if (tid == 256) {
        TS(0);
        asm volatile("prefetch.tensormap [%0];" ::"l"(&P.x[blk]) : "memory");
        asm volatile("prefetch.tensormap [%0];" ::"l"(&P.wq[blk]) : "memory");
        for (int i = 0; i < NSTAGE; i++) {
            mbar_init(bars + 8 * i, 1);
            mbar_init(bars + 8 * (NSTAGE + i), 8);
        }
        for (int i = 0; i < 10; i++) mbar_init(bars + 8 * (2 * NSTAGE + i), 4);
        asm volatile("st.volatile.shared.u32 [%0], %1;" ::"r"(prog), "r"(0) : "memory");
        asm volatile("fence.mbarrier_init.release.cluster;" ::: "memory");
        asm volatile("fence.proxy.async.shared::cta;" ::: "memory");
#pragma unroll
        for (int s = 0; s < NSTAGE; s++) {
            const uint32_t fb = bars + 8 * s;
            const uint32_t dst = smS + s * STAGE_BYTES;
            mbar_expect_tx(fb, (s & 1) ? STAGE_BYTES : STAGE_BYTES + 8192);
            if (!(s & 1)) tma_2d(smR + (s >> 1) * 8192, &P.x[blk], (s >> 1) * 64, b * 64, fb);
#pragma unroll
            for (int p = 0; p < 4; p++) tma_3d(dst + p * 8192, &P.wq[blk], 0, s * 32, hp * 8 + (p & 1) * 4 + (p >> 1) * 2, fb);
        }
        asm volatile("prefetch.tensormap [%0];" ::"l"(&P.k[blk]) : "memory");
        asm volatile("prefetch.tensormap [%0];" ::"l"(&P.v[blk]) : "memory");
        asm volatile("prefetch.tensormap [%0];" ::"l"(&P.wo[blk]) : "memory");
        asm volatile("prefetch.tensormap [%0];" ::"l"(&P.wo8[blk]) : "memory");
    }
    __syncthreads();

    if (wid >= 8) {
        asm volatile("setmaxnreg.dec.sync.aligned.u32 40;");
        auto publish = [&](int hw, int k) {
            mbar_wait(bars + 8 * (2 * NSTAGE + hw * 5 + k), 0);
            unsigned* cp = (k < 2) ? &g_c1[(grp * 8 + 4 * k + 2 * hw + ((lane >> 2) & 1)) * 8 + (hp >> 2) * 4 + (lane & 3)]
                         : (k == 2) ? &g_co[(grp * 16 + hp * 2 + hw) * 32 + lane] : &g_c8[grp * 32 + lane];
            asm volatile("fence.acq_rel.gpu;" ::: "memory");
            if (k >= 2 || lane < 8) asm volatile("red.relaxed.gpu.global.add.u32 [%0], 1;" ::"l"(cp) : "memory");
        };
        if (wid == 8) {
            if (lane == 0) {
                int slot = 0, ph = 0;
                for (int s = NSTAGE; s < N_WQ; s++) {
                    const uint32_t fb = bars + 8 * slot;
                    mbar_wait(bars + 8 * (NSTAGE + slot), ph);
                    const uint32_t dst = smS + slot * STAGE_BYTES;
                    mbar_expect_tx(fb, (s & 1) ? STAGE_BYTES : STAGE_BYTES + 8192);
                    if (!(s & 1)) tma_2d(smR + ((s >> 1) & 7) * 8192, &P.x[blk], (s >> 1) * 64, b * 64, fb);
#pragma unroll
                    for (int p = 0; p < 4; p++) {
                        const int w = p >> 1, j = p & 1;
                        tma_3d(dst + p * 8192, &P.wq[blk], 0, s * 32, hp * 8 + j * 4 + w * 2, fb);
                    }
                    if (++slot == NSTAGE) { slot = 0; ph ^= 1; }
                }
                for (int i = 0; i < 34; i++) {
                    const int u = (i >= 17), r = i - 17 * u;
                    const uint32_t fb = bars + 8 * slot;
                    mbar_wait(bars + 8 * (NSTAGE + slot), ph);
                    const uint32_t dst = smS + slot * STAGE_BYTES;
                    mbar_expect_tx(fb, STAGE_BYTES);
                    const int q = r - 8;
                    if (r < 8) {
                        const int row = (b * kHkv + hp * 2 + u) * kSk + (r >> 1) * 128;
                        tma_3d(dst, (r & 1) ? &P.v[blk] : &P.k[blk], 0, row, 0, fb);
                    } else if (u == 0 && q < 8) {
                        tma_3d(dst, &P.wo[blk], 0, hp * 512 + (q & 3) * 64, (q >> 2) * 4, fb);
                        tma_3d(dst + 16384, &P.wo[blk], 0, hp * 512 + ((q & 3) ^ 2) * 64, (q >> 2) * 4 + 2, fb);
                    } else if (u == 0 || q == 0) {
                        tma_2d(dst, &P.wo8[blk], 512, hp * 512 + u * 256, fb);
                        tma_2d(dst + 16384, &P.wo8[blk], 512, hp * 512 + u * 256 + 128, fb);
                    } else {
                        const int j = (hp + q - 1) & 7;
                        tma_2d(dst, &P.wo8[blk], hp * 64, j * 512 + 256, fb);
                        tma_2d(dst + 16384, &P.wo8[blk], hp * 64, j * 512 + 384, fb);
                    }
                    asm volatile("st.volatile.shared.u32 [%0], %1;" ::"r"(prog), "r"(i + 1) : "memory");
                    if (++slot == NSTAGE) { slot = 0; ph ^= 1; }
                }
            }
        } else if (wid == 11) {
            if (PF_DIST > 0) {
                uint32_t sink = 0;
                mbar_wait(bars, 0);
                if (PF_WQ) {
                    const char* wqs = (const char*)(P.wqp[blk] + hp * 512) + (size_t)(160 + b * 52) * 8192;
#pragma unroll
                    for (int h = 0; h < 2; h++) {
#pragma unroll
                        for (int j = 0; j < 4; j++) {
                            const int e = (h * 4 + j) * 32 + lane;
                            if (e < 208) sink |= l2_touch(wqs + (size_t)(e >> 2) * 8192 + (e & 3) * 256);
                        }
                        if (sink == 0x9E3779B9u) asm volatile("st.volatile.shared.u32 [%0], %1;" ::"r"(prog + 4), "r"(sink) : "memory");
                    }
                }
                const char* kbase = (const char*)(P.kp[blk] + (size_t)(b * kHkv + hp * 2) * kSk * kDh);
                const char* vbase = (const char*)(P.vp[blk] + (size_t)(b * kHkv + hp * 2) * kSk * kDh);
                const char* wos = (const char*)(P.wop[blk] + (size_t)hp * 512 * kD) + (size_t)b * 36864;
                for (int i = 0; i < 18; i++) {
                    const int u = (i >= 9), r = i - 9 * u;
                    const int pos = u ? (PF_POS1 + r) : r;
                    if (pos >= PF_DIST) {
                        uint32_t pr, n = 0;
                        while (true) {
                            asm volatile("ld.volatile.shared.u32 %0, [%1];" : "=r"(pr) : "r"(prog) : "memory");
                            const int prk = ((int)pr <= 8) ? (int)pr : (((int)pr <= 17) ? 8 + (((int)pr - 8) * (PF_POS1 - 8)) / 9 : (int)pr - 17 + PF_POS1);
                            if (prk + PF_DIST >= pos) break;
                            if (++n > (1u << 22)) break;
                            __nanosleep(100);
                        }
                    }
                    const char* p = (r < 8) ? (((r & 1) ? vbase : kbase) + (size_t)(u * 4 + (r >> 1)) * 32768 + lane * 256) : (wos + (size_t)u * 294912 + lane * 256);
                    uint32_t c[5];
                    if (sink == 0x9E3779B9u) asm volatile("st.volatile.shared.u32 [%0], %1;" ::"r"(prog + 4), "r"(sink) : "memory");
#pragma unroll
                    for (int j = 0; j < 4; j++) c[j] = l2_touch(p + j * 8192);
                    c[4] = 0;
                    if (r == 8 && lane < 16) c[4] = l2_touch(p + 4 * 8192);
                    sink = c[0] | c[1] | c[2] | c[3] | c[4];
                }
                if (sink == 0x9E3779B9u) asm volatile("st.volatile.shared.u32 [%0], %1;" ::"r"(prog + 4), "r"(sink) : "memory");
            }
        } else {
            const int hw = wid - 9;
            for (int k = 0; k < 4; k++) publish(hw, k);
        }
    } else {
        asm volatile("setmaxnreg.inc.sync.aligned.u32 232;");
        const int w = wid >> 2;
        const int t = tid & 127;
        int slot = 0, ph = 0;
        uint32_t qf[8][4];
        const uint32_t stash = smR + (1 + w) * 16384 + t * 16;
        {
            float acc[128];
            int pslot = 0;
            for (int s = 0; s < N_WQ; s++) {
                mbar_wait(bars + 8 * slot, ph);
                if (tid == 0 && s == 0) TS(20);
                if (tid == 0 && s == 5) TS(21);
                if (tid == 0 && s == 10) TS(22);
                const uint64_t da = mk_desc(smR + ((s >> 1) & 7) * 8192 + (s & 1) * 64, 16, 1024);
                const uint64_t db = mk_desc(smS + slot * STAGE_BYTES + w * 16384, 4096, 1024);
                wg_fence();
                wgmma_ss_n256_tb(acc, da, db, s != 0);
                wgmma_ss_n256_tb(acc, da + 2, db + 128, 1);
                wg_commit();
                wg_wait<0>();
                if (lane == 0) mbar_arrive(bars + 8 * (NSTAGE + slot));
                pslot = slot;
                if (++slot == NSTAGE) { slot = 0; ph ^= 1; }
            }
            fence_regs(acc);
            if (tid == 0) TS(1);
#pragma unroll
            for (int kk = 0; kk < 8; kk++) {
#pragma unroll
                for (int i = 0; i < 4; i++) qf[kk][i] = pack_bf16(acc[8 * kk + 2 * i], acc[8 * kk + 2 * i + 1]);
                sts128(stash + kk * 2048,
                       pack_bf16(acc[64 + 8 * kk + 0], acc[64 + 8 * kk + 1]), pack_bf16(acc[64 + 8 * kk + 2], acc[64 + 8 * kk + 3]),
                       pack_bf16(acc[64 + 8 * kk + 4], acc[64 + 8 * kk + 5]), pack_bf16(acc[64 + 8 * kk + 6], acc[64 + 8 * kk + 7]));
            }
        }
        if (w == 1) bar_arrive<5, 256>();
        const float sc = 0.08838834764831845f * 1.4426950408889634f;
#pragma unroll
        for (int u = 0; u < 2; u++) {
            uint32_t af[16][4];
            {
                float o[64], s[64];
                float m0 = -INFINITY, m1 = -INFINITY, l0 = 0.f, l1 = 0.f;
                uint32_t pf[8][4];
#pragma unroll
                for (int i = 0; i < 64; i++) { o[i] = 0.f; s[i] = 0.f; }
#pragma unroll
                for (int i = 0; i < 32; i++) pf[i >> 2][i & 3] = 0u;
#pragma unroll 1
                for (int tt = 0; tt <= 4; tt++) {
                    int vslot = slot;
                    if (tt > 0) {
                        mbar_wait(bars + 8 * slot, ph);
                        if (++slot == NSTAGE) { slot = 0; ph ^= 1; }
                    }
                    if (tt < 4) mbar_wait(bars + 8 * slot, ph);
                    if (tid == 0) TS(32 + u * 20 + tt * 4);
                    if (w == 0) bar_sync<5, 256>(); else bar_sync<6, 256>();
                    wg_fence();
                    if (tt > 0) {
                        const uint64_t db = mk_desc(smS + vslot * STAGE_BYTES, 16384, 1024);
#pragma unroll
                        for (int kk = 0; kk < 8; kk++)
                            wgmma_rs_n128_tb(o, pf[kk][0], pf[kk][1], pf[kk][2], pf[kk][3], db + kk * 128, (tt > 1) || (kk != 0));
                        wg_commit();
                    }
                    if (tt < 4) {
                        const uint64_t db = mk_desc(smS + slot * STAGE_BYTES, 16, 1024);
#pragma unroll
                        for (int kk = 0; kk < 8; kk++)
                            wgmma_rs_n128(s, qf[kk][0], qf[kk][1], qf[kk][2], qf[kk][3], db + (kk >> 2) * 1024 + (kk & 3) * 2, kk != 0);
                        wg_commit();
                    }
                    if (w == 0) bar_arrive<6, 256>(); else if (!(u == 1 && tt == 4)) bar_arrive<5, 256>();
                    if (tid == 0) TS(32 + u * 20 + tt * 4 + 1);
                    wg_wait<0>();
                    fence_regs(o);
                    fence_regs(s);
                    if (tid == 0) TS(32 + u * 20 + tt * 4 + 2);
                    if (tt > 0 && lane == 0) mbar_arrive(bars + 8 * (NSTAGE + vslot));
                    if (tt == 4) break;
                    if (lane == 0) mbar_arrive(bars + 8 * (NSTAGE + slot));
                    if (++slot == NSTAGE) { slot = 0; ph ^= 1; }
                    float mx0 = s[0], mx1 = s[2];
#pragma unroll
                    for (int j = 0; j < 16; j++) {
                        mx0 = fmaxf(mx0, fmaxf(s[4 * j], s[4 * j + 1]));
                        mx1 = fmaxf(mx1, fmaxf(s[4 * j + 2], s[4 * j + 3]));
                    }
                    mx0 = fmaxf(mx0, __shfl_xor_sync(0xffffffffu, mx0, 1));
                    mx1 = fmaxf(mx1, __shfl_xor_sync(0xffffffffu, mx1, 1));
                    mx0 = fmaxf(mx0, __shfl_xor_sync(0xffffffffu, mx0, 2));
                    mx1 = fmaxf(mx1, __shfl_xor_sync(0xffffffffu, mx1, 2));
                    const float mn0 = fmaxf(m0, mx0), mn1 = fmaxf(m1, mx1);
                    const float al0 = ex2((m0 - mn0) * sc), al1 = ex2((m1 - mn1) * sc);
                    m0 = mn0; m1 = mn1;
                    const float ms0 = mn0 * sc, ms1 = mn1 * sc;
                    float rs0 = 0.f, rs1 = 0.f;
#pragma unroll
                    for (int j = 0; j < 16; j++) {
                        const float p0 = ex2(fmaf(s[4 * j], sc, -ms0)), p1 = ex2(fmaf(s[4 * j + 1], sc, -ms0));
                        const float p2 = ex2(fmaf(s[4 * j + 2], sc, -ms1)), p3 = ex2(fmaf(s[4 * j + 3], sc, -ms1));
                        rs0 += p0 + p1; rs1 += p2 + p3;
                        pf[j >> 1][(j & 1) * 2] = pack_bf16(p0, p1);
                        pf[j >> 1][(j & 1) * 2 + 1] = pack_bf16(p2, p3);
                    }
                    l0 = l0 * al0 + rs0; l1 = l1 * al1 + rs1;
                    if (tt > 0) {
#pragma unroll
                        for (int j = 0; j < 16; j++) { o[4 * j] *= al0; o[4 * j + 1] *= al0; o[4 * j + 2] *= al1; o[4 * j + 3] *= al1; }
                    }
                    if (tid == 0) TS(32 + u * 20 + tt * 4 + 3);
                }
                if (tid == 0) TS(2 + u);
                l0 += __shfl_xor_sync(0xffffffffu, l0, 1);
                l1 += __shfl_xor_sync(0xffffffffu, l1, 1);
                l0 += __shfl_xor_sync(0xffffffffu, l0, 2);
                l1 += __shfl_xor_sync(0xffffffffu, l1, 2);
                const float i0 = 1.f / l0, i1 = 1.f / l1;
                const uint32_t zown = smR + (w ? 3 : 0) * 16384 + t * 16;
#pragma unroll
                for (int kk = 0; kk < 8; kk++) {
                    af[kk][0] = pack_bf16(o[8 * kk + 0] * i0, o[8 * kk + 1] * i0);
                    af[kk][1] = pack_bf16(o[8 * kk + 2] * i1, o[8 * kk + 3] * i1);
                    af[kk][2] = pack_bf16(o[8 * kk + 4] * i0, o[8 * kk + 5] * i0);
                    af[kk][3] = pack_bf16(o[8 * kk + 6] * i1, o[8 * kk + 7] * i1);
                    if (u == 0) sts128(zown + kk * 2048, af[kk][0], af[kk][1], af[kk][2], af[kk][3]);
                    else __stcg(g_ox + (size_t)((grp * 16 + hp * 2 + w) * 8 + kk) * 128 + t, make_uint4(af[kk][0], af[kk][1], af[kk][2], af[kk][3]));
                }
            }
            if (u == 0) {
                if (w == 0) bar_arrive<7, 256>(); else bar_arrive<8, 256>();
#pragma unroll
                for (int kk = 0; kk < 8; kk++) lds128(stash + kk * 2048, qf[kk]);
#pragma unroll
                for (int ps = 0; ps < 2; ps++) {
                    float acc[64];
#pragma unroll
                    for (int i = 0; i < 64; i++) acc[i] = 0.f;
#pragma unroll
                    for (int st = 0; st < 4; st++) {
                        if (ps == 0 && st == 2) {
                            if (w == 0) bar_sync<8, 256>(); else bar_sync<7, 256>();
#pragma unroll
                            for (int kk = 0; kk < 8; kk++) lds128(smR + (w ? 0 : 3) * 16384 + kk * 2048 + t * 16, af[8 + kk]);
                        }
                        mbar_wait(bars + 8 * slot, ph);
                        const uint64_t db = mk_desc(smS + slot * STAGE_BYTES + w * 16384, 8192, 1024);
                        wg_fence();
#pragma unroll
                        for (int kk = 0; kk < 4; kk++)
                            wgmma_rs_n128_tb(acc, af[st * 4 + kk][0], af[st * 4 + kk][1], af[st * 4 + kk][2], af[st * 4 + kk][3], db + kk * 128, 1);
                        wg_commit();
                        wg_wait<0>();
                        if (lane == 0) mbar_arrive(bars + 8 * (NSTAGE + slot));
                        if (++slot == NSTAGE) { slot = 0; ph ^= 1; }
                    }
                    fence_regs(acc);
                    uint4* dst = g_p1 + (size_t)((grp * 8 + 4 * ps + 2 * w) * 8 + hp) * 512 + t;
#pragma unroll
                    for (int j = 0; j < 8; j++)
                        __stcg(dst + (j >> 2) * 4096 + (j & 3) * 128,
                               make_uint4(pack_bf16(acc[8 * j], acc[8 * j + 1]), pack_bf16(acc[8 * j + 2], acc[8 * j + 3]),
                                          pack_bf16(acc[8 * j + 4], acc[8 * j + 5]), pack_bf16(acc[8 * j + 6], acc[8 * j + 7])));
                    __syncwarp();
                    if (lane == 0) mbar_arrive(bars + 8 * (2 * NSTAGE + w * 5 + ps));
                    if (tid == 0) TS(4 + ps);
                }
            } else {
                __syncwarp();
                if (lane == 0) mbar_arrive(bars + 8 * (2 * NSTAGE + w * 5 + 2));
            }
            {
                float acc[32];
                if (u == 0) {
#pragma unroll
                    for (int i = 0; i < 32; i++) acc[i] = 0.f;
                } else {
#pragma unroll
                    for (int j = 0; j < 4; j++) {
                        uint32_t r[4];
                        lds128(stash + j * 2048, r);
#pragma unroll
                        for (int i = 0; i < 4; i++) { acc[8 * j + 2 * i] = __uint_as_float(r[i] << 16); acc[8 * j + 2 * i + 1] = __uint_as_float(r[i] & 0xffff0000u); }
                    }
                }
                mbar_wait(bars + 8 * slot, ph);
                const uint64_t db = mk_desc(smS + slot * STAGE_BYTES + w * 16384, 8192, 1024);
                wg_fence();
#pragma unroll
                for (int kk = 0; kk < 8; kk++)
                    wgmma_rs_n64_tb(acc, af[kk][0], af[kk][1], af[kk][2], af[kk][3], db + kk * 128, 1);
                wg_commit();
                wg_wait<0>();
                if (lane == 0) mbar_arrive(bars + 8 * (NSTAGE + slot));
                if (++slot == NSTAGE) { slot = 0; ph ^= 1; }
                fence_regs(acc);
                if (u == 0) {
#pragma unroll
                    for (int j = 0; j < 4; j++)
                        sts128(stash + j * 2048, pack_bf16(acc[8 * j], acc[8 * j + 1]), pack_bf16(acc[8 * j + 2], acc[8 * j + 3]),
                               pack_bf16(acc[8 * j + 4], acc[8 * j + 5]), pack_bf16(acc[8 * j + 6], acc[8 * j + 7]));
                } else {
                    uint2* dst8 = g_p8 + (size_t)(grp * 16 + hp * 2 + w) * 1024 + t;
#pragma unroll
                    for (int j = 0; j < 8; j++)
                        __stcg(dst8 + j * 128, make_uint2(pack_bf16(acc[4 * j], acc[4 * j + 1]), pack_bf16(acc[4 * j + 2], acc[4 * j + 3])));
                    __syncwarp();
                    if (lane == 0) mbar_arrive(bars + 8 * (2 * NSTAGE + w * 5 + 3));
                }
                if (tid == 0) TS(6 + u * 8);
            }
            if (u == 1) {
                float acc[32];
                {
                    wait_count(&g_c1[(grp * 8 + hp) * 8 + w * 4 + (wid & 3)], 4u, lane);
                    const uint4* src = g_p1 + (size_t)((grp * 8 + hp) * 8 + 4 * w) * 512 + t;
                    uint4 v[16];
#pragma unroll
                    for (int i = 0; i < 16; i++) v[i] = __ldcg(src + i * 128);
#pragma unroll
                    for (int i = 0; i < 32; i++) acc[i] = 0.f;
#pragma unroll
                    for (int i = 0; i < 16; i++) {
                        const int j = i & 3;
                        acc[8 * j + 0] += __uint_as_float(v[i].x << 16); acc[8 * j + 1] += __uint_as_float(v[i].x & 0xffff0000u);
                        acc[8 * j + 2] += __uint_as_float(v[i].y << 16); acc[8 * j + 3] += __uint_as_float(v[i].y & 0xffff0000u);
                        acc[8 * j + 4] += __uint_as_float(v[i].z << 16); acc[8 * j + 5] += __uint_as_float(v[i].z & 0xffff0000u);
                        acc[8 * j + 6] += __uint_as_float(v[i].w << 16); acc[8 * j + 7] += __uint_as_float(v[i].w & 0xffff0000u);
                    }
                }
                if (tid == 0) TS(12);
                uint4 fr[3][8];
                auto fetch = [&](int i, uint4 (&f)[8]) {
                    const int j = (hp + i) & 7;
                    wait_count(&g_co[(grp * 16 + j * 2 + w) * 32 + hp * 4 + (wid & 3)], 1u, lane);
                    const uint4* src = g_ox + (size_t)(grp * 16 + j * 2 + w) * 1024 + t;
#pragma unroll
                    for (int kk = 0; kk < 8; kk++) f[kk] = __ldcg(src + kk * 128);
                };
#pragma unroll
                for (int kk = 0; kk < 8; kk++) fr[0][kk] = make_uint4(af[kk][0], af[kk][1], af[kk][2], af[kk][3]);
#pragma unroll
                for (int i = 0; i < 8; i++) {
                    mbar_wait(bars + 8 * slot, ph);
                    const uint64_t db = mk_desc(smS + slot * STAGE_BYTES + w * 16384, 8192, 1024);
                    wg_fence();
#pragma unroll
                    for (int kk = 0; kk < 8; kk++)
                        wgmma_rs_n64_tb(acc, fr[i % 3][kk].x, fr[i % 3][kk].y, fr[i % 3][kk].z, fr[i % 3][kk].w, db + kk * 128, 1);
                    wg_commit();
                    if (i == 0) fetch(1, fr[1]);
                    if (i + 2 < 8) fetch(i + 2, fr[(i + 2) % 3]);
                    wg_wait<0>();
                    if (lane == 0) mbar_arrive(bars + 8 * (NSTAGE + slot));
                    if (++slot == NSTAGE) { slot = 0; ph ^= 1; }
                    if (tid == 0) TS(80 + i);
                }
                fence_regs(acc);
                wait_count(&g_co[(grp * 16 + hp * 2 + w) * 32 + hp * 4 + (wid & 3)], 1u, lane);
                if (tid == 0) TS(13);
                const uint32_t xo = smR + w * 16384 + t * 16;
                const uint32_t xi = smR + (w ^ 1) * 16384 + t * 16;
#pragma unroll
                for (int j = 0; j < 4; j++) {
                    const float x0 = w ? acc[4 * j] : acc[16 + 4 * j], x1 = w ? acc[4 * j + 1] : acc[16 + 4 * j + 1];
                    const float x2 = w ? acc[4 * j + 2] : acc[16 + 4 * j + 2], x3 = w ? acc[4 * j + 3] : acc[16 + 4 * j + 3];
                    sts128(xo + j * 2048, __float_as_uint(x0), __float_as_uint(x1), __float_as_uint(x2), __float_as_uint(x3));
                }
                bar_sync<4, 256>();
                __nv_bfloat16* orow = P.out + (size_t)(b * 64 + (t >> 5) * 16 + (lane >> 2)) * (2 * kD) + blk * kD + (lane & 3) * 2;
#pragma unroll
                for (int j = 0; j < 4; j++) {
                    uint32_t r[4];
                    lds128(xi + j * 2048, r);
                    const float y0 = w ? acc[16 + 4 * j] : acc[4 * j], y1 = w ? acc[16 + 4 * j + 1] : acc[4 * j + 1];
                    const float y2 = w ? acc[16 + 4 * j + 2] : acc[4 * j + 2], y3 = w ? acc[16 + 4 * j + 3] : acc[4 * j + 3];
                    *(uint32_t*)(orow + hp * 64 + (w * 4 + j) * 8) = pack_bf16(y0 + __uint_as_float(r[0]), y1 + __uint_as_float(r[1]));
                    *(uint32_t*)(orow + hp * 64 + (w * 4 + j) * 8 + 8 * 2 * kD) = pack_bf16(y2 + __uint_as_float(r[2]), y3 + __uint_as_float(r[3]));
                }
                if (w == 1) {
                    wait_count(&g_c8[grp * 32 + hp * 4 + (wid & 3)], 16u, lane);
                    const uint2* src8 = g_p8 + ((size_t)grp * 16 * 8 + hp) * 128 + t;
                    uint2 u8[16];
#pragma unroll
                    for (int i = 0; i < 16; i++) u8[i] = __ldcg(src8 + (size_t)i * 1024);
                    float a0 = 0.f, a1 = 0.f, a2 = 0.f, a3 = 0.f;
#pragma unroll
                    for (int i = 0; i < 16; i++) {
                        const uint2 x = u8[i];
                        a0 += __uint_as_float(x.x << 16); a1 += __uint_as_float(x.x & 0xffff0000u);
                        a2 += __uint_as_float(x.y << 16); a3 += __uint_as_float(x.y & 0xffff0000u);
                    }
                    *(uint32_t*)(orow + 512 + hp * 8) = pack_bf16(a0, a1);
                    *(uint32_t*)(orow + 512 + hp * 8 + 8 * 2 * kD) = pack_bf16(a2, a3);
                }
                if (tid == 0 || tid == 128) TS(18 + w);
            }
        }
    }
}

typedef CUresult (*EncodeFn)(CUtensorMap*, CUtensorMapDataType, cuuint32_t, void*, const cuuint64_t*, const cuuint64_t*,
                             const cuuint32_t*, const cuuint32_t*, CUtensorMapInterleave, CUtensorMapSwizzle,
                             CUtensorMapL2promotion, CUtensorMapFloatOOBfill);

void make_map(EncodeFn fn, CUtensorMap* m, const void* ptr, uint64_t cols, uint64_t rows, uint32_t box_rows) {
    cuuint64_t dims[2] = {cols, rows};
    cuuint64_t strides[1] = {cols * 2};
    cuuint32_t box[2] = {64, box_rows};
    cuuint32_t es[2] = {1, 1};
    fn(m, CU_TENSOR_MAP_DATA_TYPE_BFLOAT16, 2, const_cast<void*>(ptr), dims, strides, box, es, CU_TENSOR_MAP_INTERLEAVE_NONE,
       CU_TENSOR_MAP_SWIZZLE_128B, L2PROMO, CU_TENSOR_MAP_FLOAT_OOB_FILL_NONE);
}

void make_map3(EncodeFn fn, CUtensorMap* m, const void* ptr, uint64_t cols, uint64_t rows, uint32_t box_rows, uint32_t box_groups) {
    cuuint64_t dims[3] = {64, rows, cols / 64};
    cuuint64_t strides[2] = {cols * 2, 128};
    cuuint32_t box[3] = {64, box_rows, box_groups};
    cuuint32_t es[3] = {1, 1, 1};
    fn(m, CU_TENSOR_MAP_DATA_TYPE_BFLOAT16, 3, const_cast<void*>(ptr), dims, strides, box, es, CU_TENSOR_MAP_INTERLEAVE_NONE,
       CU_TENSOR_MAP_SWIZZLE_128B, L2PROMO, CU_TENSOR_MAP_FLOAT_OOB_FILL_NONE);
}

}

extern "C" void kernel_launch(void* const* d_in, const int* in_sizes, int n_in, void* d_out, int out_size) {
    static EncodeFn enc = nullptr;
    if (!enc) {
        void* fn = nullptr;
        cudaDriverEntryPointQueryResult st;
        cudaGetDriverEntryPoint("cuTensorMapEncodeTiled", &fn, cudaEnableDefault, &st);
        enc = (EncodeFn)fn;
        cudaFuncSetAttribute(fused_gqa_kernel, cudaFuncAttributeMaxDynamicSharedMemorySize, SMEM_BYTES);
    }
    Params P;
    for (int blk = 0; blk < 2; blk++) {
        const void* x = d_in[blk * 5 + 0];
        const void* k = d_in[blk * 5 + 1];
        const void* v = d_in[blk * 5 + 2];
        const void* wq = d_in[blk * 5 + 3];
        const void* wo = d_in[blk * 5 + 4];
        make_map(enc, &P.x[blk], x, kD, kB * kSq, 64);
        make_map3(enc, &P.wq[blk], wq, kHq * kDh, kD, 32, 2);
        make_map3(enc, &P.k[blk], k, kDh, (uint64_t)kB * kHkv * kSk, 128, 2);
        make_map3(enc, &P.v[blk], v, kDh, (uint64_t)kB * kHkv * kSk, 128, 2);
        make_map3(enc, &P.wo[blk], wo, kD, kHq * kDh, 64, 2);
        make_map(enc, &P.wo8[blk], wo, kD, kHq * kDh, 128);
        P.wqp[blk] = (const __nv_bfloat16*)wq;
        P.kp[blk] = (const __nv_bfloat16*)k;
        P.vp[blk] = (const __nv_bfloat16*)v;
        P.wop[blk] = (const __nv_bfloat16*)wo;
    }
    P.out = (__nv_bfloat16*)d_out;
    fused_gqa_kernel<<<128, 384, SMEM_BYTES>>>(P);
}
```

```cpp
#include <cuda_runtime.h>
#include <cuda_bf16.h>
#include <cuda.h>
#include <stdint.h>

namespace {

constexpr int kB = 8, kSq = 64, kD = 576, kHq = 32, kHkv = 16, kSk = 512, kDh = 128;
constexpr int NSTAGE = 5;
constexpr int STAGE_BYTES = 32768;
constexpr int R_BYTES = 65536;
constexpr int SMEM_BYTES = R_BYTES + NSTAGE * STAGE_BYTES + 1024   + 256  ;
constexpr int N_WQ = 18;
#define PF_DIST_V 6
#define OP_WAIT0 1
#define QP_WAIT0 1
#define PF_POS1 9
#define PF_START 1
#define L2PROMO CU_TENSOR_MAP_L2_PROMOTION_L2_256B
#define PF_SPLIT 0
#define PF_SKIP 0
#define P1_TRIG 22
#define PF_EARLY 2
#define PF_WQ 0
#define PF_SLEEP 1000
constexpr int PF_DIST = PF_DIST_V;

struct __align__(64) Params {
    CUtensorMap x[2], wq[2], k[2], v[2], wo[2], wo8[2];
    const __nv_bfloat16* wqp[2];
    const __nv_bfloat16* kp[2];
    const __nv_bfloat16* vp[2];
    const __nv_bfloat16* wop[2];
    __nv_bfloat16* out;
};

__device__ uint4 g_p1[16 * 8 * 8 * 4 * 128];
__device__ uint4 g_ox[16 * 8 * 2 * 8 * 128];
__device__ uint2 g_p8[16 * 16 * 8 * 128];
__device__ unsigned int g_c1[16 * 8 * 8];
__device__ unsigned int g_co[16 * 16 * 32];
__device__ unsigned int g_c8[16 * 32];
#define TS(k) do {} while (0)

__device__ __forceinline__ uint32_t smem_u32(const void* p) { return (uint32_t)__cvta_generic_to_shared(p); }
__device__ __forceinline__ void mbar_init(uint32_t bar, int cnt) {
    asm volatile("mbarrier.init.shared::cta.b64 [%0], %1;" ::"r"(bar), "r"(cnt));
}
__device__ __forceinline__ void mbar_expect_tx(uint32_t bar, uint32_t bytes) {
    asm volatile("mbarrier.arrive.expect_tx.shared::cta.b64 _, [%0], %1;" ::"r"(bar), "r"(bytes) : "memory");
}
__device__ __forceinline__ void mbar_arrive(uint32_t bar) {
    asm volatile("mbarrier.arrive.shared::cta.b64 _, [%0];" ::"r"(bar) : "memory");
}
__device__ __forceinline__ bool mbar_try(uint32_t bar, uint32_t parity) {
    uint32_t ok;
    asm volatile("{\n.reg .pred p;\nmbarrier.try_wait.parity.shared::cta.b64 p, [%1], %2;\nselp.u32 %0, 1, 0, p;\n}\n"
                 : "=r"(ok) : "r"(bar), "r"(parity) : "memory");
    return ok != 0;
}
__device__ __forceinline__ void mbar_wait(uint32_t bar, uint32_t parity) {
    if (mbar_try(bar, parity)) return;
    uint32_t n = 0;
    while (!mbar_try(bar, parity)) {
        if (++n > (1u << 20)) break;
    }
}
__device__ __forceinline__ void tma_2d(uint32_t dst, const CUtensorMap* tm, int c0, int c1, uint32_t bar) {
    asm volatile("cp.async.bulk.tensor.2d.shared::cluster.global.mbarrier::complete_tx::bytes [%0], [%1, {%3, %4}], [%2];"
                 ::"r"(dst), "l"(tm), "r"(bar), "r"(c0), "r"(c1) : "memory");
}
__device__ __forceinline__ void tma_3d(uint32_t dst, const CUtensorMap* tm, int c0, int c1, int c2, uint32_t bar) {
    asm volatile("cp.async.bulk.tensor.3d.shared::cluster.global.mbarrier::complete_tx::bytes [%0], [%1, {%3, %4, %5}], [%2];"
                 ::"r"(dst), "l"(tm), "r"(bar), "r"(c0), "r"(c1), "r"(c2) : "memory");
}
__device__ __forceinline__ void l2_prefetch(const void* p, uint32_t bytes) {
    asm volatile("cp.async.bulk.prefetch.L2.global [%0], %1;" ::"l"(p), "r"(bytes) : "memory");
}
__device__ __forceinline__ uint32_t l2_touch(const void* p) {
    uint32_t v;
    asm volatile("ld.global.L2::256B.b32 %0, [%1];" : "=r"(v) : "l"(p) : "memory");
    return v;
}
__device__ __forceinline__ void wg_fence() { asm volatile("wgmma.fence.sync.aligned;" ::: "memory"); }
__device__ __forceinline__ void wg_commit() { asm volatile("wgmma.commit_group.sync.aligned;" ::: "memory"); }
template <int N> __device__ __forceinline__ void wg_wait() { asm volatile("wgmma.wait_group.sync.aligned %0;" ::"n"(N) : "memory"); }
template <int N> __device__ __forceinline__ void fence_regs(float (&d)[N]) {
#pragma unroll
    for (int i = 0; i < N; i++) asm volatile("" : "+f"(d[i])::"memory");
}
__device__ __forceinline__ uint64_t mk_desc(uint32_t addr, uint32_t lbo, uint32_t sbo) {
    return (uint64_t)((addr & 0x3FFFF) >> 4) | ((uint64_t)(lbo >> 4) << 16) | ((uint64_t)(sbo >> 4) << 32) | (1ull << 62);
}
__device__ __forceinline__ uint32_t pack_bf16(float a, float b) {
    uint32_t r;
    asm("cvt.rn.bf16x2.f32 %0, %1, %2;" : "=r"(r) : "f"(b), "f"(a));
    return r;
}
__device__ __forceinline__ float ex2(float x) {
    float y;
    asm("ex2.approx.ftz.f32 %0, %1;" : "=f"(y) : "f"(x));
    return y;
}
template <int ID, int N> __device__ __forceinline__ void bar_sync() { asm volatile("bar.sync %0, %1;" ::"n"(ID), "n"(N) : "memory"); }
template <int ID, int N> __device__ __forceinline__ void bar_arrive() { asm volatile("bar.arrive %0, %1;" ::"n"(ID), "n"(N) : "memory"); }
__device__ __forceinline__ void sts128(uint32_t addr, uint32_t a, uint32_t b, uint32_t c, uint32_t d) {
    asm volatile("st.shared.v4.b32 [%0], {%1,%2,%3,%4};" ::"r"(addr), "r"(a), "r"(b), "r"(c), "r"(d) : "memory");
}
__device__ __forceinline__ void bulk_store(void* dst, uint32_t src, uint32_t bytes) {
    asm volatile("cp.async.bulk.global.shared::cta.bulk_group [%0], [%1], %2;" ::"l"(dst), "r"(src), "r"(bytes) : "memory");
}
__device__ __forceinline__ void lds128(uint32_t addr, uint32_t (&r)[4]) {
    asm volatile("ld.shared.v4.b32 {%0,%1,%2,%3}, [%4];" : "=r"(r[0]), "=r"(r[1]), "=r"(r[2]), "=r"(r[3]) : "r"(addr) : "memory");
}

__device__ __forceinline__ void wait_count(unsigned* cp, unsigned need, int lane) {
    if (lane == 0) {
        unsigned v, n = 0;
        while (true) {
            asm volatile("ld.acquire.gpu.global.u32 %0, [%1];" : "=r"(v) : "l"(cp) : "memory");
            if (v >= need) break;
            if (++n > (1u << 21)) break;
        }
        *cp = 0;
    }
    __syncwarp();
}

__device__ __forceinline__ void wgmma_ss_n256_tb(float (&d)[128], uint64_t da, uint64_t db, int sd) {
    asm volatile("{\n.reg .pred p;\nsetp.ne.b32 p, %130, 0;\n"
        "wgmma.mma_async.sync.aligned.m64n256k16.f32.bf16.bf16 "
        "{%0, %1, %2, %3, %4, %5, %6, %7, %8, %9, %10, %11, %12, %13, %14, %15, %16, %17, %18, %19, %20, %21, %22, %23, %24, %25, %26, %27, %28, %29, %30, %31, %32, %33, %34, %35, %36, %37, %38, %39, %40, %41, %42, %43, %44, %45, %46, %47, %48, %49, %50, %51, %52, %53, %54, %55, %56, %57, %58, %59, %60, %61, %62, %63, %64, %65, %66, %67, %68, %69, %70, %71, %72, %73, %74, %75, %76, %77, %78, %79, %80, %81, %82, %83, %84, %85, %86, %87, %88, %89, %90, %91, %92, %93, %94, %95, %96, %97, %98, %99, %100, %101, %102, %103, %104, %105, %106, %107, %108, %109, %110, %111, %112, %113, %114, %115, %116, %117, %118, %119, %120, %121, %122, %123, %124, %125, %126, %127}, "
        "%128, %129, p, 1, 1, 0, 1;\n}\n"
        : "+f"(d[0]), "+f"(d[1]), "+f"(d[2]), "+f"(d[3]), "+f"(d[4]), "+f"(d[5]), "+f"(d[6]), "+f"(d[7]), "+f"(d[8]), "+f"(d[9]), "+f"(d[10]), "+f"(d[11]), "+f"(d[12]), "+f"(d[13]), "+f"(d[14]), "+f"(d[15]), "+f"(d[16]), "+f"(d[17]), "+f"(d[18]), "+f"(d[19]), "+f"(d[20]), "+f"(d[21]), "+f"(d[22]), "+f"(d[23]), "+f"(d[24]), "+f"(d[25]), "+f"(d[26]), "+f"(d[27]), "+f"(d[28]), "+f"(d[29]), "+f"(d[30]), "+f"(d[31]), "+f"(d[32]), "+f"(d[33]), "+f"(d[34]), "+f"(d[35]), "+f"(d[36]), "+f"(d[37]), "+f"(d[38]), "+f"(d[39]), "+f"(d[40]), "+f"(d[41]), "+f"(d[42]), "+f"(d[43]), "+f"(d[44]), "+f"(d[45]), "+f"(d[46]), "+f"(d[47]), "+f"(d[48]), "+f"(d[49]), "+f"(d[50]), "+f"(d[51]), "+f"(d[52]), "+f"(d[53]), "+f"(d[54]), "+f"(d[55]), "+f"(d[56]), "+f"(d[57]), "+f"(d[58]), "+f"(d[59]), "+f"(d[60]), "+f"(d[61]), "+f"(d[62]), "+f"(d[63]), "+f"(d[64]), "+f"(d[65]), "+f"(d[66]), "+f"(d[67]), "+f"(d[68]), "+f"(d[69]), "+f"(d[70]), "+f"(d[71]), "+f"(d[72]), "+f"(d[73]), "+f"(d[74]), "+f"(d[75]), "+f"(d[76]), "+f"(d[77]), "+f"(d[78]), "+f"(d[79]), "+f"(d[80]), "+f"(d[81]), "+f"(d[82]), "+f"(d[83]), "+f"(d[84]), "+f"(d[85]), "+f"(d[86]), "+f"(d[87]), "+f"(d[88]), "+f"(d[89]), "+f"(d[90]), "+f"(d[91]), "+f"(d[92]), "+f"(d[93]), "+f"(d[94]), "+f"(d[95]), "+f"(d[96]), "+f"(d[97]), "+f"(d[98]), "+f"(d[99]), "+f"(d[100]), "+f"(d[101]), "+f"(d[102]), "+f"(d[103]), "+f"(d[104]), "+f"(d[105]), "+f"(d[106]), "+f"(d[107]), "+f"(d[108]), "+f"(d[109]), "+f"(d[110]), "+f"(d[111]), "+f"(d[112]), "+f"(d[113]), "+f"(d[114]), "+f"(d[115]), "+f"(d[116]), "+f"(d[117]), "+f"(d[118]), "+f"(d[119]), "+f"(d[120]), "+f"(d[121]), "+f"(d[122]), "+f"(d[123]), "+f"(d[124]), "+f"(d[125]), "+f"(d[126]), "+f"(d[127])
        : "l"(da), "l"(db), "r"(sd));
}
__device__ __forceinline__ void wgmma_rs_n128(float (&d)[64], uint32_t a0, uint32_t a1, uint32_t a2, uint32_t a3, uint64_t db, int sd) {
    asm volatile("{\n.reg .pred p;\nsetp.ne.b32 p, %69, 0;\n"
        "wgmma.mma_async.sync.aligned.m64n128k16.f32.bf16.bf16 "
        "{%0, %1, %2, %3, %4, %5, %6, %7, %8, %9, %10, %11, %12, %13, %14, %15, %16, %17, %18, %19, %20, %21, %22, %23, %24, %25, %26, %27, %28, %29, %30, %31, %32, %33, %34, %35, %36, %37, %38, %39, %40, %41, %42, %43, %44, %45, %46, %47, %48, %49, %50, %51, %52, %53, %54, %55, %56, %57, %58, %59, %60, %61, %62, %63}, "
        "{%64, %65, %66, %67}, %68, p, 1, 1, 0;\n}\n"
        : "+f"(d[0]), "+f"(d[1]), "+f"(d[2]), "+f"(d[3]), "+f"(d[4]), "+f"(d[5]), "+f"(d[6]), "+f"(d[7]), "+f"(d[8]), "+f"(d[9]), "+f"(d[10]), "+f"(d[11]), "+f"(d[12]), "+f"(d[13]), "+f"(d[14]), "+f"(d[15]), "+f"(d[16]), "+f"(d[17]), "+f"(d[18]), "+f"(d[19]), "+f"(d[20]), "+f"(d[21]), "+f"(d[22]), "+f"(d[23]), "+f"(d[24]), "+f"(d[25]), "+f"(d[26]), "+f"(d[27]), "+f"(d[28]), "+f"(d[29]), "+f"(d[30]), "+f"(d[31]), "+f"(d[32]), "+f"(d[33]), "+f"(d[34]), "+f"(d[35]), "+f"(d[36]), "+f"(d[37]), "+f"(d[38]), "+f"(d[39]), "+f"(d[40]), "+f"(d[41]), "+f"(d[42]), "+f"(d[43]), "+f"(d[44]), "+f"(d[45]), "+f"(d[46]), "+f"(d[47]), "+f"(d[48]), "+f"(d[49]), "+f"(d[50]), "+f"(d[51]), "+f"(d[52]), "+f"(d[53]), "+f"(d[54]), "+f"(d[55]), "+f"(d[56]), "+f"(d[57]), "+f"(d[58]), "+f"(d[59]), "+f"(d[60]), "+f"(d[61]), "+f"(d[62]), "+f"(d[63])
        : "r"(a0), "r"(a1), "r"(a2), "r"(a3), "l"(db), "r"(sd));
}
__device__ __forceinline__ void wgmma_rs_n128_tb(float (&d)[64], uint32_t a0, uint32_t a1, uint32_t a2, uint32_t a3, uint64_t db, int sd) {
    asm volatile("{\n.reg .pred p;\nsetp.ne.b32 p, %69, 0;\n"
        "wgmma.mma_async.sync.aligned.m64n128k16.f32.bf16.bf16 "
        "{%0, %1, %2, %3, %4, %5, %6, %7, %8, %9, %10, %11, %12, %13, %14, %15, %16, %17, %18, %19, %20, %21, %22, %23, %24, %25, %26, %27, %28, %29, %30, %31, %32, %33, %34, %35, %36, %37, %38, %39, %40, %41, %42, %43, %44, %45, %46, %47, %48, %49, %50, %51, %52, %53, %54, %55, %56, %57, %58, %59, %60, %61, %62, %63}, "
        "{%64, %65, %66, %67}, %68, p, 1, 1, 1;\n}\n"
        : "+f"(d[0]), "+f"(d[1]), "+f"(d[2]), "+f"(d[3]), "+f"(d[4]), "+f"(d[5]), "+f"(d[6]), "+f"(d[7]), "+f"(d[8]), "+f"(d[9]), "+f"(d[10]), "+f"(d[11]), "+f"(d[12]), "+f"(d[13]), "+f"(d[14]), "+f"(d[15]), "+f"(d[16]), "+f"(d[17]), "+f"(d[18]), "+f"(d[19]), "+f"(d[20]), "+f"(d[21]), "+f"(d[22]), "+f"(d[23]), "+f"(d[24]), "+f"(d[25]), "+f"(d[26]), "+f"(d[27]), "+f"(d[28]), "+f"(d[29]), "+f"(d[30]), "+f"(d[31]), "+f"(d[32]), "+f"(d[33]), "+f"(d[34]), "+f"(d[35]), "+f"(d[36]), "+f"(d[37]), "+f"(d[38]), "+f"(d[39]), "+f"(d[40]), "+f"(d[41]), "+f"(d[42]), "+f"(d[43]), "+f"(d[44]), "+f"(d[45]), "+f"(d[46]), "+f"(d[47]), "+f"(d[48]), "+f"(d[49]), "+f"(d[50]), "+f"(d[51]), "+f"(d[52]), "+f"(d[53]), "+f"(d[54]), "+f"(d[55]), "+f"(d[56]), "+f"(d[57]), "+f"(d[58]), "+f"(d[59]), "+f"(d[60]), "+f"(d[61]), "+f"(d[62]), "+f"(d[63])
        : "r"(a0), "r"(a1), "r"(a2), "r"(a3), "l"(db), "r"(sd));
}
__device__ __forceinline__ void wgmma_rs_n64_tb(float (&d)[32], uint32_t a0, uint32_t a1, uint32_t a2, uint32_t a3, uint64_t db, int sd) {
    asm volatile("{\n.reg .pred p;\nsetp.ne.b32 p, %37, 0;\n"
        "wgmma.mma_async.sync.aligned.m64n64k16.f32.bf16.bf16 "
        "{%0, %1, %2, %3, %4, %5, %6, %7, %8, %9, %10, %11, %12, %13, %14, %15, %16, %17, %18, %19, %20, %21, %22, %23, %24, %25, %26, %27, %28, %29, %30, %31}, "
        "{%32, %33, %34, %35}, %36, p, 1, 1, 1;\n}\n"
        : "+f"(d[0]), "+f"(d[1]), "+f"(d[2]), "+f"(d[3]), "+f"(d[4]), "+f"(d[5]), "+f"(d[6]), "+f"(d[7]), "+f"(d[8]), "+f"(d[9]), "+f"(d[10]), "+f"(d[11]), "+f"(d[12]), "+f"(d[13]), "+f"(d[14]), "+f"(d[15]), "+f"(d[16]), "+f"(d[17]), "+f"(d[18]), "+f"(d[19]), "+f"(d[20]), "+f"(d[21]), "+f"(d[22]), "+f"(d[23]), "+f"(d[24]), "+f"(d[25]), "+f"(d[26]), "+f"(d[27]), "+f"(d[28]), "+f"(d[29]), "+f"(d[30]), "+f"(d[31])
        : "r"(a0), "r"(a1), "r"(a2), "r"(a3), "l"(db), "r"(sd));
}

__global__ void __launch_bounds__(384, 1) fused_gqa_kernel(const __grid_constant__ Params P) {
    extern __shared__ uint8_t smem_raw[];
    const uint32_t base = (smem_u32(smem_raw) + 1023u) & ~1023u;
    const uint32_t smR = base;
    const uint32_t smS = base + R_BYTES;
    const uint32_t bars = smS + NSTAGE * STAGE_BYTES;
    const uint32_t prog = bars + 8 * (2 * NSTAGE + 10);
    const int tid = threadIdx.x;
    const int wid = __shfl_sync(0xffffffffu, tid >> 5, 0);
    const int lane = tid & 31;

    const int cta = blockIdx.x;
    const int blk = cta >> 6;
    const int hp = (cta >> 3) & 7;
    const int b = cta & 7;
    const int grp = blk * 8 + b;

    if (tid == 256) {
        TS(0);
        asm volatile("prefetch.tensormap [%0];" ::"l"(&P.x[blk]) : "memory");
        asm volatile("prefetch.tensormap [%0];" ::"l"(&P.wq[blk]) : "memory");
        for (int i = 0; i < NSTAGE; i++) {
            mbar_init(bars + 8 * i, 1);
            mbar_init(bars + 8 * (NSTAGE + i), 8);
        }
        for (int i = 0; i < 10; i++) mbar_init(bars + 8 * (2 * NSTAGE + i), 4);
        asm volatile("st.volatile.shared.u32 [%0], %1;" ::"r"(prog), "r"(0) : "memory");
        asm volatile("fence.mbarrier_init.release.cluster;" ::: "memory");
        asm volatile("fence.proxy.async.shared::cta;" ::: "memory");
#pragma unroll
        for (int s = 0; s < NSTAGE; s++) {
            const uint32_t fb = bars + 8 * s;
            const uint32_t dst = smS + s * STAGE_BYTES;
            mbar_expect_tx(fb, (s & 1) ? STAGE_BYTES : STAGE_BYTES + 8192);
            if (!(s & 1)) tma_2d(smR + (s >> 1) * 8192, &P.x[blk], (s >> 1) * 64, b * 64, fb);
#pragma unroll
            for (int p = 0; p < 4; p++) tma_3d(dst + p * 8192, &P.wq[blk], 0, s * 32, hp * 8 + (p & 1) * 4 + (p >> 1) * 2, fb);
        }
        asm volatile("prefetch.tensormap [%0];" ::"l"(&P.k[blk]) : "memory");
        asm volatile("prefetch.tensormap [%0];" ::"l"(&P.v[blk]) : "memory");
        asm volatile("prefetch.tensormap [%0];" ::"l"(&P.wo[blk]) : "memory");
        asm volatile("prefetch.tensormap [%0];" ::"l"(&P.wo8[blk]) : "memory");
    }
    __syncthreads();

    if (wid >= 8) {
        asm volatile("setmaxnreg.dec.sync.aligned.u32 40;");
        auto publish = [&](int hw, int k) {
            mbar_wait(bars + 8 * (2 * NSTAGE + hw * 5 + k), 0);
            unsigned* cp = (k == 2) ? &g_co[(grp * 16 + hp * 2 + hw) * 32 + lane] : &g_c8[grp * 32 + lane];
            asm volatile("fence.acq_rel.gpu;" ::: "memory");
            asm volatile("red.relaxed.gpu.global.add.u32 [%0], 1;" ::"l"(cp) : "memory");
        };
        if (wid == 8) {
            if (lane == 0) {
                int slot = 0, ph = 0;
                for (int s = NSTAGE; s < N_WQ; s++) {
                    const uint32_t fb = bars + 8 * slot;
                    mbar_wait(bars + 8 * (NSTAGE + slot), ph);
                    const uint32_t dst = smS + slot * STAGE_BYTES;
                    mbar_expect_tx(fb, (s & 1) ? STAGE_BYTES : STAGE_BYTES + 8192);
                    if (!(s & 1)) tma_2d(smR + ((s >> 1) & 7) * 8192, &P.x[blk], (s >> 1) * 64, b * 64, fb);
#pragma unroll
                    for (int p = 0; p < 4; p++) {
                        const int w = p >> 1, j = p & 1;
                        tma_3d(dst + p * 8192, &P.wq[blk], 0, s * 32, hp * 8 + j * 4 + w * 2, fb);
                    }
                    if (++slot == NSTAGE) { slot = 0; ph ^= 1; }
                }
                int lim = NSTAGE;
                for (int i = 0; i < 34; i++) {
                    const int u = (i >= 17), r = i - 17 * u;
                    const bool extra = (i == 27) || (i == 28);
                    const int sl = extra ? (i - 24) : slot;
                    const uint32_t fb = bars + 8 * sl;
                    mbar_wait(bars + 8 * (NSTAGE + sl), extra ? 1 : ph);
                    const uint32_t dst = smS + sl * STAGE_BYTES;
                    mbar_expect_tx(fb, STAGE_BYTES);
                    const int q = r - 8;
                    if (r < 8) {
                        const int row = (b * kHkv + hp * 2 + u) * kSk + (r >> 1) * 128;
                        tma_3d(dst, (r & 1) ? &P.v[blk] : &P.k[blk], 0, row, 0, fb);
                    } else if (u == 0 && q < 8) {
                        tma_3d(dst, &P.wo[blk], 0, hp * 512 + (q & 3) * 64, (q >> 2) * 4, fb);
                        tma_3d(dst + 16384, &P.wo[blk], 0, hp * 512 + ((q & 3) ^ 2) * 64, (q >> 2) * 4 + 2, fb);
                    } else if (u == 0 || q == 0) {
                        tma_2d(dst, &P.wo8[blk], 512, hp * 512 + u * 256, fb);
                        tma_2d(dst + 16384, &P.wo8[blk], 512, hp * 512 + u * 256 + 128, fb);
                    } else {
                        const int j = (hp + q - 1) & 7;
                        tma_2d(dst, &P.wo8[blk], hp * 64, j * 512 + 256, fb);
                        tma_2d(dst + 16384, &P.wo8[blk], hp * 64, j * 512 + 384, fb);
                    }
                    asm volatile("st.volatile.shared.u32 [%0], %1;" ::"r"(prog), "r"(i + 1) : "memory");
                    if (i == 7) lim = 3;
                    if (!extra && ++slot == lim) { slot = 0; ph ^= 1; }
                }
            }
        } else if (wid == 11) {
            if (PF_DIST > 0) {
                uint32_t sink = 0;
                mbar_wait(bars, 0);
                if (PF_WQ) {
                    const char* wqs = (const char*)(P.wqp[blk] + hp * 512) + (size_t)(160 + b * 52) * 8192;
#pragma unroll
                    for (int h = 0; h < 2; h++) {
#pragma unroll
                        for (int j = 0; j < 4; j++) {
                            const int e = (h * 4 + j) * 32 + lane;
                            if (e < 208) sink |= l2_touch(wqs + (size_t)(e >> 2) * 8192 + (e & 3) * 256);
                        }
                        if (sink == 0x9E3779B9u) asm volatile("st.volatile.shared.u32 [%0], %1;" ::"r"(prog + 4), "r"(sink) : "memory");
                    }
                }
                const char* kbase = (const char*)(P.kp[blk] + (size_t)(b * kHkv + hp * 2) * kSk * kDh);
                const char* vbase = (const char*)(P.vp[blk] + (size_t)(b * kHkv + hp * 2) * kSk * kDh);
                const char* wos = (const char*)(P.wop[blk] + (size_t)hp * 512 * kD) + (size_t)b * 36864;
                for (int i = 0; i < 18; i++) {
                    const int u = (i >= 9), r = i - 9 * u;
                    const int pos = u ? (PF_POS1 + r) : r;
                    if (pos >= PF_DIST) {
                        uint32_t pr, n = 0;
                        while (true) {
                            asm volatile("ld.volatile.shared.u32 %0, [%1];" : "=r"(pr) : "r"(prog) : "memory");
                            const int prk = ((int)pr <= 8) ? (int)pr : (((int)pr <= 17) ? 8 + (((int)pr - 8) * (PF_POS1 - 8)) / 9 : (int)pr - 17 + PF_POS1);
                            if (prk + PF_DIST >= pos) break;
                            if (++n > (1u << 22)) break;
                            __nanosleep(100);
                        }
                    }
                    const char* p = (r < 8) ? (((r & 1) ? vbase : kbase) + (size_t)(u * 4 + (r >> 1)) * 32768 + lane * 256) : (wos + (size_t)u * 294912 + lane * 256);
                    uint32_t c[5];
                    if (sink == 0x9E3779B9u) asm volatile("st.volatile.shared.u32 [%0], %1;" ::"r"(prog + 4), "r"(sink) : "memory");
#pragma unroll
                    for (int j = 0; j < 4; j++) c[j] = l2_touch(p + j * 8192);
                    c[4] = 0;
                    if (r == 8 && lane < 16) c[4] = l2_touch(p + 4 * 8192);
                    sink = c[0] | c[1] | c[2] | c[3] | c[4];
                }
                if (sink == 0x9E3779B9u) asm volatile("st.volatile.shared.u32 [%0], %1;" ::"r"(prog + 4), "r"(sink) : "memory");
            }
        } else {
            const int hw = wid - 9;
            mbar_wait(bars + 8 * (2 * NSTAGE + hw * 5 + 1), 0);
            if (lane == 0) {
                uint32_t pr, n = 0;
                while (true) {
                    asm volatile("ld.volatile.shared.u32 %0, [%1];" : "=r"(pr) : "r"(prog) : "memory");
                    if (pr >= P1_TRIG) break;
                    if (++n > (1u << 22)) break;
                    __nanosleep(200);
                }
#pragma unroll
                for (int c = 0; c < 4; c++)
                    bulk_store(g_p1 + (size_t)((grp * 8 + 4 * (c >> 1) + 2 * hw + (c & 1)) * 8 + hp) * 512,
                               smS + (3 + (c >> 1)) * STAGE_BYTES + hw * 16384 + (c & 1) * 8192, 8192);
                asm volatile("cp.async.bulk.commit_group;" ::: "memory");
                asm volatile("cp.async.bulk.wait_group 0;" ::: "memory");
#pragma unroll
                for (int x = 0; x < 4; x++) { mbar_arrive(bars + 8 * (NSTAGE + 3)); mbar_arrive(bars + 8 * (NSTAGE + 4)); }
                asm volatile("fence.acq_rel.gpu;" ::: "memory");
            }
            __syncwarp();
            if (lane < 16)
                asm volatile("red.relaxed.gpu.global.add.u32 [%0], 1;"
                             ::"l"(&g_c1[(grp * 8 + 4 * (lane >> 3) + 2 * hw + ((lane >> 2) & 1)) * 8 + (hp >> 2) * 4 + (lane & 3)]) : "memory");
            publish(hw, 2);
            publish(hw, 3);
        }
    } else {
        asm volatile("setmaxnreg.inc.sync.aligned.u32 232;");
        const int w = wid >> 2;
        const int t = tid & 127;
        int slot = 0, ph = 0, lim = NSTAGE;
        uint32_t qf[8][4];
        const uint32_t stash = smR + (1 + w) * 16384 + t * 16;
        {
            float acc[128];
            int pslot = 0;
            for (int s = 0; s < N_WQ; s++) {
                mbar_wait(bars + 8 * slot, ph);
                if (tid == 0 && s == 0) TS(20);
                if (tid == 0 && s == 5) TS(21);
                if (tid == 0 && s == 10) TS(22);
                const uint64_t da = mk_desc(smR + ((s >> 1) & 7) * 8192 + (s & 1) * 64, 16, 1024);
                const uint64_t db = mk_desc(smS + slot * STAGE_BYTES + w * 16384, 4096, 1024);
                wg_fence();
                wgmma_ss_n256_tb(acc, da, db, s != 0);
                wgmma_ss_n256_tb(acc, da + 2, db + 128, 1);
                wg_commit();
                wg_wait<0>();
                if (lane == 0) mbar_arrive(bars + 8 * (NSTAGE + slot));
                pslot = slot;
                if (++slot == NSTAGE) { slot = 0; ph ^= 1; }
            }
            fence_regs(acc);
            if (tid == 0) TS(1);
#pragma unroll
            for (int kk = 0; kk < 8; kk++) {
#pragma unroll
                for (int i = 0; i < 4; i++) qf[kk][i] = pack_bf16(acc[8 * kk + 2 * i], acc[8 * kk + 2 * i + 1]);
                sts128(stash + kk * 2048,
                       pack_bf16(acc[64 + 8 * kk + 0], acc[64 + 8 * kk + 1]), pack_bf16(acc[64 + 8 * kk + 2], acc[64 + 8 * kk + 3]),
                       pack_bf16(acc[64 + 8 * kk + 4], acc[64 + 8 * kk + 5]), pack_bf16(acc[64 + 8 * kk + 6], acc[64 + 8 * kk + 7]));
            }
        }
        if (w == 1) bar_arrive<5, 256>();
        const float sc = 0.08838834764831845f * 1.4426950408889634f;
#pragma unroll
        for (int u = 0; u < 2; u++) {
            uint32_t af[16][4];
            {
                float o[64], s[64];
                float m0 = -INFINITY, m1 = -INFINITY, l0 = 0.f, l1 = 0.f;
                uint32_t pf[8][4];
#pragma unroll
                for (int i = 0; i < 64; i++) { o[i] = 0.f; s[i] = 0.f; }
#pragma unroll
                for (int i = 0; i < 32; i++) pf[i >> 2][i & 3] = 0u;
#pragma unroll 1
                for (int tt = 0; tt <= 4; tt++) {
                    int vslot = slot;
                    if (tt > 0) {
                        mbar_wait(bars + 8 * slot, ph);
                        if (++slot == lim) { slot = 0; ph ^= 1; }
                    }
                    if (tt < 4) mbar_wait(bars + 8 * slot, ph);
                    if (tid == 0) TS(32 + u * 20 + tt * 4);
                    if (w == 0) bar_sync<5, 256>(); else bar_sync<6, 256>();
                    wg_fence();
                    if (tt > 0) {
                        const uint64_t db = mk_desc(smS + vslot * STAGE_BYTES, 16384, 1024);
#pragma unroll
                        for (int kk = 0; kk < 8; kk++)
                            wgmma_rs_n128_tb(o, pf[kk][0], pf[kk][1], pf[kk][2], pf[kk][3], db + kk * 128, (tt > 1) || (kk != 0));
                        wg_commit();
                    }
                    if (tt < 4) {
                        const uint64_t db = mk_desc(smS + slot * STAGE_BYTES, 16, 1024);
#pragma unroll
                        for (int kk = 0; kk < 8; kk++)
                            wgmma_rs_n128(s, qf[kk][0], qf[kk][1], qf[kk][2], qf[kk][3], db + (kk >> 2) * 1024 + (kk & 3) * 2, kk != 0);
                        wg_commit();
                    }
                    if (w == 0) bar_arrive<6, 256>(); else if (!(u == 1 && tt == 4)) bar_arrive<5, 256>();
                    if (tid == 0) TS(32 + u * 20 + tt * 4 + 1);
                    wg_wait<0>();
                    fence_regs(o);
                    fence_regs(s);
                    if (tid == 0) TS(32 + u * 20 + tt * 4 + 2);
                    if (tt > 0 && lane == 0) mbar_arrive(bars + 8 * (NSTAGE + vslot));
                    if (tt == 4) break;
                    if (lane == 0) mbar_arrive(bars + 8 * (NSTAGE + slot));
                    if (++slot == lim) { slot = 0; ph ^= 1; }
                    float mx0 = s[0], mx1 = s[2];
#pragma unroll
                    for (int j = 0; j < 16; j++) {
                        mx0 = fmaxf(mx0, fmaxf(s[4 * j], s[4 * j + 1]));
                        mx1 = fmaxf(mx1, fmaxf(s[4 * j + 2], s[4 * j + 3]));
                    }
                    mx0 = fmaxf(mx0, __shfl_xor_sync(0xffffffffu, mx0, 1));
                    mx1 = fmaxf(mx1, __shfl_xor_sync(0xffffffffu, mx1, 1));
                    mx0 = fmaxf(mx0, __shfl_xor_sync(0xffffffffu, mx0, 2));
                    mx1 = fmaxf(mx1, __shfl_xor_sync(0xffffffffu, mx1, 2));
                    const float mn0 = fmaxf(m0, mx0), mn1 = fmaxf(m1, mx1);
                    const float al0 = ex2((m0 - mn0) * sc), al1 = ex2((m1 - mn1) * sc);
                    m0 = mn0; m1 = mn1;
                    const float ms0 = mn0 * sc, ms1 = mn1 * sc;
                    float rs0 = 0.f, rs1 = 0.f;
#pragma unroll
                    for (int j = 0; j < 16; j++) {
                        const float p0 = ex2(fmaf(s[4 * j], sc, -ms0)), p1 = ex2(fmaf(s[4 * j + 1], sc, -ms0));
                        const float p2 = ex2(fmaf(s[4 * j + 2], sc, -ms1)), p3 = ex2(fmaf(s[4 * j + 3], sc, -ms1));
                        rs0 += p0 + p1; rs1 += p2 + p3;
                        pf[j >> 1][(j & 1) * 2] = pack_bf16(p0, p1);
                        pf[j >> 1][(j & 1) * 2 + 1] = pack_bf16(p2, p3);
                    }
                    l0 = l0 * al0 + rs0; l1 = l1 * al1 + rs1;
                    if (tt > 0) {
#pragma unroll
                        for (int j = 0; j < 16; j++) { o[4 * j] *= al0; o[4 * j + 1] *= al0; o[4 * j + 2] *= al1; o[4 * j + 3] *= al1; }
                    }
                    if (tid == 0) TS(32 + u * 20 + tt * 4 + 3);
                }
                if (tid == 0) TS(2 + u);
                l0 += __shfl_xor_sync(0xffffffffu, l0, 1);
                l1 += __shfl_xor_sync(0xffffffffu, l1, 1);
                l0 += __shfl_xor_sync(0xffffffffu, l0, 2);
                l1 += __shfl_xor_sync(0xffffffffu, l1, 2);
                const float i0 = 1.f / l0, i1 = 1.f / l1;
                const uint32_t zown = smR + (w ? 3 : 0) * 16384 + t * 16;
#pragma unroll
                for (int kk = 0; kk < 8; kk++) {
                    af[kk][0] = pack_bf16(o[8 * kk + 0] * i0, o[8 * kk + 1] * i0);
                    af[kk][1] = pack_bf16(o[8 * kk + 2] * i1, o[8 * kk + 3] * i1);
                    af[kk][2] = pack_bf16(o[8 * kk + 4] * i0, o[8 * kk + 5] * i0);
                    af[kk][3] = pack_bf16(o[8 * kk + 6] * i1, o[8 * kk + 7] * i1);
                    if (u == 0) sts128(zown + kk * 2048, af[kk][0], af[kk][1], af[kk][2], af[kk][3]);
                    else __stcg(g_ox + (size_t)((grp * 16 + hp * 2 + w) * 8 + kk) * 128 + t, make_uint4(af[kk][0], af[kk][1], af[kk][2], af[kk][3]));
                }
            }
            if (u == 0) {
                if (w == 0) bar_arrive<7, 256>(); else bar_arrive<8, 256>();
                lim = 3;
#pragma unroll
                for (int kk = 0; kk < 8; kk++) lds128(stash + kk * 2048, qf[kk]);
#pragma unroll
                for (int ps = 0; ps < 2; ps++) {
                    float acc[64];
#pragma unroll
                    for (int i = 0; i < 64; i++) acc[i] = 0.f;
#pragma unroll
                    for (int st = 0; st < 4; st++) {
                        if (ps == 0 && st == 2) {
                            if (w == 0) bar_sync<8, 256>(); else bar_sync<7, 256>();
#pragma unroll
                            for (int kk = 0; kk < 8; kk++) lds128(smR + (w ? 0 : 3) * 16384 + kk * 2048 + t * 16, af[8 + kk]);
                        }
                        mbar_wait(bars + 8 * slot, ph);
                        const uint64_t db = mk_desc(smS + slot * STAGE_BYTES + w * 16384, 8192, 1024);
                        wg_fence();
#pragma unroll
                        for (int kk = 0; kk < 4; kk++)
                            wgmma_rs_n128_tb(acc, af[st * 4 + kk][0], af[st * 4 + kk][1], af[st * 4 + kk][2], af[st * 4 + kk][3], db + kk * 128, 1);
                        wg_commit();
                        wg_wait<0>();
                        if (lane == 0) mbar_arrive(bars + 8 * (NSTAGE + slot));
                        if (++slot == lim) { slot = 0; ph ^= 1; }
                    }
                    fence_regs(acc);
                    const uint32_t keep = smS + (3 + ps) * STAGE_BYTES + w * 16384 + t * 16;
#pragma unroll
                    for (int j = 0; j < 8; j++)
                        sts128(keep + j * 2048, pack_bf16(acc[8 * j], acc[8 * j + 1]), pack_bf16(acc[8 * j + 2], acc[8 * j + 3]),
                               pack_bf16(acc[8 * j + 4], acc[8 * j + 5]), pack_bf16(acc[8 * j + 6], acc[8 * j + 7]));
                    if (ps == 1) {
                        asm volatile("fence.proxy.async.shared::cta;" ::: "memory");
                        __syncwarp();
                        if (lane == 0) mbar_arrive(bars + 8 * (2 * NSTAGE + w * 5 + 1));
                    }
                    if (tid == 0) TS(4 + ps);
                }
            } else {
                __syncwarp();
                if (lane == 0) mbar_arrive(bars + 8 * (2 * NSTAGE + w * 5 + 2));
            }
            {
                float acc[32];
                if (u == 0) {
#pragma unroll
                    for (int i = 0; i < 32; i++) acc[i] = 0.f;
                } else {
#pragma unroll
                    for (int j = 0; j < 4; j++) {
                        uint32_t r[4];
                        lds128(stash + j * 2048, r);
#pragma unroll
                        for (int i = 0; i < 4; i++) { acc[8 * j + 2 * i] = __uint_as_float(r[i] << 16); acc[8 * j + 2 * i + 1] = __uint_as_float(r[i] & 0xffff0000u); }
                    }
                }
                mbar_wait(bars + 8 * slot, ph);
                const uint64_t db = mk_desc(smS + slot * STAGE_BYTES + w * 16384, 8192, 1024);
                wg_fence();
#pragma unroll
                for (int kk = 0; kk < 8; kk++)
                    wgmma_rs_n64_tb(acc, af[kk][0], af[kk][1], af[kk][2], af[kk][3], db + kk * 128, 1);
                wg_commit();
                wg_wait<0>();
                if (lane == 0) mbar_arrive(bars + 8 * (NSTAGE + slot));
                if (++slot == lim) { slot = 0; ph ^= 1; }
                fence_regs(acc);
                if (u == 0) {
#pragma unroll
                    for (int j = 0; j < 4; j++)
                        sts128(stash + j * 2048, pack_bf16(acc[8 * j], acc[8 * j + 1]), pack_bf16(acc[8 * j + 2], acc[8 * j + 3]),
                               pack_bf16(acc[8 * j + 4], acc[8 * j + 5]), pack_bf16(acc[8 * j + 6], acc[8 * j + 7]));
                } else {
                    uint2* dst8 = g_p8 + (size_t)(grp * 16 + hp * 2 + w) * 1024 + t;
#pragma unroll
                    for (int j = 0; j < 8; j++)
                        __stcg(dst8 + j * 128, make_uint2(pack_bf16(acc[4 * j], acc[4 * j + 1]), pack_bf16(acc[4 * j + 2], acc[4 * j + 3])));
                    __syncwarp();
                    if (lane == 0) mbar_arrive(bars + 8 * (2 * NSTAGE + w * 5 + 3));
                }
                if (tid == 0) TS(6 + u * 8);
            }
            if (u == 1) {
                float acc[32];
                {
                    wait_count(&g_c1[(grp * 8 + hp) * 8 + w * 4 + (wid & 3)], 4u, lane);
                    const uint4* src = g_p1 + (size_t)((grp * 8 + hp) * 8 + 4 * w) * 512 + t;
                    uint4 v[16];
#pragma unroll
                    for (int i = 0; i < 16; i++) v[i] = __ldcg(src + i * 128);
#pragma unroll
                    for (int i = 0; i < 32; i++) acc[i] = 0.f;
#pragma unroll
                    for (int i = 0; i < 16; i++) {
                        const int j = i & 3;
                        acc[8 * j + 0] += __uint_as_float(v[i].x << 16); acc[8 * j + 1] += __uint_as_float(v[i].x & 0xffff0000u);
                        acc[8 * j + 2] += __uint_as_float(v[i].y << 16); acc[8 * j + 3] += __uint_as_float(v[i].y & 0xffff0000u);
                        acc[8 * j + 4] += __uint_as_float(v[i].z << 16); acc[8 * j + 5] += __uint_as_float(v[i].z & 0xffff0000u);
                        acc[8 * j + 6] += __uint_as_float(v[i].w << 16); acc[8 * j + 7] += __uint_as_float(v[i].w & 0xffff0000u);
                    }
                }
                if (tid == 0) TS(12);
                uint4 fr[5][8];
                unsigned* myflag = &g_co[(grp * 16 + ((hp + lane) & 7) * 2 + w) * 32 + hp * 4 + (wid & 3)];
                unsigned ready = 0;
                auto fetch = [&](int i, uint4 (&f)[8]) {
                    unsigned n = 0;
                    while (!((ready >> i) & 1)) {
                        unsigned v = 0;
                        if (lane < 8 && !((ready >> lane) & 1))
                            asm volatile("ld.acquire.gpu.global.u32 %0, [%1];" : "=r"(v) : "l"(myflag) : "memory");
                        ready |= __ballot_sync(0xffffffffu, v != 0);
                        if (++n > (1u << 21)) break;
                    }
                    const uint4* src = g_ox + (size_t)(grp * 16 + ((hp + i) & 7) * 2 + w) * 1024 + t;
#pragma unroll
                    for (int kk = 0; kk < 8; kk++) f[kk] = __ldcg(src + kk * 128);
                };
#pragma unroll
                for (int kk = 0; kk < 8; kk++) fr[0][kk] = make_uint4(af[kk][0], af[kk][1], af[kk][2], af[kk][3]);
#pragma unroll
                for (int i = 0; i < 8; i++) {
                    const bool extra = (i == 1) || (i == 2);
                    const int sl = extra ? (2 + i) : slot;
                    mbar_wait(bars + 8 * sl, extra ? 1 : ph);
                    const uint64_t db = mk_desc(smS + sl * STAGE_BYTES + w * 16384, 8192, 1024);
                    wg_fence();
#pragma unroll
                    for (int kk = 0; kk < 8; kk++)
                        wgmma_rs_n64_tb(acc, fr[i % 5][kk].x, fr[i % 5][kk].y, fr[i % 5][kk].z, fr[i % 5][kk].w, db + kk * 128, 1);
                    wg_commit();
                    if (i == 0) { fetch(1, fr[1]); fetch(2, fr[2]); fetch(3, fr[3]); }
                    if (i + 4 < 8) fetch(i + 4, fr[(i + 4) % 5]);
                    wg_wait<0>();
                    if (!extra) {
                        if (lane == 0) mbar_arrive(bars + 8 * (NSTAGE + slot));
                        if (++slot == lim) { slot = 0; ph ^= 1; }
                    }
                    if (tid == 0) TS(80 + i);
                }
                fence_regs(acc);
                {
                    unsigned n = 0;
                    while (!(ready & 1)) {
                        unsigned v = 0;
                        if (lane == 0) asm volatile("ld.acquire.gpu.global.u32 %0, [%1];" : "=r"(v) : "l"(myflag) : "memory");
                        ready |= __ballot_sync(0xffffffffu, v != 0);
                        if (++n > (1u << 21)) break;
                    }
                    if (lane < 8) *myflag = 0;
                }
                if (tid == 0) TS(13);
                const uint32_t xo = smR + w * 16384 + t * 16;
                const uint32_t xi = smR + (w ^ 1) * 16384 + t * 16;
#pragma unroll
                for (int j = 0; j < 4; j++) {
                    const float x0 = w ? acc[4 * j] : acc[16 + 4 * j], x1 = w ? acc[4 * j + 1] : acc[16 + 4 * j + 1];
                    const float x2 = w ? acc[4 * j + 2] : acc[16 + 4 * j + 2], x3 = w ? acc[4 * j + 3] : acc[16 + 4 * j + 3];
                    sts128(xo + j * 2048, __float_as_uint(x0), __float_as_uint(x1), __float_as_uint(x2), __float_as_uint(x3));
                }
                bar_sync<4, 256>();
                __nv_bfloat16* orow = P.out + (size_t)(b * 64 + (t >> 5) * 16 + (lane >> 2)) * (2 * kD) + blk * kD + (lane & 3) * 2;
#pragma unroll
                for (int j = 0; j < 4; j++) {
                    uint32_t r[4];
                    lds128(xi + j * 2048, r);
                    const float y0 = w ? acc[16 + 4 * j] : acc[4 * j], y1 = w ? acc[16 + 4 * j + 1] : acc[4 * j + 1];
                    const float y2 = w ? acc[16 + 4 * j + 2] : acc[4 * j + 2], y3 = w ? acc[16 + 4 * j + 3] : acc[4 * j + 3];
                    *(uint32_t*)(orow + hp * 64 + (w * 4 + j) * 8) = pack_bf16(y0 + __uint_as_float(r[0]), y1 + __uint_as_float(r[1]));
                    *(uint32_t*)(orow + hp * 64 + (w * 4 + j) * 8 + 8 * 2 * kD) = pack_bf16(y2 + __uint_as_float(r[2]), y3 + __uint_as_float(r[3]));
                }
                if (w == 1) {
                    wait_count(&g_c8[grp * 32 + hp * 4 + (wid & 3)], 16u, lane);
                    const uint2* src8 = g_p8 + ((size_t)grp * 16 * 8 + hp) * 128 + t;
                    uint2 u8[16];
#pragma unroll
                    for (int i = 0; i < 16; i++) u8[i] = __ldcg(src8 + (size_t)i * 1024);
                    float a0 = 0.f, a1 = 0.f, a2 = 0.f, a3 = 0.f;
#pragma unroll
                    for (int i = 0; i < 16; i++) {
                        const uint2 x = u8[i];
                        a0 += __uint_as_float(x.x << 16); a1 += __uint_as_float(x.x & 0xffff0000u);
                        a2 += __uint_as_float(x.y << 16); a3 += __uint_as_float(x.y & 0xffff0000u);
                    }
                    *(uint32_t*)(orow + 512 + hp * 8) = pack_bf16(a0, a1);
                    *(uint32_t*)(orow + 512 + hp * 8 + 8 * 2 * kD) = pack_bf16(a2, a3);
                }
                if (tid == 0 || tid == 128) TS(18 + w);
            }
        }
    }
}

typedef CUresult (*EncodeFn)(CUtensorMap*, CUtensorMapDataType, cuuint32_t, void*, const cuuint64_t*, const cuuint64_t*,
                             const cuuint32_t*, const cuuint32_t*, CUtensorMapInterleave, CUtensorMapSwizzle,
                             CUtensorMapL2promotion, CUtensorMapFloatOOBfill);

void make_map(EncodeFn fn, CUtensorMap* m, const void* ptr, uint64_t cols, uint64_t rows, uint32_t box_rows) {
    cuuint64_t dims[2] = {cols, rows};
    cuuint64_t strides[1] = {cols * 2};
    cuuint32_t box[2] = {64, box_rows};
    cuuint32_t es[2] = {1, 1};
    fn(m, CU_TENSOR_MAP_DATA_TYPE_BFLOAT16, 2, const_cast<void*>(ptr), dims, strides, box, es, CU_TENSOR_MAP_INTERLEAVE_NONE,
       CU_TENSOR_MAP_SWIZZLE_128B, L2PROMO, CU_TENSOR_MAP_FLOAT_OOB_FILL_NONE);
}

void make_map3(EncodeFn fn, CUtensorMap* m, const void* ptr, uint64_t cols, uint64_t rows, uint32_t box_rows, uint32_t box_groups) {
    cuuint64_t dims[3] = {64, rows, cols / 64};
    cuuint64_t strides[2] = {cols * 2, 128};
    cuuint32_t box[3] = {64, box_rows, box_groups};
    cuuint32_t es[3] = {1, 1, 1};
    fn(m, CU_TENSOR_MAP_DATA_TYPE_BFLOAT16, 3, const_cast<void*>(ptr), dims, strides, box, es, CU_TENSOR_MAP_INTERLEAVE_NONE,
       CU_TENSOR_MAP_SWIZZLE_128B, L2PROMO, CU_TENSOR_MAP_FLOAT_OOB_FILL_NONE);
}

}

extern "C" void kernel_launch(void* const* d_in, const int* in_sizes, int n_in, void* d_out, int out_size) {
    static EncodeFn enc = nullptr;
    if (!enc) {
        void* fn = nullptr;
        cudaDriverEntryPointQueryResult st;
        cudaGetDriverEntryPoint("cuTensorMapEncodeTiled", &fn, cudaEnableDefault, &st);
        enc = (EncodeFn)fn;
        cudaFuncSetAttribute(fused_gqa_kernel, cudaFuncAttributeMaxDynamicSharedMemorySize, SMEM_BYTES);
    }
    Params P;
    for (int blk = 0; blk < 2; blk++) {
        const void* x = d_in[blk * 5 + 0];
        const void* k = d_in[blk * 5 + 1];
        const void* v = d_in[blk * 5 + 2];
        const void* wq = d_in[blk * 5 + 3];
        const void* wo = d_in[blk * 5 + 4];
        make_map(enc, &P.x[blk], x, kD, kB * kSq, 64);
        make_map3(enc, &P.wq[blk], wq, kHq * kDh, kD, 32, 2);
        make_map3(enc, &P.k[blk], k, kDh, (uint64_t)kB * kHkv * kSk, 128, 2);
        make_map3(enc, &P.v[blk], v, kDh, (uint64_t)kB * kHkv * kSk, 128, 2);
        make_map3(enc, &P.wo[blk], wo, kD, kHq * kDh, 64, 2);
        make_map(enc, &P.wo8[blk], wo, kD, kHq * kDh, 128);
        P.wqp[blk] = (const __nv_bfloat16*)wq;
        P.kp[blk] = (const __nv_bfloat16*)k;
        P.vp[blk] = (const __nv_bfloat16*)v;
        P.wop[blk] = (const __nv_bfloat16*)wo;
    }
    P.out = (__nv_bfloat16*)d_out;
    fused_gqa_kernel<<<128, 384, SMEM_BYTES>>>(P);
}
```

```cpp
#include <cuda_runtime.h>
#include <cuda_bf16.h>
#include <cuda.h>
#include <stdint.h>

namespace {

constexpr int kB = 8, kSq = 64, kD = 576, kHq = 32, kHkv = 16, kSk = 512, kDh = 128;
constexpr int NSTAGE = 5;
constexpr int STAGE_BYTES = 32768;
constexpr int R_BYTES = 65536;
constexpr int SMEM_BYTES = R_BYTES + NSTAGE * STAGE_BYTES + 1024   + 256  ;
constexpr int N_WQ = 18;
#define PF_DIST_V 6
#define OP_WAIT0 1
#define QP_WAIT0 1
#define PF_POS1 9
#define PF_START 1
#define L2PROMO CU_TENSOR_MAP_L2_PROMOTION_L2_256B
#define PF_SPLIT 0
#define PF_SKIP 0
#define P1_TRIG 25
#define PF_EARLY 2
#define PF_WQ 0
#define PF_SLEEP 1000
constexpr int PF_DIST = PF_DIST_V;

struct __align__(64) Params {
    CUtensorMap x[2], wq[2], k[2], v[2], wo[2], wo8[2];
    const __nv_bfloat16* wqp[2];
    const __nv_bfloat16* kp[2];
    const __nv_bfloat16* vp[2];
    const __nv_bfloat16* wop[2];
    __nv_bfloat16* out;
};

__device__ uint4 g_p1[16 * 8 * 8 * 4 * 128];
__device__ uint4 g_ox[16 * 8 * 2 * 8 * 128];
__device__ uint2 g_p8[16 * 16 * 8 * 128];
__device__ unsigned int g_c1[16 * 8 * 8];
__device__ unsigned int g_co[16 * 16 * 32];
__device__ unsigned int g_c8[16 * 32];
#define TS(k) do {} while (0)

__device__ __forceinline__ uint32_t smem_u32(const void* p) { return (uint32_t)__cvta_generic_to_shared(p); }
__device__ __forceinline__ void mbar_init(uint32_t bar, int cnt) {
    asm volatile("mbarrier.init.shared::cta.b64 [%0], %1;" ::"r"(bar), "r"(cnt));
}
__device__ __forceinline__ void mbar_expect_tx(uint32_t bar, uint32_t bytes) {
    asm volatile("mbarrier.arrive.expect_tx.shared::cta.b64 _, [%0], %1;" ::"r"(bar), "r"(bytes) : "memory");
}
__device__ __forceinline__ void mbar_arrive(uint32_t bar) {
    asm volatile("mbarrier.arrive.shared::cta.b64 _, [%0];" ::"r"(bar) : "memory");
}
__device__ __forceinline__ bool mbar_try(uint32_t bar, uint32_t parity) {
    uint32_t ok;
    asm volatile("{\n.reg .pred p;\nmbarrier.try_wait.parity.shared::cta.b64 p, [%1], %2;\nselp.u32 %0, 1, 0, p;\n}\n"
                 : "=r"(ok) : "r"(bar), "r"(parity) : "memory");
    return ok != 0;
}
__device__ __forceinline__ void mbar_wait(uint32_t bar, uint32_t parity) {
    if (mbar_try(bar, parity)) return;
    uint32_t n = 0;
    while (!mbar_try(bar, parity)) {
        if (++n > (1u << 20)) break;
    }
}
__device__ __forceinline__ void tma_2d(uint32_t dst, const CUtensorMap* tm, int c0, int c1, uint32_t bar) {
    asm volatile("cp.async.bulk.tensor.2d.shared::cluster.global.mbarrier::complete_tx::bytes [%0], [%1, {%3, %4}], [%2];"
                 ::"r"(dst), "l"(tm), "r"(bar), "r"(c0), "r"(c1) : "memory");
}
__device__ __forceinline__ void tma_3d(uint32_t dst, const CUtensorMap* tm, int c0, int c1, int c2, uint32_t bar) {
    asm volatile("cp.async.bulk.tensor.3d.shared::cluster.global.mbarrier::complete_tx::bytes [%0], [%1, {%3, %4, %5}], [%2];"
                 ::"r"(dst), "l"(tm), "r"(bar), "r"(c0), "r"(c1), "r"(c2) : "memory");
}
__device__ __forceinline__ void l2_prefetch(const void* p, uint32_t bytes) {
    asm volatile("cp.async.bulk.prefetch.L2.global [%0], %1;" ::"l"(p), "r"(bytes) : "memory");
}
__device__ __forceinline__ uint32_t l2_touch(const void* p) {
    uint32_t v;
    asm volatile("ld.global.L2::256B.b32 %0, [%1];" : "=r"(v) : "l"(p) : "memory");
    return v;
}
__device__ __forceinline__ void wg_fence() { asm volatile("wgmma.fence.sync.aligned;" ::: "memory"); }
__device__ __forceinline__ void wg_commit() { asm volatile("wgmma.commit_group.sync.aligned;" ::: "memory"); }
template <int N> __device__ __forceinline__ void wg_wait() { asm volatile("wgmma.wait_group.sync.aligned %0;" ::"n"(N) : "memory"); }
template <int N> __device__ __forceinline__ void fence_regs(float (&d)[N]) {
#pragma unroll
    for (int i = 0; i < N; i++) asm volatile("" : "+f"(d[i])::"memory");
}
__device__ __forceinline__ uint64_t mk_desc(uint32_t addr, uint32_t lbo, uint32_t sbo) {
    return (uint64_t)((addr & 0x3FFFF) >> 4) | ((uint64_t)(lbo >> 4) << 16) | ((uint64_t)(sbo >> 4) << 32) | (1ull << 62);
}
__device__ __forceinline__ uint32_t pack_bf16(float a, float b) {
    uint32_t r;
    asm("cvt.rn.bf16x2.f32 %0, %1, %2;" : "=r"(r) : "f"(b), "f"(a));
    return r;
}
__device__ __forceinline__ float ex2(float x) {
    float y;
    asm("ex2.approx.ftz.f32 %0, %1;" : "=f"(y) : "f"(x));
    return y;
}
template <int ID, int N> __device__ __forceinline__ void bar_sync() { asm volatile("bar.sync %0, %1;" ::"n"(ID), "n"(N) : "memory"); }
template <int ID, int N> __device__ __forceinline__ void bar_arrive() { asm volatile("bar.arrive %0, %1;" ::"n"(ID), "n"(N) : "memory"); }
__device__ __forceinline__ void sts128(uint32_t addr, uint32_t a, uint32_t b, uint32_t c, uint32_t d) {
    asm volatile("st.shared.v4.b32 [%0], {%1,%2,%3,%4};" ::"r"(addr), "r"(a), "r"(b), "r"(c), "r"(d) : "memory");
}
__device__ __forceinline__ void bulk_store(void* dst, uint32_t src, uint32_t bytes) {
    asm volatile("cp.async.bulk.global.shared::cta.bulk_group [%0], [%1], %2;" ::"l"(dst), "r"(src), "r"(bytes) : "memory");
}
__device__ __forceinline__ void lds128(uint32_t addr, uint32_t (&r)[4]) {
    asm volatile("ld.shared.v4.b32 {%0,%1,%2,%3}, [%4];" : "=r"(r[0]), "=r"(r[1]), "=r"(r[2]), "=r"(r[3]) : "r"(addr) : "memory");
}

__device__ __forceinline__ void wait_count(unsigned* cp, unsigned need, int lane) {
    if (lane == 0) {
        unsigned v, n = 0;
        while (true) {
            asm volatile("ld.acquire.gpu.global.u32 %0, [%1];" : "=r"(v) : "l"(cp) : "memory");
            if (v >= need) break;
            if (++n > (1u << 21)) break;
        }
        *cp = 0;
    }
    __syncwarp();
}

__device__ __forceinline__ void wgmma_ss_n256_tb(float (&d)[128], uint64_t da, uint64_t db, int sd) {
    asm volatile("{\n.reg .pred p;\nsetp.ne.b32 p, %130, 0;\n"
        "wgmma.mma_async.sync.aligned.m64n256k16.f32.bf16.bf16 "
        "{%0, %1, %2, %3, %4, %5, %6, %7, %8, %9, %10, %11, %12, %13, %14, %15, %16, %17, %18, %19, %20, %21, %22, %23, %24, %25, %26, %27, %28, %29, %30, %31, %32, %33, %34, %35, %36, %37, %38, %39, %40, %41, %42, %43, %44, %45, %46, %47, %48, %49, %50, %51, %52, %53, %54, %55, %56, %57, %58, %59, %60, %61, %62, %63, %64, %65, %66, %67, %68, %69, %70, %71, %72, %73, %74, %75, %76, %77, %78, %79, %80, %81, %82, %83, %84, %85, %86, %87, %88, %89, %90, %91, %92, %93, %94, %95, %96, %97, %98, %99, %100, %101, %102, %103, %104, %105, %106, %107, %108, %109, %110, %111, %112, %113, %114, %115, %116, %117, %118, %119, %120, %121, %122, %123, %124, %125, %126, %127}, "
        "%128, %129, p, 1, 1, 0, 1;\n}\n"
        : "+f"(d[0]), "+f"(d[1]), "+f"(d[2]), "+f"(d[3]), "+f"(d[4]), "+f"(d[5]), "+f"(d[6]), "+f"(d[7]), "+f"(d[8]), "+f"(d[9]), "+f"(d[10]), "+f"(d[11]), "+f"(d[12]), "+f"(d[13]), "+f"(d[14]), "+f"(d[15]), "+f"(d[16]), "+f"(d[17]), "+f"(d[18]), "+f"(d[19]), "+f"(d[20]), "+f"(d[21]), "+f"(d[22]), "+f"(d[23]), "+f"(d[24]), "+f"(d[25]), "+f"(d[26]), "+f"(d[27]), "+f"(d[28]), "+f"(d[29]), "+f"(d[30]), "+f"(d[31]), "+f"(d[32]), "+f"(d[33]), "+f"(d[34]), "+f"(d[35]), "+f"(d[36]), "+f"(d[37]), "+f"(d[38]), "+f"(d[39]), "+f"(d[40]), "+f"(d[41]), "+f"(d[42]), "+f"(d[43]), "+f"(d[44]), "+f"(d[45]), "+f"(d[46]), "+f"(d[47]), "+f"(d[48]), "+f"(d[49]), "+f"(d[50]), "+f"(d[51]), "+f"(d[52]), "+f"(d[53]), "+f"(d[54]), "+f"(d[55]), "+f"(d[56]), "+f"(d[57]), "+f"(d[58]), "+f"(d[59]), "+f"(d[60]), "+f"(d[61]), "+f"(d[62]), "+f"(d[63]), "+f"(d[64]), "+f"(d[65]), "+f"(d[66]), "+f"(d[67]), "+f"(d[68]), "+f"(d[69]), "+f"(d[70]), "+f"(d[71]), "+f"(d[72]), "+f"(d[73]), "+f"(d[74]), "+f"(d[75]), "+f"(d[76]), "+f"(d[77]), "+f"(d[78]), "+f"(d[79]), "+f"(d[80]), "+f"(d[81]), "+f"(d[82]), "+f"(d[83]), "+f"(d[84]), "+f"(d[85]), "+f"(d[86]), "+f"(d[87]), "+f"(d[88]), "+f"(d[89]), "+f"(d[90]), "+f"(d[91]), "+f"(d[92]), "+f"(d[93]), "+f"(d[94]), "+f"(d[95]), "+f"(d[96]), "+f"(d[97]), "+f"(d[98]), "+f"(d[99]), "+f"(d[100]), "+f"(d[101]), "+f"(d[102]), "+f"(d[103]), "+f"(d[104]), "+f"(d[105]), "+f"(d[106]), "+f"(d[107]), "+f"(d[108]), "+f"(d[109]), "+f"(d[110]), "+f"(d[111]), "+f"(d[112]), "+f"(d[113]), "+f"(d[114]), "+f"(d[115]), "+f"(d[116]), "+f"(d[117]), "+f"(d[118]), "+f"(d[119]), "+f"(d[120]), "+f"(d[121]), "+f"(d[122]), "+f"(d[123]), "+f"(d[124]), "+f"(d[125]), "+f"(d[126]), "+f"(d[127])
        : "l"(da), "l"(db), "r"(sd));
}
__device__ __forceinline__ void wgmma_rs_n128(float (&d)[64], uint32_t a0, uint32_t a1, uint32_t a2, uint32_t a3, uint64_t db, int sd) {
    asm volatile("{\n.reg .pred p;\nsetp.ne.b32 p, %69, 0;\n"
        "wgmma.mma_async.sync.aligned.m64n128k16.f32.bf16.bf16 "
        "{%0, %1, %2, %3, %4, %5, %6, %7, %8, %9, %10, %11, %12, %13, %14, %15, %16, %17, %18, %19, %20, %21, %22, %23, %24, %25, %26, %27, %28, %29, %30, %31, %32, %33, %34, %35, %36, %37, %38, %39, %40, %41, %42, %43, %44, %45, %46, %47, %48, %49, %50, %51, %52, %53, %54, %55, %56, %57, %58, %59, %60, %61, %62, %63}, "
        "{%64, %65, %66, %67}, %68, p, 1, 1, 0;\n}\n"
        : "+f"(d[0]), "+f"(d[1]), "+f"(d[2]), "+f"(d[3]), "+f"(d[4]), "+f"(d[5]), "+f"(d[6]), "+f"(d[7]), "+f"(d[8]), "+f"(d[9]), "+f"(d[10]), "+f"(d[11]), "+f"(d[12]), "+f"(d[13]), "+f"(d[14]), "+f"(d[15]), "+f"(d[16]), "+f"(d[17]), "+f"(d[18]), "+f"(d[19]), "+f"(d[20]), "+f"(d[21]), "+f"(d[22]), "+f"(d[23]), "+f"(d[24]), "+f"(d[25]), "+f"(d[26]), "+f"(d[27]), "+f"(d[28]), "+f"(d[29]), "+f"(d[30]), "+f"(d[31]), "+f"(d[32]), "+f"(d[33]), "+f"(d[34]), "+f"(d[35]), "+f"(d[36]), "+f"(d[37]), "+f"(d[38]), "+f"(d[39]), "+f"(d[40]), "+f"(d[41]), "+f"(d[42]), "+f"(d[43]), "+f"(d[44]), "+f"(d[45]), "+f"(d[46]), "+f"(d[47]), "+f"(d[48]), "+f"(d[49]), "+f"(d[50]), "+f"(d[51]), "+f"(d[52]), "+f"(d[53]), "+f"(d[54]), "+f"(d[55]), "+f"(d[56]), "+f"(d[57]), "+f"(d[58]), "+f"(d[59]), "+f"(d[60]), "+f"(d[61]), "+f"(d[62]), "+f"(d[63])
        : "r"(a0), "r"(a1), "r"(a2), "r"(a3), "l"(db), "r"(sd));
}
__device__ __forceinline__ void wgmma_rs_n128_tb(float (&d)[64], uint32_t a0, uint32_t a1, uint32_t a2, uint32_t a3, uint64_t db, int sd) {
    asm volatile("{\n.reg .pred p;\nsetp.ne.b32 p, %69, 0;\n"
        "wgmma.mma_async.sync.aligned.m64n128k16.f32.bf16.bf16 "
        "{%0, %1, %2, %3, %4, %5, %6, %7, %8, %9, %10, %11, %12, %13, %14, %15, %16, %17, %18, %19, %20, %21, %22, %23, %24, %25, %26, %27, %28, %29, %30, %31, %32, %33, %34, %35, %36, %37, %38, %39, %40, %41, %42, %43, %44, %45, %46, %47, %48, %49, %50, %51, %52, %53, %54, %55, %56, %57, %58, %59, %60, %61, %62, %63}, "
        "{%64, %65, %66, %67}, %68, p, 1, 1, 1;\n}\n"
        : "+f"(d[0]), "+f"(d[1]), "+f"(d[2]), "+f"(d[3]), "+f"(d[4]), "+f"(d[5]), "+f"(d[6]), "+f"(d[7]), "+f"(d[8]), "+f"(d[9]), "+f"(d[10]), "+f"(d[11]), "+f"(d[12]), "+f"(d[13]), "+f"(d[14]), "+f"(d[15]), "+f"(d[16]), "+f"(d[17]), "+f"(d[18]), "+f"(d[19]), "+f"(d[20]), "+f"(d[21]), "+f"(d[22]), "+f"(d[23]), "+f"(d[24]), "+f"(d[25]), "+f"(d[26]), "+f"(d[27]), "+f"(d[28]), "+f"(d[29]), "+f"(d[30]), "+f"(d[31]), "+f"(d[32]), "+f"(d[33]), "+f"(d[34]), "+f"(d[35]), "+f"(d[36]), "+f"(d[37]), "+f"(d[38]), "+f"(d[39]), "+f"(d[40]), "+f"(d[41]), "+f"(d[42]), "+f"(d[43]), "+f"(d[44]), "+f"(d[45]), "+f"(d[46]), "+f"(d[47]), "+f"(d[48]), "+f"(d[49]), "+f"(d[50]), "+f"(d[51]), "+f"(d[52]), "+f"(d[53]), "+f"(d[54]), "+f"(d[55]), "+f"(d[56]), "+f"(d[57]), "+f"(d[58]), "+f"(d[59]), "+f"(d[60]), "+f"(d[61]), "+f"(d[62]), "+f"(d[63])
        : "r"(a0), "r"(a1), "r"(a2), "r"(a3), "l"(db), "r"(sd));
}
__device__ __forceinline__ void wgmma_rs_n64_tb(float (&d)[32], uint32_t a0, uint32_t a1, uint32_t a2, uint32_t a3, uint64_t db, int sd) {
    asm volatile("{\n.reg .pred p;\nsetp.ne.b32 p, %37, 0;\n"
        "wgmma.mma_async.sync.aligned.m64n64k16.f32.bf16.bf16 "
        "{%0, %1, %2, %3, %4, %5, %6, %7, %8, %9, %10, %11, %12, %13, %14, %15, %16, %17, %18, %19, %20, %21, %22, %23, %24, %25, %26, %27, %28, %29, %30, %31}, "
        "{%32, %33, %34, %35}, %36, p, 1, 1, 1;\n}\n"
        : "+f"(d[0]), "+f"(d[1]), "+f"(d[2]), "+f"(d[3]), "+f"(d[4]), "+f"(d[5]), "+f"(d[6]), "+f"(d[7]), "+f"(d[8]), "+f"(d[9]), "+f"(d[10]), "+f"(d[11]), "+f"(d[12]), "+f"(d[13]), "+f"(d[14]), "+f"(d[15]), "+f"(d[16]), "+f"(d[17]), "+f"(d[18]), "+f"(d[19]), "+f"(d[20]), "+f"(d[21]), "+f"(d[22]), "+f"(d[23]), "+f"(d[24]), "+f"(d[25]), "+f"(d[26]), "+f"(d[27]), "+f"(d[28]), "+f"(d[29]), "+f"(d[30]), "+f"(d[31])
        : "r"(a0), "r"(a1), "r"(a2), "r"(a3), "l"(db), "r"(sd));
}

__global__ void __launch_bounds__(384, 1) fused_gqa_kernel(const __grid_constant__ Params P) {
    extern __shared__ uint8_t smem_raw[];
    const uint32_t base = (smem_u32(smem_raw) + 1023u) & ~1023u;
    const uint32_t smR = base;
    const uint32_t smS = base + R_BYTES;
    const uint32_t bars = smS + NSTAGE * STAGE_BYTES;
    const uint32_t prog = bars + 8 * (2 * NSTAGE + 10);
    const int tid = threadIdx.x;
    const int wid = __shfl_sync(0xffffffffu, tid >> 5, 0);
    const int lane = tid & 31;

    const int cta = blockIdx.x;
    const int blk = cta >> 6;
    const int hp = (cta >> 3) & 7;
    const int b = cta & 7;
    const int grp = blk * 8 + b;

    if (tid == 256) {
        TS(0);
        asm volatile("prefetch.tensormap [%0];" ::"l"(&P.x[blk]) : "memory");
        asm volatile("prefetch.tensormap [%0];" ::"l"(&P.wq[blk]) : "memory");
        for (int i = 0; i < NSTAGE; i++) {
            mbar_init(bars + 8 * i, 1);
            mbar_init(bars + 8 * (NSTAGE + i), 8);
        }
        for (int i = 0; i < 10; i++) mbar_init(bars + 8 * (2 * NSTAGE + i), (i == 4) ? 1 : 4);
        asm volatile("st.volatile.shared.u32 [%0], %1;" ::"r"(prog), "r"(0) : "memory");
        asm volatile("fence.mbarrier_init.release.cluster;" ::: "memory");
        asm volatile("fence.proxy.async.shared::cta;" ::: "memory");
#pragma unroll
        for (int s = 0; s < NSTAGE; s++) {
            const uint32_t fb = bars + 8 * s;
            const uint32_t dst = smS + s * STAGE_BYTES;
            mbar_expect_tx(fb, (s & 1) ? STAGE_BYTES : STAGE_BYTES + 8192);
            if (!(s & 1)) tma_2d(smR + (s >> 1) * 8192, &P.x[blk], (s >> 1) * 64, b * 64, fb);
#pragma unroll
            for (int p = 0; p < 4; p++) tma_3d(dst + p * 8192, &P.wq[blk], 0, s * 32, hp * 8 + (p & 1) * 4 + (p >> 1) * 2, fb);
        }
        asm volatile("prefetch.tensormap [%0];" ::"l"(&P.k[blk]) : "memory");
        asm volatile("prefetch.tensormap [%0];" ::"l"(&P.v[blk]) : "memory");
        asm volatile("prefetch.tensormap [%0];" ::"l"(&P.wo[blk]) : "memory");
        asm volatile("prefetch.tensormap [%0];" ::"l"(&P.wo8[blk]) : "memory");
    }
    __syncthreads();

    if (wid >= 8) {
        asm volatile("setmaxnreg.dec.sync.aligned.u32 40;");
        auto publish = [&](int hw, int k) {
            mbar_wait(bars + 8 * (2 * NSTAGE + hw * 5 + k), 0);
            unsigned* cp = (k == 2) ? &g_co[(grp * 16 + hp * 2 + hw) * 32 + lane] : &g_c8[grp * 32 + lane];
            asm volatile("fence.acq_rel.gpu;" ::: "memory");
            asm volatile("red.relaxed.gpu.global.add.u32 [%0], 1;" ::"l"(cp) : "memory");
        };
        if (wid == 8) {
            if (lane == 0) {
                int slot = 0, ph = 0;
                for (int s = NSTAGE; s < N_WQ; s++) {
                    const uint32_t fb = bars + 8 * slot;
                    mbar_wait(bars + 8 * (NSTAGE + slot), ph);
                    const uint32_t dst = smS + slot * STAGE_BYTES;
                    mbar_expect_tx(fb, (s & 1) ? STAGE_BYTES : STAGE_BYTES + 8192);
                    if (!(s & 1)) tma_2d(smR + ((s >> 1) & 7) * 8192, &P.x[blk], (s >> 1) * 64, b * 64, fb);
#pragma unroll
                    for (int p = 0; p < 4; p++) {
                        const int w = p >> 1, j = p & 1;
                        tma_3d(dst + p * 8192, &P.wq[blk], 0, s * 32, hp * 8 + j * 4 + w * 2, fb);
                    }
                    if (++slot == NSTAGE) { slot = 0; ph ^= 1; }
                }
                int lim = NSTAGE;
                for (int i = 0; i < 34; i++) {
                    const int u = (i >= 17), r = i - 17 * u;
                    const bool zst = (i == 28), extra = (i >= 32) || zst;
                    const int sl = (i >= 32) ? (i - 29) : slot;
                    const uint32_t fb = zst ? (bars + 8 * (2 * NSTAGE + 4)) : (bars + 8 * sl);
                    if (!zst) mbar_wait(bars + 8 * (NSTAGE + sl), extra ? 1 : ph);
                    const uint32_t dst = zst ? smR : (smS + sl * STAGE_BYTES);
                    const uint32_t dst1 = zst ? (smR + 3 * 16384) : (dst + 16384);
                    mbar_expect_tx(fb, STAGE_BYTES);
                    const int q = r - 8;
                    if (r < 8) {
                        const int row = (b * kHkv + hp * 2 + u) * kSk + (r >> 1) * 128;
                        tma_3d(dst, (r & 1) ? &P.v[blk] : &P.k[blk], 0, row, 0, fb);
                    } else if (u == 0 && q < 8) {
                        tma_3d(dst, &P.wo[blk], 0, hp * 512 + (q & 3) * 64, (q >> 2) * 4, fb);
                        tma_3d(dst + 16384, &P.wo[blk], 0, hp * 512 + ((q & 3) ^ 2) * 64, (q >> 2) * 4 + 2, fb);
                    } else if (u == 0 || q == 0) {
                        tma_2d(dst, &P.wo8[blk], 512, hp * 512 + u * 256, fb);
                        tma_2d(dst + 16384, &P.wo8[blk], 512, hp * 512 + u * 256 + 128, fb);
                    } else {
                        const int j = (hp + q - 1) & 7;
                        tma_2d(dst, &P.wo8[blk], hp * 64, j * 512 + 256, fb);
                        tma_2d(dst1, &P.wo8[blk], hp * 64, j * 512 + 384, fb);
                    }
                    asm volatile("st.volatile.shared.u32 [%0], %1;" ::"r"(prog), "r"(i + 1) : "memory");
                    if (i == 7) lim = 3;
                    if (!extra && ++slot == lim) { slot = 0; ph ^= 1; }
                }
            }
        } else if (wid == 11) {
            if (PF_DIST > 0) {
                uint32_t sink = 0;
                mbar_wait(bars, 0);
                if (PF_WQ) {
                    const char* wqs = (const char*)(P.wqp[blk] + hp * 512) + (size_t)(160 + b * 52) * 8192;
#pragma unroll
                    for (int h = 0; h < 2; h++) {
#pragma unroll
                        for (int j = 0; j < 4; j++) {
                            const int e = (h * 4 + j) * 32 + lane;
                            if (e < 208) sink |= l2_touch(wqs + (size_t)(e >> 2) * 8192 + (e & 3) * 256);
                        }
                        if (sink == 0x9E3779B9u) asm volatile("st.volatile.shared.u32 [%0], %1;" ::"r"(prog + 4), "r"(sink) : "memory");
                    }
                }
                const char* kbase = (const char*)(P.kp[blk] + (size_t)(b * kHkv + hp * 2) * kSk * kDh);
                const char* vbase = (const char*)(P.vp[blk] + (size_t)(b * kHkv + hp * 2) * kSk * kDh);
                const char* wos = (const char*)(P.wop[blk] + (size_t)hp * 512 * kD) + (size_t)b * 36864;
                for (int i = 0; i < 18; i++) {
                    const int u = (i >= 9), r = i - 9 * u;
                    const int pos = u ? (PF_POS1 + r) : r;
                    if (pos >= PF_DIST) {
                        uint32_t pr, n = 0;
                        while (true) {
                            asm volatile("ld.volatile.shared.u32 %0, [%1];" : "=r"(pr) : "r"(prog) : "memory");
                            const int prk = ((int)pr <= 8) ? (int)pr : (((int)pr <= 17) ? 8 + (((int)pr - 8) * (PF_POS1 - 8)) / 9 : (int)pr - 17 + PF_POS1);
                            if (prk + PF_DIST >= pos) break;
                            if (++n > (1u << 22)) break;
                            __nanosleep(100);
                        }
                    }
                    const char* p = (r < 8) ? (((r & 1) ? vbase : kbase) + (size_t)(u * 4 + (r >> 1)) * 32768 + lane * 256) : (wos + (size_t)u * 294912 + lane * 256);
                    uint32_t c[5];
                    if (sink == 0x9E3779B9u) asm volatile("st.volatile.shared.u32 [%0], %1;" ::"r"(prog + 4), "r"(sink) : "memory");
#pragma unroll
                    for (int j = 0; j < 4; j++) c[j] = l2_touch(p + j * 8192);
                    c[4] = 0;
                    if (r == 8 && lane < 16) c[4] = l2_touch(p + 4 * 8192);
                    sink = c[0] | c[1] | c[2] | c[3] | c[4];
                }
                if (sink == 0x9E3779B9u) asm volatile("st.volatile.shared.u32 [%0], %1;" ::"r"(prog + 4), "r"(sink) : "memory");
            }
        } else {
            const int hw = wid - 9;
            mbar_wait(bars + 8 * (2 * NSTAGE + hw * 5 + 1), 0);
            if (lane == 0) {
                uint32_t pr, n = 0;
                while (true) {
                    asm volatile("ld.volatile.shared.u32 %0, [%1];" : "=r"(pr) : "r"(prog) : "memory");
                    if (pr >= P1_TRIG) break;
                    if (++n > (1u << 22)) break;
                    __nanosleep(200);
                }
#pragma unroll
                for (int c = 0; c < 4; c++)
                    bulk_store(g_p1 + (size_t)((grp * 8 + 4 * (c >> 1) + 2 * hw + (c & 1)) * 8 + hp) * 512,
                               smS + (3 + (c >> 1)) * STAGE_BYTES + hw * 16384 + (c & 1) * 8192, 8192);
                asm volatile("cp.async.bulk.commit_group;" ::: "memory");
                asm volatile("cp.async.bulk.wait_group 0;" ::: "memory");
#pragma unroll
                for (int x = 0; x < 4; x++) { mbar_arrive(bars + 8 * (NSTAGE + 3)); mbar_arrive(bars + 8 * (NSTAGE + 4)); }
                asm volatile("fence.acq_rel.gpu;" ::: "memory");
            }
            __syncwarp();
            if (lane < 16)
                asm volatile("red.relaxed.gpu.global.add.u32 [%0], 1;"
                             ::"l"(&g_c1[(grp * 8 + 4 * (lane >> 3) + 2 * hw + ((lane >> 2) & 1)) * 8 + (hp >> 2) * 4 + (lane & 3)]) : "memory");
            publish(hw, 2);
            publish(hw, 3);
        }
    } else {
        asm volatile("setmaxnreg.inc.sync.aligned.u32 232;");
        const int w = wid >> 2;
        const int t = tid & 127;
        int slot = 0, ph = 0, lim = NSTAGE;
        uint32_t qf[8][4];
        const uint32_t stash = smR + (1 + w) * 16384 + t * 16;
        {
            float acc[128];
            int pslot = 0;
            for (int s = 0; s < N_WQ; s++) {
                mbar_wait(bars + 8 * slot, ph);
                if (tid == 0 && s == 0) TS(20);
                if (tid == 0 && s == 5) TS(21);
                if (tid == 0 && s == 10) TS(22);
                const uint64_t da = mk_desc(smR + ((s >> 1) & 7) * 8192 + (s & 1) * 64, 16, 1024);
                const uint64_t db = mk_desc(smS + slot * STAGE_BYTES + w * 16384, 4096, 1024);
                wg_fence();
                wgmma_ss_n256_tb(acc, da, db, s != 0);
                wgmma_ss_n256_tb(acc, da + 2, db + 128, 1);
                wg_commit();
                wg_wait<0>();
                if (lane == 0) mbar_arrive(bars + 8 * (NSTAGE + slot));
                pslot = slot;
                if (++slot == NSTAGE) { slot = 0; ph ^= 1; }
            }
            fence_regs(acc);
            if (tid == 0) TS(1);
#pragma unroll
            for (int kk = 0; kk < 8; kk++) {
#pragma unroll
                for (int i = 0; i < 4; i++) qf[kk][i] = pack_bf16(acc[8 * kk + 2 * i], acc[8 * kk + 2 * i + 1]);
                sts128(stash + kk * 2048,
                       pack_bf16(acc[64 + 8 * kk + 0], acc[64 + 8 * kk + 1]), pack_bf16(acc[64 + 8 * kk + 2], acc[64 + 8 * kk + 3]),
                       pack_bf16(acc[64 + 8 * kk + 4], acc[64 + 8 * kk + 5]), pack_bf16(acc[64 + 8 * kk + 6], acc[64 + 8 * kk + 7]));
            }
        }
        if (w == 1) bar_arrive<5, 256>();
        const float sc = 0.08838834764831845f * 1.4426950408889634f;
#pragma unroll
        for (int u = 0; u < 2; u++) {
            uint32_t af[16][4];
            {
                float o[64], s[64];
                float m0 = -INFINITY, m1 = -INFINITY, l0 = 0.f, l1 = 0.f;
                uint32_t pf[8][4];
#pragma unroll
                for (int i = 0; i < 64; i++) { o[i] = 0.f; s[i] = 0.f; }
#pragma unroll
                for (int i = 0; i < 32; i++) pf[i >> 2][i & 3] = 0u;
#pragma unroll 1
                for (int tt = 0; tt <= 4; tt++) {
                    int vslot = slot;
                    if (tt > 0) {
                        mbar_wait(bars + 8 * slot, ph);
                        if (++slot == lim) { slot = 0; ph ^= 1; }
                    }
                    if (tt < 4) mbar_wait(bars + 8 * slot, ph);
                    if (tid == 0) TS(32 + u * 20 + tt * 4);
                    if (w == 0) bar_sync<5, 256>(); else bar_sync<6, 256>();
                    wg_fence();
                    if (tt > 0) {
                        const uint64_t db = mk_desc(smS + vslot * STAGE_BYTES, 16384, 1024);
#pragma unroll
                        for (int kk = 0; kk < 8; kk++)
                            wgmma_rs_n128_tb(o, pf[kk][0], pf[kk][1], pf[kk][2], pf[kk][3], db + kk * 128, (tt > 1) || (kk != 0));
                        wg_commit();
                    }
                    if (tt < 4) {
                        const uint64_t db = mk_desc(smS + slot * STAGE_BYTES, 16, 1024);
#pragma unroll
                        for (int kk = 0; kk < 8; kk++)
                            wgmma_rs_n128(s, qf[kk][0], qf[kk][1], qf[kk][2], qf[kk][3], db + (kk >> 2) * 1024 + (kk & 3) * 2, kk != 0);
                        wg_commit();
                    }
                    if (w == 0) bar_arrive<6, 256>(); else if (!(u == 1 && tt == 4)) bar_arrive<5, 256>();
                    if (tid == 0) TS(32 + u * 20 + tt * 4 + 1);
                    wg_wait<0>();
                    fence_regs(o);
                    fence_regs(s);
                    if (tid == 0) TS(32 + u * 20 + tt * 4 + 2);
                    if (tt > 0 && lane == 0) mbar_arrive(bars + 8 * (NSTAGE + vslot));
                    if (tt == 4) break;
                    if (lane == 0) mbar_arrive(bars + 8 * (NSTAGE + slot));
                    if (++slot == lim) { slot = 0; ph ^= 1; }
                    float mx0 = s[0], mx1 = s[2];
#pragma unroll
                    for (int j = 0; j < 16; j++) {
                        mx0 = fmaxf(mx0, fmaxf(s[4 * j], s[4 * j + 1]));
                        mx1 = fmaxf(mx1, fmaxf(s[4 * j + 2], s[4 * j + 3]));
                    }
                    mx0 = fmaxf(mx0, __shfl_xor_sync(0xffffffffu, mx0, 1));
                    mx1 = fmaxf(mx1, __shfl_xor_sync(0xffffffffu, mx1, 1));
                    mx0 = fmaxf(mx0, __shfl_xor_sync(0xffffffffu, mx0, 2));
                    mx1 = fmaxf(mx1, __shfl_xor_sync(0xffffffffu, mx1, 2));
                    const float mn0 = fmaxf(m0, mx0), mn1 = fmaxf(m1, mx1);
                    const float al0 = ex2((m0 - mn0) * sc), al1 = ex2((m1 - mn1) * sc);
                    m0 = mn0; m1 = mn1;
                    const float ms0 = mn0 * sc, ms1 = mn1 * sc;
                    float rs0 = 0.f, rs1 = 0.f;
#pragma unroll
                    for (int j = 0; j < 16; j++) {
                        const float p0 = ex2(fmaf(s[4 * j], sc, -ms0)), p1 = ex2(fmaf(s[4 * j + 1], sc, -ms0));
                        const float p2 = ex2(fmaf(s[4 * j + 2], sc, -ms1)), p3 = ex2(fmaf(s[4 * j + 3], sc, -ms1));
                        rs0 += p0 + p1; rs1 += p2 + p3;
                        pf[j >> 1][(j & 1) * 2] = pack_bf16(p0, p1);
                        pf[j >> 1][(j & 1) * 2 + 1] = pack_bf16(p2, p3);
                    }
                    l0 = l0 * al0 + rs0; l1 = l1 * al1 + rs1;
                    if (tt > 0) {
#pragma unroll
                        for (int j = 0; j < 16; j++) { o[4 * j] *= al0; o[4 * j + 1] *= al0; o[4 * j + 2] *= al1; o[4 * j + 3] *= al1; }
                    }
                    if (tid == 0) TS(32 + u * 20 + tt * 4 + 3);
                }
                if (tid == 0) TS(2 + u);
                l0 += __shfl_xor_sync(0xffffffffu, l0, 1);
                l1 += __shfl_xor_sync(0xffffffffu, l1, 1);
                l0 += __shfl_xor_sync(0xffffffffu, l0, 2);
                l1 += __shfl_xor_sync(0xffffffffu, l1, 2);
                const float i0 = 1.f / l0, i1 = 1.f / l1;
                const uint32_t zown = smR + (w ? 3 : 0) * 16384 + t * 16;
#pragma unroll
                for (int kk = 0; kk < 8; kk++) {
                    af[kk][0] = pack_bf16(o[8 * kk + 0] * i0, o[8 * kk + 1] * i0);
                    af[kk][1] = pack_bf16(o[8 * kk + 2] * i1, o[8 * kk + 3] * i1);
                    af[kk][2] = pack_bf16(o[8 * kk + 4] * i0, o[8 * kk + 5] * i0);
                    af[kk][3] = pack_bf16(o[8 * kk + 6] * i1, o[8 * kk + 7] * i1);
                    if (u == 0) sts128(zown + kk * 2048, af[kk][0], af[kk][1], af[kk][2], af[kk][3]);
                    else __stcg(g_ox + (size_t)((grp * 16 + hp * 2 + w) * 8 + kk) * 128 + t, make_uint4(af[kk][0], af[kk][1], af[kk][2], af[kk][3]));
                }
            }
            if (u == 0) {
                if (w == 0) bar_arrive<7, 256>(); else bar_arrive<8, 256>();
                lim = 3;
#pragma unroll
                for (int kk = 0; kk < 8; kk++) lds128(stash + kk * 2048, qf[kk]);
#pragma unroll
                for (int ps = 0; ps < 2; ps++) {
                    float acc[64];
#pragma unroll
                    for (int i = 0; i < 64; i++) acc[i] = 0.f;
#pragma unroll
                    for (int st = 0; st < 4; st++) {
                        if (ps == 0 && st == 2) {
                            if (w == 0) bar_sync<8, 256>(); else bar_sync<7, 256>();
#pragma unroll
                            for (int kk = 0; kk < 8; kk++) lds128(smR + (w ? 0 : 3) * 16384 + kk * 2048 + t * 16, af[8 + kk]);
                        }
                        mbar_wait(bars + 8 * slot, ph);
                        const uint64_t db = mk_desc(smS + slot * STAGE_BYTES + w * 16384, 8192, 1024);
                        wg_fence();
#pragma unroll
                        for (int kk = 0; kk < 4; kk++)
                            wgmma_rs_n128_tb(acc, af[st * 4 + kk][0], af[st * 4 + kk][1], af[st * 4 + kk][2], af[st * 4 + kk][3], db + kk * 128, 1);
                        wg_commit();
                        wg_wait<0>();
                        if (lane == 0) mbar_arrive(bars + 8 * (NSTAGE + slot));
                        if (++slot == lim) { slot = 0; ph ^= 1; }
                    }
                    fence_regs(acc);
                    const uint32_t keep = smS + (3 + ps) * STAGE_BYTES + w * 16384 + t * 16;
#pragma unroll
                    for (int j = 0; j < 8; j++)
                        sts128(keep + j * 2048, pack_bf16(acc[8 * j], acc[8 * j + 1]), pack_bf16(acc[8 * j + 2], acc[8 * j + 3]),
                               pack_bf16(acc[8 * j + 4], acc[8 * j + 5]), pack_bf16(acc[8 * j + 6], acc[8 * j + 7]));
                    if (ps == 1) {
                        asm volatile("fence.proxy.async.shared::cta;" ::: "memory");
                        __syncwarp();
                        if (lane == 0) mbar_arrive(bars + 8 * (2 * NSTAGE + w * 5 + 1));
                    }
                    if (tid == 0) TS(4 + ps);
                }
            } else {
                __syncwarp();
                if (lane == 0) mbar_arrive(bars + 8 * (2 * NSTAGE + w * 5 + 2));
            }
            {
                float acc[32];
                if (u == 0) {
#pragma unroll
                    for (int i = 0; i < 32; i++) acc[i] = 0.f;
                } else {
#pragma unroll
                    for (int j = 0; j < 4; j++) {
                        uint32_t r[4];
                        lds128(stash + j * 2048, r);
#pragma unroll
                        for (int i = 0; i < 4; i++) { acc[8 * j + 2 * i] = __uint_as_float(r[i] << 16); acc[8 * j + 2 * i + 1] = __uint_as_float(r[i] & 0xffff0000u); }
                    }
                }
                mbar_wait(bars + 8 * slot, ph);
                const uint64_t db = mk_desc(smS + slot * STAGE_BYTES + w * 16384, 8192, 1024);
                wg_fence();
#pragma unroll
                for (int kk = 0; kk < 8; kk++)
                    wgmma_rs_n64_tb(acc, af[kk][0], af[kk][1], af[kk][2], af[kk][3], db + kk * 128, 1);
                wg_commit();
                wg_wait<0>();
                if (lane == 0) mbar_arrive(bars + 8 * (NSTAGE + slot));
                if (++slot == lim) { slot = 0; ph ^= 1; }
                fence_regs(acc);
                if (u == 0) {
#pragma unroll
                    for (int j = 0; j < 4; j++)
                        sts128(stash + j * 2048, pack_bf16(acc[8 * j], acc[8 * j + 1]), pack_bf16(acc[8 * j + 2], acc[8 * j + 3]),
                               pack_bf16(acc[8 * j + 4], acc[8 * j + 5]), pack_bf16(acc[8 * j + 6], acc[8 * j + 7]));
                } else {
                    uint2* dst8 = g_p8 + (size_t)(grp * 16 + hp * 2 + w) * 1024 + t;
#pragma unroll
                    for (int j = 0; j < 8; j++)
                        __stcg(dst8 + j * 128, make_uint2(pack_bf16(acc[4 * j], acc[4 * j + 1]), pack_bf16(acc[4 * j + 2], acc[4 * j + 3])));
                    __syncwarp();
                    if (lane == 0) mbar_arrive(bars + 8 * (2 * NSTAGE + w * 5 + 3));
                }
                if (tid == 0) TS(6 + u * 8);
            }
            if (u == 1) {
                float acc[32];
#pragma unroll
                for (int i = 0; i < 32; i++) acc[i] = 0.f;
                if (tid == 0) TS(12);
                uint4 fr[5][8];
                unsigned* myflag = &g_co[(grp * 16 + ((hp + lane) & 7) * 2 + w) * 32 + hp * 4 + (wid & 3)];
                unsigned ready = 0, fetched = 1;
                auto poll = [&]() {
                    unsigned v = 0;
                    if (lane < 8 && !((ready >> lane) & 1))
                        asm volatile("ld.acquire.gpu.global.u32 %0, [%1];" : "=r"(v) : "l"(myflag) : "memory");
                    ready |= __ballot_sync(0xffffffffu, v != 0);
                };
                auto load = [&](int i, uint4 (&f)[8]) {
                    const uint4* src = g_ox + (size_t)(grp * 16 + ((hp + i) & 7) * 2 + w) * 1024 + t;
#pragma unroll
                    for (int kk = 0; kk < 8; kk++) f[kk] = __ldcg(src + kk * 128);
                    fetched |= 1u << i;
                };
#pragma unroll
                for (int kk = 0; kk < 8; kk++) fr[0][kk] = make_uint4(af[kk][0], af[kk][1], af[kk][2], af[kk][3]);
#pragma unroll
                for (int i = 0; i < 8; i++) {
                    const bool zst = (i == 2), extra = (i >= 6) || zst;
                    const int sl = (i >= 6) ? (i - 3) : slot;
                    mbar_wait(zst ? (bars + 8 * (2 * NSTAGE + 4)) : (bars + 8 * sl), zst ? 0 : (extra ? 1 : ph));
                    const uint64_t db = mk_desc(zst ? (smR + w * 3 * 16384) : (smS + sl * STAGE_BYTES + w * 16384), 8192, 1024);
                    wg_fence();
#pragma unroll
                    for (int kk = 0; kk < 8; kk++)
                        wgmma_rs_n64_tb(acc, fr[i % 5][kk].x, fr[i % 5][kk].y, fr[i % 5][kk].z, fr[i % 5][kk].w, db + kk * 128, 1);
                    wg_commit();
                    if (i < 7) {
                        unsigned n = 0;
                        do {
                            poll();
#pragma unroll
                            for (int d = 1; d <= 4; d++)
                                if (i + d < 8 && ((ready & ~fetched) >> (i + d)) & 1) load(i + d, fr[(i + d) % 5]);
                            if (++n > (1u << 21)) break;
                        } while (!((fetched >> (i + 1)) & 1));
                    }
                    if (i == 6) {
                        wait_count(&g_c1[(grp * 8 + hp) * 8 + w * 4 + (wid & 3)], 4u, lane);
                        const uint4* src = g_p1 + (size_t)((grp * 8 + hp) * 8 + 4 * w) * 512 + t;
#pragma unroll
                        for (int x = 0; x < 16; x++) fr[3 + (x >> 3)][x & 7] = __ldcg(src + x * 128);
                    }
                    wg_wait<0>();
                    if (!extra) {
                        if (lane == 0) mbar_arrive(bars + 8 * (NSTAGE + slot));
                        if (++slot == lim) { slot = 0; ph ^= 1; }
                    }
                    if (tid == 0) TS(80 + i);
                }
                fence_regs(acc);
#pragma unroll
                for (int x = 0; x < 16; x++) {
                    const int j = x & 3;
                    const uint4 v = fr[3 + (x >> 3)][x & 7];
                    acc[8 * j + 0] += __uint_as_float(v.x << 16); acc[8 * j + 1] += __uint_as_float(v.x & 0xffff0000u);
                    acc[8 * j + 2] += __uint_as_float(v.y << 16); acc[8 * j + 3] += __uint_as_float(v.y & 0xffff0000u);
                    acc[8 * j + 4] += __uint_as_float(v.z << 16); acc[8 * j + 5] += __uint_as_float(v.z & 0xffff0000u);
                    acc[8 * j + 6] += __uint_as_float(v.w << 16); acc[8 * j + 7] += __uint_as_float(v.w & 0xffff0000u);
                }
                {
                    unsigned n = 0;
                    while (!(ready & 1)) {
                        poll();
                        if (++n > (1u << 21)) break;
                    }
                    if (lane < 8) *myflag = 0;
                }
                if (tid == 0) TS(13);
                const uint32_t xo = smR + (1 + w) * 16384 + t * 16;
                const uint32_t xi = smR + (2 - w) * 16384 + t * 16;
#pragma unroll
                for (int j = 0; j < 4; j++) {
                    const float x0 = w ? acc[4 * j] : acc[16 + 4 * j], x1 = w ? acc[4 * j + 1] : acc[16 + 4 * j + 1];
                    const float x2 = w ? acc[4 * j + 2] : acc[16 + 4 * j + 2], x3 = w ? acc[4 * j + 3] : acc[16 + 4 * j + 3];
                    sts128(xo + j * 2048, __float_as_uint(x0), __float_as_uint(x1), __float_as_uint(x2), __float_as_uint(x3));
                }
                bar_sync<4, 256>();
                __nv_bfloat16* orow = P.out + (size_t)(b * 64 + (t >> 5) * 16 + (lane >> 2)) * (2 * kD) + blk * kD + (lane & 3) * 2;
#pragma unroll
                for (int j = 0; j < 4; j++) {
                    uint32_t r[4];
                    lds128(xi + j * 2048, r);
                    const float y0 = w ? acc[16 + 4 * j] : acc[4 * j], y1 = w ? acc[16 + 4 * j + 1] : acc[4 * j + 1];
                    const float y2 = w ? acc[16 + 4 * j + 2] : acc[4 * j + 2], y3 = w ? acc[16 + 4 * j + 3] : acc[4 * j + 3];
                    *(uint32_t*)(orow + hp * 64 + (w * 4 + j) * 8) = pack_bf16(y0 + __uint_as_float(r[0]), y1 + __uint_as_float(r[1]));
                    *(uint32_t*)(orow + hp * 64 + (w * 4 + j) * 8 + 8 * 2 * kD) = pack_bf16(y2 + __uint_as_float(r[2]), y3 + __uint_as_float(r[3]));
                }
                if (w == 1) {
                    wait_count(&g_c8[grp * 32 + hp * 4 + (wid & 3)], 16u, lane);
                    const uint2* src8 = g_p8 + ((size_t)grp * 16 * 8 + hp) * 128 + t;
                    uint2 u8[16];
#pragma unroll
                    for (int i = 0; i < 16; i++) u8[i] = __ldcg(src8 + (size_t)i * 1024);
                    float a0 = 0.f, a1 = 0.f, a2 = 0.f, a3 = 0.f;
#pragma unroll
                    for (int i = 0; i < 16; i++) {
                        const uint2 x = u8[i];
                        a0 += __uint_as_float(x.x << 16); a1 += __uint_as_float(x.x & 0xffff0000u);
                        a2 += __uint_as_float(x.y << 16); a3 += __uint_as_float(x.y & 0xffff0000u);
                    }
                    *(uint32_t*)(orow + 512 + hp * 8) = pack_bf16(a0, a1);
                    *(uint32_t*)(orow + 512 + hp * 8 + 8 * 2 * kD) = pack_bf16(a2, a3);
                }
                if (tid == 0 || tid == 128) TS(18 + w);
            }
        }
    }
}

typedef CUresult (*EncodeFn)(CUtensorMap*, CUtensorMapDataType, cuuint32_t, void*, const cuuint64_t*, const cuuint64_t*,
                             const cuuint32_t*, const cuuint32_t*, CUtensorMapInterleave, CUtensorMapSwizzle,
                             CUtensorMapL2promotion, CUtensorMapFloatOOBfill);

void make_map(EncodeFn fn, CUtensorMap* m, const void* ptr, uint64_t cols, uint64_t rows, uint32_t box_rows) {
    cuuint64_t dims[2] = {cols, rows};
    cuuint64_t strides[1] = {cols * 2};
    cuuint32_t box[2] = {64, box_rows};
    cuuint32_t es[2] = {1, 1};
    fn(m, CU_TENSOR_MAP_DATA_TYPE_BFLOAT16, 2, const_cast<void*>(ptr), dims, strides, box, es, CU_TENSOR_MAP_INTERLEAVE_NONE,
       CU_TENSOR_MAP_SWIZZLE_128B, L2PROMO, CU_TENSOR_MAP_FLOAT_OOB_FILL_NONE);
}

void make_map3(EncodeFn fn, CUtensorMap* m, const void* ptr, uint64_t cols, uint64_t rows, uint32_t box_rows, uint32_t box_groups) {
    cuuint64_t dims[3] = {64, rows, cols / 64};
    cuuint64_t strides[2] = {cols * 2, 128};
    cuuint32_t box[3] = {64, box_rows, box_groups};
    cuuint32_t es[3] = {1, 1, 1};
    fn(m, CU_TENSOR_MAP_DATA_TYPE_BFLOAT16, 3, const_cast<void*>(ptr), dims, strides, box, es, CU_TENSOR_MAP_INTERLEAVE_NONE,
       CU_TENSOR_MAP_SWIZZLE_128B, L2PROMO, CU_TENSOR_MAP_FLOAT_OOB_FILL_NONE);
}

}

extern "C" void kernel_launch(void* const* d_in, const int* in_sizes, int n_in, void* d_out, int out_size) {
    static EncodeFn enc = nullptr;
    if (!enc) {
        void* fn = nullptr;
        cudaDriverEntryPointQueryResult st;
        cudaGetDriverEntryPoint("cuTensorMapEncodeTiled", &fn, cudaEnableDefault, &st);
        enc = (EncodeFn)fn;
        cudaFuncSetAttribute(fused_gqa_kernel, cudaFuncAttributeMaxDynamicSharedMemorySize, SMEM_BYTES);
    }
    Params P;
    for (int blk = 0; blk < 2; blk++) {
        const void* x = d_in[blk * 5 + 0];
        const void* k = d_in[blk * 5 + 1];
        const void* v = d_in[blk * 5 + 2];
        const void* wq = d_in[blk * 5 + 3];
        const void* wo = d_in[blk * 5 + 4];
        make_map(enc, &P.x[blk], x, kD, kB * kSq, 64);
        make_map3(enc, &P.wq[blk], wq, kHq * kDh, kD, 32, 2);
        make_map3(enc, &P.k[blk], k, kDh, (uint64_t)kB * kHkv * kSk, 128, 2);
        make_map3(enc, &P.v[blk], v, kDh, (uint64_t)kB * kHkv * kSk, 128, 2);
        make_map3(enc, &P.wo[blk], wo, kD, kHq * kDh, 64, 2);
        make_map(enc, &P.wo8[blk], wo, kD, kHq * kDh, 128);
        P.wqp[blk] = (const __nv_bfloat16*)wq;
        P.kp[blk] = (const __nv_bfloat16*)k;
        P.vp[blk] = (const __nv_bfloat16*)v;
        P.wop[blk] = (const __nv_bfloat16*)wo;
    }
    P.out = (__nv_bfloat16*)d_out;
    fused_gqa_kernel<<<128, 384, SMEM_BYTES>>>(P);
}
```

```cpp
#include <cuda_runtime.h>
#include <cuda_bf16.h>
#include <cuda.h>
#include <stdint.h>

namespace {

constexpr int kB = 8, kSq = 64, kD = 576, kHq = 32, kHkv = 16, kSk = 512, kDh = 128;
constexpr int NSTAGE = 5;
constexpr int STAGE_BYTES = 32768;
constexpr int R_BYTES = 65536;
constexpr int SMEM_BYTES = R_BYTES + NSTAGE * STAGE_BYTES + 1024   + 256  ;
constexpr int N_WQ = 18;
constexpr int PF_DIST = 6;

struct __align__(64) Params {
    CUtensorMap x[2], wq[2], k[2], v[2], wo[2], wo8[2];
    const __nv_bfloat16* kp[2];
    const __nv_bfloat16* vp[2];
    const __nv_bfloat16* wop[2];
    __nv_bfloat16* out;
};

__device__ uint2 g_part[16 * 80 * 8 * 128];
__device__ unsigned int g_cnt[16 * 9 * 32];

__device__ __forceinline__ uint32_t smem_u32(const void* p) { return (uint32_t)__cvta_generic_to_shared(p); }
__device__ __forceinline__ void mbar_init(uint32_t bar, int cnt) {
    asm volatile("mbarrier.init.shared::cta.b64 [%0], %1;" ::"r"(bar), "r"(cnt));
}
__device__ __forceinline__ void mbar_expect_tx(uint32_t bar, uint32_t bytes) {
    asm volatile("mbarrier.arrive.expect_tx.shared::cta.b64 _, [%0], %1;" ::"r"(bar), "r"(bytes) : "memory");
}
__device__ __forceinline__ void mbar_arrive(uint32_t bar) {
    asm volatile("mbarrier.arrive.shared::cta.b64 _, [%0];" ::"r"(bar) : "memory");
}
__device__ __forceinline__ bool mbar_try(uint32_t bar, uint32_t parity) {
    uint32_t ok;
    asm volatile("{\n.reg .pred p;\nmbarrier.try_wait.parity.shared::cta.b64 p, [%1], %2;\nselp.u32 %0, 1, 0, p;\n}\n"
                 : "=r"(ok) : "r"(bar), "r"(parity) : "memory");
    return ok != 0;
}
__device__ __forceinline__ void mbar_wait(uint32_t bar, uint32_t parity) {
    if (mbar_try(bar, parity)) return;
    const long long t0 = clock64();
    while (!mbar_try(bar, parity)) {
        if (clock64() - t0 > (1ll << 28)) break;
    }
}
__device__ __forceinline__ void tma_2d(uint32_t dst, const CUtensorMap* tm, int c0, int c1, uint32_t bar) {
    asm volatile("cp.async.bulk.tensor.2d.shared::cluster.global.mbarrier::complete_tx::bytes [%0], [%1, {%3, %4}], [%2];"
                 ::"r"(dst), "l"(tm), "r"(bar), "r"(c0), "r"(c1) : "memory");
}
__device__ __forceinline__ void tma_3d(uint32_t dst, const CUtensorMap* tm, int c0, int c1, int c2, uint32_t bar) {
    asm volatile("cp.async.bulk.tensor.3d.shared::cluster.global.mbarrier::complete_tx::bytes [%0], [%1, {%3, %4, %5}], [%2];"
                 ::"r"(dst), "l"(tm), "r"(bar), "r"(c0), "r"(c1), "r"(c2) : "memory");
}
__device__ __forceinline__ uint32_t l2_touch(const void* p) {
    uint32_t v;
    asm volatile("ld.global.L2::256B.b32 %0, [%1];" : "=r"(v) : "l"(p) : "memory");
    return v;
}
__device__ __forceinline__ void wg_fence() { asm volatile("wgmma.fence.sync.aligned;" ::: "memory"); }
__device__ __forceinline__ void wg_commit() { asm volatile("wgmma.commit_group.sync.aligned;" ::: "memory"); }
template <int N> __device__ __forceinline__ void wg_wait() { asm volatile("wgmma.wait_group.sync.aligned %0;" ::"n"(N) : "memory"); }
template <int N> __device__ __forceinline__ void fence_regs(float (&d)[N]) {
#pragma unroll
    for (int i = 0; i < N; i++) asm volatile("" : "+f"(d[i])::"memory");
}
__device__ __forceinline__ uint64_t mk_desc(uint32_t addr, uint32_t lbo, uint32_t sbo) {
    return (uint64_t)((addr & 0x3FFFF) >> 4) | ((uint64_t)(lbo >> 4) << 16) | ((uint64_t)(sbo >> 4) << 32) | (1ull << 62);
}
__device__ __forceinline__ uint32_t pack_bf16(float a, float b) {
    uint32_t r;
    asm("cvt.rn.bf16x2.f32 %0, %1, %2;" : "=r"(r) : "f"(b), "f"(a));
    return r;
}
__device__ __forceinline__ float ex2(float x) {
    float y;
    asm("ex2.approx.ftz.f32 %0, %1;" : "=f"(y) : "f"(x));
    return y;
}
template <int ID, int N> __device__ __forceinline__ void bar_sync() { asm volatile("bar.sync %0, %1;" ::"n"(ID), "n"(N) : "memory"); }
template <int ID, int N> __device__ __forceinline__ void bar_arrive() { asm volatile("bar.arrive %0, %1;" ::"n"(ID), "n"(N) : "memory"); }
__device__ __forceinline__ void sts128(uint32_t addr, uint32_t a, uint32_t b, uint32_t c, uint32_t d) {
    asm volatile("st.shared.v4.b32 [%0], {%1,%2,%3,%4};" ::"r"(addr), "r"(a), "r"(b), "r"(c), "r"(d) : "memory");
}
__device__ __forceinline__ void lds128(uint32_t addr, uint32_t (&r)[4]) {
    asm volatile("ld.shared.v4.b32 {%0,%1,%2,%3}, [%4];" : "=r"(r[0]), "=r"(r[1]), "=r"(r[2]), "=r"(r[3]) : "r"(addr) : "memory");
}

__device__ __forceinline__ void wgmma_ss_n256_tb(float (&d)[128], uint64_t da, uint64_t db, int sd) {
    asm volatile("{\n.reg .pred p;\nsetp.ne.b32 p, %130, 0;\n"
        "wgmma.mma_async.sync.aligned.m64n256k16.f32.bf16.bf16 "
        "{%0, %1, %2, %3, %4, %5, %6, %7, %8, %9, %10, %11, %12, %13, %14, %15, %16, %17, %18, %19, %20, %21, %22, %23, %24, %25, %26, %27, %28, %29, %30, %31, %32, %33, %34, %35, %36, %37, %38, %39, %40, %41, %42, %43, %44, %45, %46, %47, %48, %49, %50, %51, %52, %53, %54, %55, %56, %57, %58, %59, %60, %61, %62, %63, %64, %65, %66, %67, %68, %69, %70, %71, %72, %73, %74, %75, %76, %77, %78, %79, %80, %81, %82, %83, %84, %85, %86, %87, %88, %89, %90, %91, %92, %93, %94, %95, %96, %97, %98, %99, %100, %101, %102, %103, %104, %105, %106, %107, %108, %109, %110, %111, %112, %113, %114, %115, %116, %117, %118, %119, %120, %121, %122, %123, %124, %125, %126, %127}, "
        "%128, %129, p, 1, 1, 0, 1;\n}\n"
        : "+f"(d[0]), "+f"(d[1]), "+f"(d[2]), "+f"(d[3]), "+f"(d[4]), "+f"(d[5]), "+f"(d[6]), "+f"(d[7]), "+f"(d[8]), "+f"(d[9]), "+f"(d[10]), "+f"(d[11]), "+f"(d[12]), "+f"(d[13]), "+f"(d[14]), "+f"(d[15]), "+f"(d[16]), "+f"(d[17]), "+f"(d[18]), "+f"(d[19]), "+f"(d[20]), "+f"(d[21]), "+f"(d[22]), "+f"(d[23]), "+f"(d[24]), "+f"(d[25]), "+f"(d[26]), "+f"(d[27]), "+f"(d[28]), "+f"(d[29]), "+f"(d[30]), "+f"(d[31]), "+f"(d[32]), "+f"(d[33]), "+f"(d[34]), "+f"(d[35]), "+f"(d[36]), "+f"(d[37]), "+f"(d[38]), "+f"(d[39]), "+f"(d[40]), "+f"(d[41]), "+f"(d[42]), "+f"(d[43]), "+f"(d[44]), "+f"(d[45]), "+f"(d[46]), "+f"(d[47]), "+f"(d[48]), "+f"(d[49]), "+f"(d[50]), "+f"(d[51]), "+f"(d[52]), "+f"(d[53]), "+f"(d[54]), "+f"(d[55]), "+f"(d[56]), "+f"(d[57]), "+f"(d[58]), "+f"(d[59]), "+f"(d[60]), "+f"(d[61]), "+f"(d[62]), "+f"(d[63]), "+f"(d[64]), "+f"(d[65]), "+f"(d[66]), "+f"(d[67]), "+f"(d[68]), "+f"(d[69]), "+f"(d[70]), "+f"(d[71]), "+f"(d[72]), "+f"(d[73]), "+f"(d[74]), "+f"(d[75]), "+f"(d[76]), "+f"(d[77]), "+f"(d[78]), "+f"(d[79]), "+f"(d[80]), "+f"(d[81]), "+f"(d[82]), "+f"(d[83]), "+f"(d[84]), "+f"(d[85]), "+f"(d[86]), "+f"(d[87]), "+f"(d[88]), "+f"(d[89]), "+f"(d[90]), "+f"(d[91]), "+f"(d[92]), "+f"(d[93]), "+f"(d[94]), "+f"(d[95]), "+f"(d[96]), "+f"(d[97]), "+f"(d[98]), "+f"(d[99]), "+f"(d[100]), "+f"(d[101]), "+f"(d[102]), "+f"(d[103]), "+f"(d[104]), "+f"(d[105]), "+f"(d[106]), "+f"(d[107]), "+f"(d[108]), "+f"(d[109]), "+f"(d[110]), "+f"(d[111]), "+f"(d[112]), "+f"(d[113]), "+f"(d[114]), "+f"(d[115]), "+f"(d[116]), "+f"(d[117]), "+f"(d[118]), "+f"(d[119]), "+f"(d[120]), "+f"(d[121]), "+f"(d[122]), "+f"(d[123]), "+f"(d[124]), "+f"(d[125]), "+f"(d[126]), "+f"(d[127])
        : "l"(da), "l"(db), "r"(sd));
}
__device__ __forceinline__ void wgmma_rs_n128(float (&d)[64], uint32_t a0, uint32_t a1, uint32_t a2, uint32_t a3, uint64_t db, int sd) {
    asm volatile("{\n.reg .pred p;\nsetp.ne.b32 p, %69, 0;\n"
        "wgmma.mma_async.sync.aligned.m64n128k16.f32.bf16.bf16 "
        "{%0, %1, %2, %3, %4, %5, %6, %7, %8, %9, %10, %11, %12, %13, %14, %15, %16, %17, %18, %19, %20, %21, %22, %23, %24, %25, %26, %27, %28, %29, %30, %31, %32, %33, %34, %35, %36, %37, %38, %39, %40, %41, %42, %43, %44, %45, %46, %47, %48, %49, %50, %51, %52, %53, %54, %55, %56, %57, %58, %59, %60, %61, %62, %63}, "
        "{%64, %65, %66, %67}, %68, p, 1, 1, 0;\n}\n"
        : "+f"(d[0]), "+f"(d[1]), "+f"(d[2]), "+f"(d[3]), "+f"(d[4]), "+f"(d[5]), "+f"(d[6]), "+f"(d[7]), "+f"(d[8]), "+f"(d[9]), "+f"(d[10]), "+f"(d[11]), "+f"(d[12]), "+f"(d[13]), "+f"(d[14]), "+f"(d[15]), "+f"(d[16]), "+f"(d[17]), "+f"(d[18]), "+f"(d[19]), "+f"(d[20]), "+f"(d[21]), "+f"(d[22]), "+f"(d[23]), "+f"(d[24]), "+f"(d[25]), "+f"(d[26]), "+f"(d[27]), "+f"(d[28]), "+f"(d[29]), "+f"(d[30]), "+f"(d[31]), "+f"(d[32]), "+f"(d[33]), "+f"(d[34]), "+f"(d[35]), "+f"(d[36]), "+f"(d[37]), "+f"(d[38]), "+f"(d[39]), "+f"(d[40]), "+f"(d[41]), "+f"(d[42]), "+f"(d[43]), "+f"(d[44]), "+f"(d[45]), "+f"(d[46]), "+f"(d[47]), "+f"(d[48]), "+f"(d[49]), "+f"(d[50]), "+f"(d[51]), "+f"(d[52]), "+f"(d[53]), "+f"(d[54]), "+f"(d[55]), "+f"(d[56]), "+f"(d[57]), "+f"(d[58]), "+f"(d[59]), "+f"(d[60]), "+f"(d[61]), "+f"(d[62]), "+f"(d[63])
        : "r"(a0), "r"(a1), "r"(a2), "r"(a3), "l"(db), "r"(sd));
}
__device__ __forceinline__ void wgmma_rs_n128_tb(float (&d)[64], uint32_t a0, uint32_t a1, uint32_t a2, uint32_t a3, uint64_t db, int sd) {
    asm volatile("{\n.reg .pred p;\nsetp.ne.b32 p, %69, 0;\n"
        "wgmma.mma_async.sync.aligned.m64n128k16.f32.bf16.bf16 "
        "{%0, %1, %2, %3, %4, %5, %6, %7, %8, %9, %10, %11, %12, %13, %14, %15, %16, %17, %18, %19, %20, %21, %22, %23, %24, %25, %26, %27, %28, %29, %30, %31, %32, %33, %34, %35, %36, %37, %38, %39, %40, %41, %42, %43, %44, %45, %46, %47, %48, %49, %50, %51, %52, %53, %54, %55, %56, %57, %58, %59, %60, %61, %62, %63}, "
        "{%64, %65, %66, %67}, %68, p, 1, 1, 1;\n}\n"
        : "+f"(d[0]), "+f"(d[1]), "+f"(d[2]), "+f"(d[3]), "+f"(d[4]), "+f"(d[5]), "+f"(d[6]), "+f"(d[7]), "+f"(d[8]), "+f"(d[9]), "+f"(d[10]), "+f"(d[11]), "+f"(d[12]), "+f"(d[13]), "+f"(d[14]), "+f"(d[15]), "+f"(d[16]), "+f"(d[17]), "+f"(d[18]), "+f"(d[19]), "+f"(d[20]), "+f"(d[21]), "+f"(d[22]), "+f"(d[23]), "+f"(d[24]), "+f"(d[25]), "+f"(d[26]), "+f"(d[27]), "+f"(d[28]), "+f"(d[29]), "+f"(d[30]), "+f"(d[31]), "+f"(d[32]), "+f"(d[33]), "+f"(d[34]), "+f"(d[35]), "+f"(d[36]), "+f"(d[37]), "+f"(d[38]), "+f"(d[39]), "+f"(d[40]), "+f"(d[41]), "+f"(d[42]), "+f"(d[43]), "+f"(d[44]), "+f"(d[45]), "+f"(d[46]), "+f"(d[47]), "+f"(d[48]), "+f"(d[49]), "+f"(d[50]), "+f"(d[51]), "+f"(d[52]), "+f"(d[53]), "+f"(d[54]), "+f"(d[55]), "+f"(d[56]), "+f"(d[57]), "+f"(d[58]), "+f"(d[59]), "+f"(d[60]), "+f"(d[61]), "+f"(d[62]), "+f"(d[63])
        : "r"(a0), "r"(a1), "r"(a2), "r"(a3), "l"(db), "r"(sd));
}
__device__ __forceinline__ void wgmma_rs_n64_tb(float (&d)[32], uint32_t a0, uint32_t a1, uint32_t a2, uint32_t a3, uint64_t db, int sd) {
    asm volatile("{\n.reg .pred p;\nsetp.ne.b32 p, %37, 0;\n"
        "wgmma.mma_async.sync.aligned.m64n64k16.f32.bf16.bf16 "
        "{%0, %1, %2, %3, %4, %5, %6, %7, %8, %9, %10, %11, %12, %13, %14, %15, %16, %17, %18, %19, %20, %21, %22, %23, %24, %25, %26, %27, %28, %29, %30, %31}, "
        "{%32, %33, %34, %35}, %36, p, 1, 1, 1;\n}\n"
        : "+f"(d[0]), "+f"(d[1]), "+f"(d[2]), "+f"(d[3]), "+f"(d[4]), "+f"(d[5]), "+f"(d[6]), "+f"(d[7]), "+f"(d[8]), "+f"(d[9]), "+f"(d[10]), "+f"(d[11]), "+f"(d[12]), "+f"(d[13]), "+f"(d[14]), "+f"(d[15]), "+f"(d[16]), "+f"(d[17]), "+f"(d[18]), "+f"(d[19]), "+f"(d[20]), "+f"(d[21]), "+f"(d[22]), "+f"(d[23]), "+f"(d[24]), "+f"(d[25]), "+f"(d[26]), "+f"(d[27]), "+f"(d[28]), "+f"(d[29]), "+f"(d[30]), "+f"(d[31])
        : "r"(a0), "r"(a1), "r"(a2), "r"(a3), "l"(db), "r"(sd));
}


__global__ void __launch_bounds__(384, 1) fused_gqa_kernel(const __grid_constant__ Params P) {
    extern __shared__ uint8_t smem_raw[];
    const uint32_t base = (smem_u32(smem_raw) + 1023u) & ~1023u;
    const uint32_t smR = base;
    const uint32_t smS = base + R_BYTES;
    const uint32_t bars = smS + NSTAGE * STAGE_BYTES;
    const uint32_t prog = bars + 8 * (2 * NSTAGE + 10);
    const int tid = threadIdx.x;
    const int wid = __shfl_sync(0xffffffffu, tid >> 5, 0);
    const int lane = tid & 31;

    const int cta = blockIdx.x;
    const int blk = cta >> 6;
    const int hp = (cta >> 3) & 7;
    const int b = cta & 7;
    const int grp = blk * 8 + b;

    if (tid == 256) {
        asm volatile("prefetch.tensormap [%0];" ::"l"(&P.x[blk]) : "memory");
        asm volatile("prefetch.tensormap [%0];" ::"l"(&P.wq[blk]) : "memory");
        for (int i = 0; i < NSTAGE; i++) {
            mbar_init(bars + 8 * i, 1);
            mbar_init(bars + 8 * (NSTAGE + i), 8);
        }
        for (int i = 0; i < 10; i++) mbar_init(bars + 8 * (2 * NSTAGE + i), 4);
        asm volatile("st.volatile.shared.u32 [%0], %1;" ::"r"(prog), "r"(0) : "memory");
        asm volatile("fence.mbarrier_init.release.cluster;" ::: "memory");
        asm volatile("fence.proxy.async.shared::cta;" ::: "memory");
#pragma unroll
        for (int s = 0; s < NSTAGE; s++) {
            const uint32_t fb = bars + 8 * s;
            const uint32_t dst = smS + s * STAGE_BYTES;
            mbar_expect_tx(fb, (s & 1) ? STAGE_BYTES : STAGE_BYTES + 8192);
            if (!(s & 1)) tma_2d(smR + (s >> 1) * 8192, &P.x[blk], (s >> 1) * 64, b * 64, fb);
#pragma unroll
            for (int p = 0; p < 4; p++) tma_3d(dst + p * 8192, &P.wq[blk], 0, s * 32, hp * 8 + (p & 1) * 4 + (p >> 1) * 2, fb);
        }
        asm volatile("prefetch.tensormap [%0];" ::"l"(&P.k[blk]) : "memory");
        asm volatile("prefetch.tensormap [%0];" ::"l"(&P.v[blk]) : "memory");
        asm volatile("prefetch.tensormap [%0];" ::"l"(&P.wo[blk]) : "memory");
        asm volatile("prefetch.tensormap [%0];" ::"l"(&P.wo8[blk]) : "memory");
    }
    __syncthreads();

    if (wid >= 8) {
        asm volatile("setmaxnreg.dec.sync.aligned.u32 40;");
        auto publish = [&](int hw, int k) {
            mbar_wait(bars + 8 * (2 * NSTAGE + hw * 5 + k), 0);
            const int c = (k < 2) ? (2 * k + hw) : 4;
            asm volatile("fence.acq_rel.gpu;" ::: "memory");
            asm volatile("red.relaxed.gpu.global.add.u32 [%0], 1;" ::"l"(&g_cnt[(grp * 9 + c) * 32 + lane]) : "memory");
        };
        if (wid == 8) {
            if (lane == 0) {
                int slot = 0, ph = 0;
                for (int s = NSTAGE; s < N_WQ; s++) {
                    const uint32_t fb = bars + 8 * slot;
                    mbar_wait(bars + 8 * (NSTAGE + slot), ph);
                    const uint32_t dst = smS + slot * STAGE_BYTES;
                    mbar_expect_tx(fb, (s & 1) ? STAGE_BYTES : STAGE_BYTES + 8192);
                    if (!(s & 1)) tma_2d(smR + ((s >> 1) & 7) * 8192, &P.x[blk], (s >> 1) * 64, b * 64, fb);
#pragma unroll
                    for (int p = 0; p < 4; p++) {
                        const int w = p >> 1, j = p & 1;
                        tma_3d(dst + p * 8192, &P.wq[blk], 0, s * 32, hp * 8 + j * 4 + w * 2, fb);
                    }
                    if (++slot == NSTAGE) { slot = 0; ph ^= 1; }
                }
                int lim = NSTAGE;
                for (int i = 0; i < 34; i++) {
                    const int u = (i >= 17), r = i - 17 * u;
                    const bool extra = (i == 28) || (i == 33);
                    const int sl = extra ? ((i == 28) ? 3 : 4) : slot;
                    const uint32_t fb = bars + 8 * sl;
                    mbar_wait(bars + 8 * (NSTAGE + sl), extra ? 1 : ph);
                    const uint32_t dst = smS + sl * STAGE_BYTES;
                    mbar_expect_tx(fb, STAGE_BYTES);
                    if (r < 8) {
                        const int row = (b * kHkv + hp * 2 + u) * kSk + (r >> 1) * 128;
                        tma_3d(dst, (r & 1) ? &P.v[blk] : &P.k[blk], 0, row, 0, fb);
                    } else {
                        const int q = r - 8, row = hp * 512 + u * 256;
                        if (q < 8) {
                            tma_3d(dst, &P.wo[blk], 0, row + (q & 3) * 64, (q >> 2) * 4, fb);
                            tma_3d(dst + 16384, &P.wo[blk], 0, row + ((q & 3) ^ 2) * 64, (q >> 2) * 4 + 2, fb);
                        } else {
                            tma_2d(dst, &P.wo8[blk], 512, row, fb);
                            tma_2d(dst + 16384, &P.wo8[blk], 512, row + 128, fb);
                        }
                    }
                    asm volatile("st.volatile.shared.u32 [%0], %1;" ::"r"(prog), "r"(i + 1) : "memory");
                    if (i == 7) lim = 3;
                    if (!extra && ++slot == lim) { slot = 0; ph ^= 1; }
                }
            }
            __syncwarp();
            publish(1, 1);
        } else if (wid == 11) {
            uint32_t sink = 0;
            mbar_wait(bars, 0);
            const char* kbase = (const char*)(P.kp[blk] + (size_t)(b * kHkv + hp * 2) * kSk * kDh);
            const char* vbase = (const char*)(P.vp[blk] + (size_t)(b * kHkv + hp * 2) * kSk * kDh);
            const char* wos = (const char*)(P.wop[blk] + (size_t)hp * 512 * kD) + (size_t)b * 36864;
            for (int i = 0; i < 18; i++) {
                const int u = (i >= 9), r = i - 9 * u;
                if (i >= PF_DIST) {
                    uint32_t pr, n = 0;
                    while (true) {
                        asm volatile("ld.volatile.shared.u32 %0, [%1];" : "=r"(pr) : "r"(prog) : "memory");
                        const int prk = ((int)pr <= 8) ? (int)pr : (((int)pr <= 17) ? 8 + ((int)pr - 8) / 9 : (int)pr - 8);
                        if (prk + PF_DIST >= i) break;
                        if (++n > (1u << 22)) break;
                        __nanosleep(100);
                    }
                }
                const char* p = (r < 8) ? (((r & 1) ? vbase : kbase) + (size_t)(u * 4 + (r >> 1)) * 32768 + lane * 256) : (wos + (size_t)u * 294912 + lane * 256);
                uint32_t c[5];
                if (sink == 0x9E3779B9u) asm volatile("st.volatile.shared.u32 [%0], %1;" ::"r"(prog + 4), "r"(sink) : "memory");
#pragma unroll
                for (int j = 0; j < 4; j++) c[j] = l2_touch(p + j * 8192);
                c[4] = 0;
                if (r == 8 && lane < 16) c[4] = l2_touch(p + 4 * 8192);
                sink = c[0] | c[1] | c[2] | c[3] | c[4];
            }
            if (sink == 0x9E3779B9u) asm volatile("st.volatile.shared.u32 [%0], %1;" ::"r"(prog + 4), "r"(sink) : "memory");
            publish(0, 1);
        } else {
            const int hw = wid - 9;
            publish(hw, 0);
            publish(hw, 2);
        }
    } else {
        asm volatile("setmaxnreg.inc.sync.aligned.u32 232;");
        const int w = wid >> 2;
        const int t = tid & 127;
        int slot = 0, ph = 0, lim = NSTAGE;
        uint32_t qf[8][4];
        const uint32_t stash = smR + (1 + w) * 16384 + t * 16;
        {
            float acc[128];
            for (int s = 0; s < N_WQ; s++) {
                mbar_wait(bars + 8 * slot, ph);
                const uint64_t da = mk_desc(smR + ((s >> 1) & 7) * 8192 + (s & 1) * 64, 16, 1024);
                const uint64_t db = mk_desc(smS + slot * STAGE_BYTES + w * 16384, 4096, 1024);
                wg_fence();
                wgmma_ss_n256_tb(acc, da, db, s != 0);
                wgmma_ss_n256_tb(acc, da + 2, db + 128, 1);
                wg_commit();
                wg_wait<0>();
                if (lane == 0) mbar_arrive(bars + 8 * (NSTAGE + slot));
                if (++slot == NSTAGE) { slot = 0; ph ^= 1; }
            }
            fence_regs(acc);
#pragma unroll
            for (int kk = 0; kk < 8; kk++) {
#pragma unroll
                for (int i = 0; i < 4; i++) qf[kk][i] = pack_bf16(acc[8 * kk + 2 * i], acc[8 * kk + 2 * i + 1]);
                sts128(stash + kk * 2048,
                       pack_bf16(acc[64 + 8 * kk + 0], acc[64 + 8 * kk + 1]), pack_bf16(acc[64 + 8 * kk + 2], acc[64 + 8 * kk + 3]),
                       pack_bf16(acc[64 + 8 * kk + 4], acc[64 + 8 * kk + 5]), pack_bf16(acc[64 + 8 * kk + 6], acc[64 + 8 * kk + 7]));
            }
        }
        if (w == 1) bar_arrive<5, 256>();
        const float sc = 0.08838834764831845f * 1.4426950408889634f;
        uint2* dst0 = g_part + (size_t)(grp * 80 + 2 * w * 8 + hp) * 1024 + t;
        uint2* dst8 = g_part + (size_t)(grp * 80 + 64 + hp * 2 + w) * 1024 + t;
#pragma unroll
        for (int u = 0; u < 2; u++) {
            uint32_t af[16][4];
            {
                float o[64], s[64];
                float m0 = -INFINITY, m1 = -INFINITY, l0 = 0.f, l1 = 0.f;
                uint32_t pf[8][4];
#pragma unroll
                for (int i = 0; i < 64; i++) { o[i] = 0.f; s[i] = 0.f; }
#pragma unroll
                for (int i = 0; i < 32; i++) pf[i >> 2][i & 3] = 0u;
#pragma unroll 1
                for (int tt = 0; tt <= 4; tt++) {
                    int vslot = slot;
                    if (tt > 0) {
                        mbar_wait(bars + 8 * slot, ph);
                        if (++slot == lim) { slot = 0; ph ^= 1; }
                    }
                    if (tt < 4) mbar_wait(bars + 8 * slot, ph);
                    if (w == 0) bar_sync<5, 256>(); else bar_sync<6, 256>();
                    wg_fence();
                    if (tt > 0) {
                        const uint64_t db = mk_desc(smS + vslot * STAGE_BYTES, 16384, 1024);
#pragma unroll
                        for (int kk = 0; kk < 8; kk++)
                            wgmma_rs_n128_tb(o, pf[kk][0], pf[kk][1], pf[kk][2], pf[kk][3], db + kk * 128, (tt > 1) || (kk != 0));
                        wg_commit();
                    }
                    if (tt < 4) {
                        const uint64_t db = mk_desc(smS + slot * STAGE_BYTES, 16, 1024);
#pragma unroll
                        for (int kk = 0; kk < 8; kk++)
                            wgmma_rs_n128(s, qf[kk][0], qf[kk][1], qf[kk][2], qf[kk][3], db + (kk >> 2) * 1024 + (kk & 3) * 2, kk != 0);
                        wg_commit();
                    }
                    if (w == 0) bar_arrive<6, 256>(); else if (!(u == 1 && tt == 4)) bar_arrive<5, 256>();
                    wg_wait<0>();
                    fence_regs(o);
                    fence_regs(s);
                    if (tt > 0 && lane == 0) mbar_arrive(bars + 8 * (NSTAGE + vslot));
                    if (tt == 4) break;
                    if (lane == 0) mbar_arrive(bars + 8 * (NSTAGE + slot));
                    if (++slot == lim) { slot = 0; ph ^= 1; }
                    float mx0 = s[0], mx1 = s[2];
#pragma unroll
                    for (int j = 0; j < 16; j++) {
                        mx0 = fmaxf(mx0, fmaxf(s[4 * j], s[4 * j + 1]));
                        mx1 = fmaxf(mx1, fmaxf(s[4 * j + 2], s[4 * j + 3]));
                    }
                    mx0 = fmaxf(mx0, __shfl_xor_sync(0xffffffffu, mx0, 1));
                    mx1 = fmaxf(mx1, __shfl_xor_sync(0xffffffffu, mx1, 1));
                    mx0 = fmaxf(mx0, __shfl_xor_sync(0xffffffffu, mx0, 2));
                    mx1 = fmaxf(mx1, __shfl_xor_sync(0xffffffffu, mx1, 2));
                    const float mn0 = fmaxf(m0, mx0), mn1 = fmaxf(m1, mx1);
                    const float al0 = ex2((m0 - mn0) * sc), al1 = ex2((m1 - mn1) * sc);
                    m0 = mn0; m1 = mn1;
                    const float ms0 = mn0 * sc, ms1 = mn1 * sc;
                    float rs0 = 0.f, rs1 = 0.f;
#pragma unroll
                    for (int j = 0; j < 16; j++) {
                        const float p0 = ex2(fmaf(s[4 * j], sc, -ms0)), p1 = ex2(fmaf(s[4 * j + 1], sc, -ms0));
                        const float p2 = ex2(fmaf(s[4 * j + 2], sc, -ms1)), p3 = ex2(fmaf(s[4 * j + 3], sc, -ms1));
                        rs0 += p0 + p1; rs1 += p2 + p3;
                        pf[j >> 1][(j & 1) * 2] = pack_bf16(p0, p1);
                        pf[j >> 1][(j & 1) * 2 + 1] = pack_bf16(p2, p3);
                    }
                    l0 = l0 * al0 + rs0; l1 = l1 * al1 + rs1;
                    if (tt > 0) {
#pragma unroll
                        for (int j = 0; j < 16; j++) { o[4 * j] *= al0; o[4 * j + 1] *= al0; o[4 * j + 2] *= al1; o[4 * j + 3] *= al1; }
                    }
                }
                l0 += __shfl_xor_sync(0xffffffffu, l0, 1);
                l1 += __shfl_xor_sync(0xffffffffu, l1, 1);
                l0 += __shfl_xor_sync(0xffffffffu, l0, 2);
                l1 += __shfl_xor_sync(0xffffffffu, l1, 2);
                const float i0 = 1.f / l0, i1 = 1.f / l1;
                const uint32_t zown = smR + (w ? 3 : 0) * 16384 + t * 16;
#pragma unroll
                for (int kk = 0; kk < 8; kk++) {
                    af[kk][0] = pack_bf16(o[8 * kk + 0] * i0, o[8 * kk + 1] * i0);
                    af[kk][1] = pack_bf16(o[8 * kk + 2] * i1, o[8 * kk + 3] * i1);
                    af[kk][2] = pack_bf16(o[8 * kk + 4] * i0, o[8 * kk + 5] * i0);
                    af[kk][3] = pack_bf16(o[8 * kk + 6] * i1, o[8 * kk + 7] * i1);
                    sts128(zown + kk * 2048, af[kk][0], af[kk][1], af[kk][2], af[kk][3]);
                }
            }
            if (w == 0) bar_arrive<7, 256>(); else bar_arrive<8, 256>();
            lim = 3;
            if (u == 0) {
#pragma unroll
                for (int kk = 0; kk < 8; kk++) lds128(stash + kk * 2048, qf[kk]);
            }
            uint32_t nx[8][4];
#pragma unroll
            for (int ps = 0; ps < 2; ps++) {
                float acc[64];
                const uint32_t keep = smS + (3 + ps) * STAGE_BYTES + w * 16384 + t * 16;
                if (u == 0) {
#pragma unroll
                    for (int i = 0; i < 64; i++) acc[i] = 0.f;
                } else {
                    if (ps == 0) {
#pragma unroll
                        for (int j = 0; j < 8; j++) lds128(keep + j * 2048, nx[j]);
                        asm volatile("fence.proxy.async.shared::cta;" ::: "memory");
                        __syncwarp();
                        if (lane == 0) mbar_arrive(bars + 8 * (NSTAGE + 3));
                    }
#pragma unroll
                    for (int j = 0; j < 8; j++)
#pragma unroll
                        for (int i = 0; i < 4; i++) { acc[8 * j + 2 * i] = __uint_as_float(nx[j][i] << 16); acc[8 * j + 2 * i + 1] = __uint_as_float(nx[j][i] & 0xffff0000u); }
                }
#pragma unroll
                for (int st = 0; st < 4; st++) {
                    if (ps == 0 && st == 2) {
                        if (w == 0) bar_sync<8, 256>(); else bar_sync<7, 256>();
#pragma unroll
                        for (int kk = 0; kk < 8; kk++) lds128(smR + (w ? 0 : 3) * 16384 + kk * 2048 + t * 16, af[8 + kk]);
                    }
                    const bool extra = (u == 1) && (ps == 0 && st == 3);
                    const int sl = extra ? (3 + ps) : slot;
                    mbar_wait(bars + 8 * sl, extra ? 1 : ph);
                    const uint64_t db = mk_desc(smS + sl * STAGE_BYTES + w * 16384, 8192, 1024);
                    wg_fence();
#pragma unroll
                    for (int kk = 0; kk < 4; kk++)
                        wgmma_rs_n128_tb(acc, af[st * 4 + kk][0], af[st * 4 + kk][1], af[st * 4 + kk][2], af[st * 4 + kk][3], db + kk * 128, 1);
                    wg_commit();
                    if (u == 1 && st == 1) {
                        if (ps == 0) {
#pragma unroll
                            for (int j = 0; j < 8; j++) lds128(keep + STAGE_BYTES + j * 2048, nx[j]);
                            asm volatile("fence.proxy.async.shared::cta;" ::: "memory");
                            __syncwarp();
                            if (lane == 0) mbar_arrive(bars + 8 * (NSTAGE + 4));
                        } else {
#pragma unroll
                            for (int j = 0; j < 4; j++) lds128(stash + j * 2048, nx[j]);
                        }
                    }
                    wg_wait<0>();
                    if (!extra) {
                        if (lane == 0) mbar_arrive(bars + 8 * (NSTAGE + slot));
                        if (++slot == 3) { slot = 0; ph ^= 1; }
                    }
                }
                fence_regs(acc);
                if (u == 0) {
#pragma unroll
                    for (int j = 0; j < 8; j++)
                        sts128(keep + j * 2048, pack_bf16(acc[8 * j], acc[8 * j + 1]), pack_bf16(acc[8 * j + 2], acc[8 * j + 3]),
                               pack_bf16(acc[8 * j + 4], acc[8 * j + 5]), pack_bf16(acc[8 * j + 6], acc[8 * j + 7]));
                } else {
                    uint2* dst = dst0 + (size_t)ps * 32 * 1024;
#pragma unroll
                    for (int j = 0; j < 16; j++)
                        __stcg(dst + (j >> 3) * 8192 + (j & 7) * 128, make_uint2(pack_bf16(acc[4 * j], acc[4 * j + 1]), pack_bf16(acc[4 * j + 2], acc[4 * j + 3])));
                    __syncwarp();
                    if (lane == 0) mbar_arrive(bars + 8 * (2 * NSTAGE + w * 5 + ps));
                }
            }
            {
                float acc[32];
                if (u == 0) {
#pragma unroll
                    for (int i = 0; i < 32; i++) acc[i] = 0.f;
                } else {
#pragma unroll
                    for (int j = 0; j < 4; j++)
#pragma unroll
                        for (int i = 0; i < 4; i++) { acc[8 * j + 2 * i] = __uint_as_float(nx[j][i] << 16); acc[8 * j + 2 * i + 1] = __uint_as_float(nx[j][i] & 0xffff0000u); }
                }
                const int sl = u ? 4 : slot;
                mbar_wait(bars + 8 * sl, u ? 1 : ph);
                const uint64_t db = mk_desc(smS + sl * STAGE_BYTES + w * 16384, 8192, 1024);
                wg_fence();
#pragma unroll
                for (int kk = 0; kk < 8; kk++)
                    wgmma_rs_n64_tb(acc, af[kk][0], af[kk][1], af[kk][2], af[kk][3], db + kk * 128, 1);
                wg_commit();
                wg_wait<0>();
                if (u == 0) {
                    if (lane == 0) mbar_arrive(bars + 8 * (NSTAGE + slot));
                    if (++slot == 3) { slot = 0; ph ^= 1; }
                }
                fence_regs(acc);
                if (u == 0) {
#pragma unroll
                    for (int j = 0; j < 4; j++)
                        sts128(stash + j * 2048, pack_bf16(acc[8 * j], acc[8 * j + 1]), pack_bf16(acc[8 * j + 2], acc[8 * j + 3]),
                               pack_bf16(acc[8 * j + 4], acc[8 * j + 5]), pack_bf16(acc[8 * j + 6], acc[8 * j + 7]));
                } else {
#pragma unroll
                    for (int j = 0; j < 8; j++)
                        __stcg(dst8 + j * 128, make_uint2(pack_bf16(acc[4 * j], acc[4 * j + 1]), pack_bf16(acc[4 * j + 2], acc[4 * j + 3])));
                    __syncwarp();
                    if (lane == 0) mbar_arrive(bars + 8 * (2 * NSTAGE + w * 5 + 2));
                }
            }
        }
        {
            __nv_bfloat16* orow = P.out + (size_t)(b * 64 + (t >> 5) * 16 + (lane >> 2)) * (2 * kD) + blk * kD + hp * 8 + (lane & 3) * 2;
#pragma unroll
            for (int g = 0; g < 2; g++) {
                const bool last = (g == 1) && (w == 0);
                if (lane == 0 || (last && lane == 1)) {
                    unsigned* cp = &g_cnt[(grp * 9 + (lane ? 4 : (2 * g + w))) * 32 + hp * 4 + (wid & 3)];
                    unsigned v, n = 0;
                    while (true) {
                        asm volatile("ld.acquire.gpu.global.u32 %0, [%1];" : "=r"(v) : "l"(cp) : "memory");
                        if (v >= (lane ? 16u : 8u)) break;
                        if (++n > (1u << 21)) break;
                    }
                    *cp = 0;
                }
                __syncwarp();
                const uint2* src = g_part + ((size_t)(grp * 80 + g * 32 + 2 * w * 8) * 8 + hp) * 128 + t;
                uint2 v[16], u8[16];
#pragma unroll
                for (int i = 0; i < 16; i++) v[i] = __ldcg(src + (size_t)i * 1024);
                if (last) {
                    const uint2* src8 = g_part + ((size_t)(grp * 80 + 64) * 8 + hp) * 128 + t;
#pragma unroll
                    for (int i = 0; i < 16; i++) u8[i] = __ldcg(src8 + (size_t)i * 1024);
                }
#pragma unroll
                for (int h = 0; h < 2; h++) {
                    float a0 = 0.f, a1 = 0.f, a2 = 0.f, a3 = 0.f;
#pragma unroll
                    for (int i = 0; i < 8; i++) {
                        const uint2 x = v[h * 8 + i];
                        a0 += __uint_as_float(x.x << 16); a1 += __uint_as_float(x.x & 0xffff0000u);
                        a2 += __uint_as_float(x.y << 16); a3 += __uint_as_float(x.y & 0xffff0000u);
                    }
                    *(uint32_t*)(orow + (g * 4 + 2 * w + h) * 64) = pack_bf16(a0, a1);
                    *(uint32_t*)(orow + (g * 4 + 2 * w + h) * 64 + 8 * 2 * kD) = pack_bf16(a2, a3);
                }
                if (last) {
                    float a0 = 0.f, a1 = 0.f, a2 = 0.f, a3 = 0.f;
#pragma unroll
                    for (int i = 0; i < 16; i++) {
                        const uint2 x = u8[i];
                        a0 += __uint_as_float(x.x << 16); a1 += __uint_as_float(x.x & 0xffff0000u);
                        a2 += __uint_as_float(x.y << 16); a3 += __uint_as_float(x.y & 0xffff0000u);
                    }
                    *(uint32_t*)(orow + 512) = pack_bf16(a0, a1);
                    *(uint32_t*)(orow + 512 + 8 * 2 * kD) = pack_bf16(a2, a3);
                }
            }
        }
    }
}

typedef CUresult (*EncodeFn)(CUtensorMap*, CUtensorMapDataType, cuuint32_t, void*, const cuuint64_t*, const cuuint64_t*,
                             const cuuint32_t*, const cuuint32_t*, CUtensorMapInterleave, CUtensorMapSwizzle,
                             CUtensorMapL2promotion, CUtensorMapFloatOOBfill);

void make_map(EncodeFn fn, CUtensorMap* m, const void* ptr, uint64_t cols, uint64_t rows, uint32_t box_rows) {
    cuuint64_t dims[2] = {cols, rows};
    cuuint64_t strides[1] = {cols * 2};
    cuuint32_t box[2] = {64, box_rows};
    cuuint32_t es[2] = {1, 1};
    fn(m, CU_TENSOR_MAP_DATA_TYPE_BFLOAT16, 2, const_cast<void*>(ptr), dims, strides, box, es, CU_TENSOR_MAP_INTERLEAVE_NONE,
       CU_TENSOR_MAP_SWIZZLE_128B, CU_TENSOR_MAP_L2_PROMOTION_L2_256B, CU_TENSOR_MAP_FLOAT_OOB_FILL_NONE);
}

void make_map3(EncodeFn fn, CUtensorMap* m, const void* ptr, uint64_t cols, uint64_t rows, uint32_t box_rows, uint32_t box_groups) {
    cuuint64_t dims[3] = {64, rows, cols / 64};
    cuuint64_t strides[2] = {cols * 2, 128};
    cuuint32_t box[3] = {64, box_rows, box_groups};
    cuuint32_t es[3] = {1, 1, 1};
    fn(m, CU_TENSOR_MAP_DATA_TYPE_BFLOAT16, 3, const_cast<void*>(ptr), dims, strides, box, es, CU_TENSOR_MAP_INTERLEAVE_NONE,
       CU_TENSOR_MAP_SWIZZLE_128B, CU_TENSOR_MAP_L2_PROMOTION_L2_256B, CU_TENSOR_MAP_FLOAT_OOB_FILL_NONE);
}

}

extern "C" void kernel_launch(void* const* d_in, const int* in_sizes, int n_in, void* d_out, int out_size) {
    static EncodeFn enc = nullptr;
    if (!enc) {
        void* fn = nullptr;
        cudaDriverEntryPointQueryResult st;
        cudaGetDriverEntryPoint("cuTensorMapEncodeTiled", &fn, cudaEnableDefault, &st);
        enc = (EncodeFn)fn;
        cudaFuncSetAttribute(fused_gqa_kernel, cudaFuncAttributeMaxDynamicSharedMemorySize, SMEM_BYTES);
    }
    Params P;
    for (int blk = 0; blk < 2; blk++) {
        const void* x = d_in[blk * 5 + 0];
        const void* k = d_in[blk * 5 + 1];
        const void* v = d_in[blk * 5 + 2];
        const void* wq = d_in[blk * 5 + 3];
        const void* wo = d_in[blk * 5 + 4];
        make_map(enc, &P.x[blk], x, kD, kB * kSq, 64);
        make_map3(enc, &P.wq[blk], wq, kHq * kDh, kD, 32, 2);
        make_map3(enc, &P.k[blk], k, kDh, (uint64_t)kB * kHkv * kSk, 128, 2);
        make_map3(enc, &P.v[blk], v, kDh, (uint64_t)kB * kHkv * kSk, 128, 2);
        make_map3(enc, &P.wo[blk], wo, kD, kHq * kDh, 64, 2);
        make_map(enc, &P.wo8[blk], wo, kD, kHq * kDh, 128);
        P.kp[blk] = (const __nv_bfloat16*)k;
        P.vp[blk] = (const __nv_bfloat16*)v;
        P.wop[blk] = (const __nv_bfloat16*)wo;
    }
    P.out = (__nv_bfloat16*)d_out;
    fused_gqa_kernel<<<128, 384, SMEM_BYTES>>>(P);
}
```
